```python
import torch

def _softmax(x, axis=-1):
    return torch.softmax(x, dim=axis)
def _gelu(x):
    return torch.nn.functional.gelu(x, approximate="tanh")
def _silu(x):
    return torch.nn.functional.silu(x)
def _sigmoid(x):
    return torch.sigmoid(x)
def _layernorm(x, axis=-1, eps=1e-5):
    m = x.mean(dim=axis, keepdim=True)
    v = x.var(dim=axis, keepdim=True, unbiased=False)
    return (x - m) / torch.sqrt(v + eps)
def _scatter_add(tgt, idx, src, axis=0):
    return tgt.clone().index_add_(axis, idx, src)
def _segment_sum(src, seg, n):
    out = torch.zeros((n,) + src.shape[1:], dtype=src.dtype)
    return out.index_add_(0, seg, src)
def _pad(x, pw):
    flat = tuple(v for pair in reversed(pw) for v in pair)
    return torch.nn.functional.pad(x, flat)

kernel_name = 'gated_mix__sliding_block__dense_activation_relu__prompt'

def setup_inputs():

    _w = (lambda a: (lambda t: t.to(torch.bfloat16) if t.is_floating_point() else t)(torch.as_tensor(a)))
    def _A_setup():
        B, S, D = 1, 2048, 512
        return {
            "x": _w((lambda *s: torch.randn(*s, dtype=torch.bfloat16) * 0.05)(B, S, D)),
            "wqkv": _w((lambda *s: torch.randn(*s, dtype=torch.bfloat16) * 1.6)(D, 3 * D)),
            "wo": _w((lambda *s: torch.randn(*s, dtype=torch.bfloat16) * 0.05)(D, D)),
        }
    _A_in = _A_setup()

    def _B_setup():
        B, S, D, Dff = 1, 2048, 512, 1792
        return {
            "x": _w((lambda *s: torch.randn(*s, dtype=torch.bfloat16) * 0.05)(B, S, D)),
            "w1": _w((lambda *s: torch.randn(*s, dtype=torch.bfloat16) * 0.2)(D, Dff)),
            "w2": _w((lambda *s: torch.randn(*s, dtype=torch.bfloat16) * 0.2)(Dff, D)),
        }
    _B_in = _B_setup()

    return {
        "A_x": _A_in["x"],
        "A_wqkv": _A_in["wqkv"],
        "A_wo": _A_in["wo"],
        "B_x": _B_in["x"],
        "B_w1": _B_in["w1"],
        "B_w2": _B_in["w2"],
        "gate_w": _w((lambda *s: torch.randn(*s, dtype=torch.bfloat16) * 0.05)(512) * 16.0),
    }

def reference(A_x, A_wqkv, A_wo, B_x, B_w1, B_w2, gate_w):
    def _A_ref(x, wqkv, wo):
        B, S, D = x.shape
        H = 32; Dh = D // H; W = 256
        qkv = (lambda x, *d: x.permute(*d))((x @ wqkv).reshape(B, S, 3, H, Dh), 2, 0, 3, 1, 4)
        q, k, v = qkv[0], qkv[1], qkv[2]
        scores = torch.einsum("bhqd,bhkd->bhqk", q, k) * (Dh ** -0.5)
        idx = torch.arange(S)
        mask = (idx[:, None] - idx[None, :] >= 0) & (idx[:, None] - idx[None, :] < W)
        scores = torch.where(mask[None, None], scores, -1e9)
        p = _softmax(scores, axis=-1)
        o = torch.einsum("bhqk,bhkd->bhqd", p, v)
        return (lambda x, *d: x.permute(*d))(o, 0, 2, 1, 3).reshape(B, S, D) @ wo

    def _B_ref(x, w1, w2):
        h = torch.einsum("bsd,df->bsf", x, w1)
        zero = torch.zeros_like(h)
        h = torch.maximum(h, zero)
        return torch.einsum("bsf,fd->bsd", h, w2)

    x = A_x
    g = _sigmoid((x * gate_w).sum(-1, keepdims=True))
    a = _A_ref(x, A_wqkv, A_wo)
    b = _B_ref(x, B_w1, B_w2)
    return g * a + (1 - g) * b
```

```cpp
#include <cuda_runtime.h>
#include <cuda_bf16.h>
#include <cuda.h>
#include <stdint.h>

#define DEVI __device__ __forceinline__

namespace {

constexpr int SEQ = 2048, DM = 512, DFF = 1792, KHO = 2304;
constexpr int NA = 5, NB = 6, SLOT = 16384, KVBUF = 24576;
constexpr int OFF_A = 0, OFF_B = NA * SLOT, OFF_KV = OFF_B + NB * SLOT, OFF_BAR = OFF_KV + 2 * KVBUF;
constexpr int SMEM_BYTES = OFF_BAR + 512 + 1024;
constexpr uint32_t TIMEOUT = 1u << 28;
constexpr int FS = 8;

constexpr int BAR_FULLA = 0, BAR_EMPTYA = BAR_FULLA + NA, BAR_FULLB = BAR_EMPTYA + NA, BAR_EMPTYB = BAR_FULLB + NB,
              BAR_KVFULL = BAR_EMPTYB + NB, BAR_STG = BAR_KVFULL + 2;

__device__ __align__(1024) uint8_t g_kv[32 * SEQ * 64];
__device__ __align__(1024) uint4 g_q[16 * 8 * 4 * 8 * 32];
__device__ __align__(1024) __nv_bfloat16 g_ho[SEQ * KHO];
__device__ __align__(1024) float4 g_part[16 * 2 * 4 * 4 * 8 * 8 * 32];
__device__ float g_gate[SEQ];
__device__ unsigned g_flag_kv[128 * FS], g_flag_h[128 * FS], g_flag_o[128 * FS], g_flag_g[16 * FS], g_flag_p[1024 * FS];
__device__ unsigned g_epoch, g_done;

struct Params {
  CUtensorMap tmX, tmWqkv, tmW1a, tmW1b, tmW2, tmWo, tmHO, tmHOs;
  const __nv_bfloat16* x;
  const __nv_bfloat16* gate_w;
  const __nv_bfloat16* w1;
  const __nv_bfloat16* w2;
  const __nv_bfloat16* wo;
  __nv_bfloat16* out;
};

DEVI uint32_t smem_u32(const void* p) { return (uint32_t)__cvta_generic_to_shared(p); }
DEVI uint32_t clk32() { uint32_t c; asm volatile("mov.u32 %0, %%clock;" : "=r"(c)); return c; }
DEVI void mbar_init(uint32_t bar, uint32_t cnt) { asm volatile("mbarrier.init.shared::cta.b64 [%0], %1;" ::"r"(bar), "r"(cnt)); }
DEVI void mbar_expect_tx(uint32_t bar, uint32_t bytes) { asm volatile("mbarrier.arrive.expect_tx.shared::cta.b64 _, [%0], %1;" ::"r"(bar), "r"(bytes) : "memory"); }
DEVI void mbar_arrive(uint32_t bar) { asm volatile("mbarrier.arrive.shared::cta.b64 _, [%0];" ::"r"(bar) : "memory"); }
DEVI void mbar_arrive_n(uint32_t bar, uint32_t n) { asm volatile("mbarrier.arrive.shared::cta.b64 _, [%0], %1;" ::"r"(bar), "r"(n) : "memory"); }
DEVI void mbar_arrive_cluster(uint32_t bar, uint32_t cta) {
  asm volatile("{ .reg .b32 ra; mapa.shared::cluster.u32 ra, %0, %1; mbarrier.arrive.shared::cluster.b64 _, [ra]; }" ::"r"(bar), "r"(cta) : "memory");
}
DEVI bool mbar_try(uint32_t bar, uint32_t parity) {
  uint32_t ok;
  asm volatile("{ .reg .pred p; mbarrier.try_wait.parity.shared::cta.b64 p, [%1], %2; selp.u32 %0, 1, 0, p; }" : "=r"(ok) : "r"(bar), "r"(parity) : "memory");
  return ok;
}
DEVI void mbar_wait(uint32_t bar, uint32_t parity, uint32_t t0) {
  while (!mbar_try(bar, parity)) { if (clk32() - t0 > TIMEOUT) break; }
}
DEVI unsigned ld_acquire(const unsigned* p) { unsigned v; asm volatile("ld.acquire.gpu.global.u32 %0, [%1];" : "=r"(v) : "l"(p) : "memory"); return v; }
DEVI void flag_wait(const unsigned* p, unsigned target, uint32_t t0) {
  while ((int)(ld_acquire(p) - target) < 0) { if (clk32() - t0 > TIMEOUT) break; }
}
DEVI void flag_add(unsigned* p) { asm volatile("red.release.gpu.global.add.u32 [%0], 1;" ::"l"(p) : "memory"); }
DEVI void fence_async_smem() { asm volatile("fence.proxy.async.shared::cta;" ::: "memory"); }
DEVI void fence_async_all() { asm volatile("fence.proxy.async;" ::: "memory"); }
DEVI void tma_load_2d(uint32_t dst, const CUtensorMap* m, int c0, int c1, uint32_t bar) {
  asm volatile("cp.async.bulk.tensor.2d.shared::cluster.global.mbarrier::complete_tx::bytes [%0], [%1, {%3, %4}], [%2];" ::"r"(dst), "l"(m), "r"(bar), "r"(c0), "r"(c1) : "memory");
}
DEVI void tma_load_3d_mc(uint32_t dst, const CUtensorMap* m, int c0, int c1, int c2, uint32_t bar) {
  asm volatile("cp.async.bulk.tensor.3d.shared::cluster.global.mbarrier::complete_tx::bytes.multicast::cluster [%0], [%1, {%3, %4, %5}], [%2], %6;"
               ::"r"(dst), "l"(m), "r"(bar), "r"(c0), "r"(c1), "r"(c2), "h"((uint16_t)3) : "memory");
}
DEVI void tma_store_2d(const CUtensorMap* m, int c0, int c1, uint32_t src) {
  asm volatile("cp.async.bulk.tensor.2d.global.shared::cta.bulk_group [%0, {%1, %2}], [%3];" ::"l"(m), "r"(c0), "r"(c1), "r"(src) : "memory");
}
DEVI void bulk_store(void* dst, uint32_t src, uint32_t bytes) {
  asm volatile("cp.async.bulk.global.shared::cta.bulk_group [%0], [%1], %2;" ::"l"(dst), "r"(src), "r"(bytes) : "memory");
}
DEVI void bulk_load(uint32_t dst, const void* src, uint32_t bytes, uint32_t bar) {
  asm volatile("cp.async.bulk.shared::cluster.global.mbarrier::complete_tx::bytes [%0], [%1], %2, [%3];" ::"r"(dst), "l"(src), "r"(bytes), "r"(bar) : "memory");
}
DEVI void bulk_commit() { asm volatile("cp.async.bulk.commit_group;" ::: "memory"); }
DEVI void bulk_wait_read() { asm volatile("cp.async.bulk.wait_group.read 0;" ::: "memory"); }
DEVI void bulk_wait_all() { asm volatile("cp.async.bulk.wait_group 0;" ::: "memory"); }
DEVI void l2_prefetch(const void* p, uint32_t bytes) { asm volatile("cp.async.bulk.prefetch.L2.global [%0], %1;" ::"l"(p), "r"(bytes) : "memory"); }
DEVI void cluster_sync() { asm volatile("barrier.cluster.arrive.release.aligned; barrier.cluster.wait.acquire.aligned;" ::: "memory"); }
DEVI void named_bar(int id, int n) { asm volatile("bar.sync %0, %1;" ::"r"(id), "r"(n) : "memory"); }
DEVI void wgmma_fence() { asm volatile("wgmma.fence.sync.aligned;" ::: "memory"); }
DEVI void wgmma_commit() { asm volatile("wgmma.commit_group.sync.aligned;" ::: "memory"); }
template <int N> DEVI void wgmma_wait() { asm volatile("wgmma.wait_group.sync.aligned %0;" ::"n"(N) : "memory"); }
DEVI uint64_t make_desc(uint32_t addr, uint32_t lbo, uint32_t sbo) {
  return (uint64_t)((addr & 0x3FFFF) >> 4) | ((uint64_t)(lbo >> 4) << 16) | ((uint64_t)(sbo >> 4) << 32) | (1ull << 62);
}
DEVI uint32_t pack_bf16(float lo, float hi) { uint32_t r; asm("cvt.rn.bf16x2.f32 %0, %1, %2;" : "=r"(r) : "f"(hi), "f"(lo)); return r; }
DEVI void stsm_x4(uint32_t addr, uint32_t r0, uint32_t r1, uint32_t r2, uint32_t r3) {
  asm volatile("stmatrix.sync.aligned.m8n8.x4.shared.b16 [%0], {%1, %2, %3, %4};" ::"r"(addr), "r"(r0), "r"(r1), "r"(r2), "r"(r3) : "memory");
}
DEVI void ldsm_x4(uint32_t (&r)[4], uint32_t addr) {
  asm volatile("ldmatrix.sync.aligned.m8n8.x4.shared.b16 {%0, %1, %2, %3}, [%4];" : "=r"(r[0]), "=r"(r[1]), "=r"(r[2]), "=r"(r[3]) : "r"(addr) : "memory");
}
DEVI void ldsm_x4_t(uint32_t (&r)[4], uint32_t addr) {
  asm volatile("ldmatrix.sync.aligned.m8n8.x4.trans.shared.b16 {%0, %1, %2, %3}, [%4];" : "=r"(r[0]), "=r"(r[1]), "=r"(r[2]), "=r"(r[3]) : "r"(addr) : "memory");
}
DEVI void mma_acc(float* c, uint32_t a0, uint32_t a1, uint32_t a2, uint32_t a3, uint32_t b0, uint32_t b1) {
  asm("mma.sync.aligned.m16n8k16.row.col.f32.bf16.bf16.f32 {%0,%1,%2,%3}, {%4,%5,%6,%7}, {%8,%9}, {%0,%1,%2,%3};"
      : "+f"(c[0]), "+f"(c[1]), "+f"(c[2]), "+f"(c[3]) : "r"(a0), "r"(a1), "r"(a2), "r"(a3), "r"(b0), "r"(b1));
}
DEVI void mma_zero(float* c, const uint32_t (&a)[4], uint32_t b0, uint32_t b1) {
  asm("mma.sync.aligned.m16n8k16.row.col.f32.bf16.bf16.f32 {%0,%1,%2,%3}, {%4,%5,%6,%7}, {%8,%9}, {%10,%10,%10,%10};"
      : "=f"(c[0]), "=f"(c[1]), "=f"(c[2]), "=f"(c[3]) : "r"(a[0]), "r"(a[1]), "r"(a[2]), "r"(a[3]), "r"(b0), "r"(b1), "f"(0.f));
}
DEVI float ex2(float x) { float y; asm("ex2.approx.ftz.f32 %0, %1;" : "=f"(y) : "f"(x)); return y; }

DEVI void wgmma_n192(float (&d)[96], uint64_t da, uint64_t db, int sc) {
  asm volatile("{ .reg .pred p; setp.ne.b32 p, %98, 0;\n"
    "wgmma.mma_async.sync.aligned.m64n192k16.f32.bf16.bf16 {%0, %1, %2, %3, %4, %5, %6, %7, %8, %9, %10, %11, %12, %13, %14, %15, %16, %17, %18, %19, %20, %21, %22, %23, %24, %25, %26, %27, %28, %29, %30, %31, %32, %33, %34, %35, %36, %37, %38, %39, %40, %41, %42, %43, %44, %45, %46, %47, %48, %49, %50, %51, %52, %53, %54, %55, %56, %57, %58, %59, %60, %61, %62, %63, %64, %65, %66, %67, %68, %69, %70, %71, %72, %73, %74, %75, %76, %77, %78, %79, %80, %81, %82, %83, %84, %85, %86, %87, %88, %89, %90, %91, %92, %93, %94, %95}, %96, %97, p, 1, 1, 0, 1;\n}"
    : "+f"(d[0]), "+f"(d[1]), "+f"(d[2]), "+f"(d[3]), "+f"(d[4]), "+f"(d[5]), "+f"(d[6]), "+f"(d[7]), "+f"(d[8]), "+f"(d[9]), "+f"(d[10]), "+f"(d[11]), "+f"(d[12]), "+f"(d[13]), "+f"(d[14]), "+f"(d[15]), "+f"(d[16]), "+f"(d[17]), "+f"(d[18]), "+f"(d[19]), "+f"(d[20]), "+f"(d[21]), "+f"(d[22]), "+f"(d[23]), "+f"(d[24]), "+f"(d[25]), "+f"(d[26]), "+f"(d[27]), "+f"(d[28]), "+f"(d[29]), "+f"(d[30]), "+f"(d[31]), "+f"(d[32]), "+f"(d[33]), "+f"(d[34]), "+f"(d[35]), "+f"(d[36]), "+f"(d[37]), "+f"(d[38]), "+f"(d[39]), "+f"(d[40]), "+f"(d[41]), "+f"(d[42]), "+f"(d[43]), "+f"(d[44]), "+f"(d[45]), "+f"(d[46]), "+f"(d[47]), "+f"(d[48]), "+f"(d[49]), "+f"(d[50]), "+f"(d[51]), "+f"(d[52]), "+f"(d[53]), "+f"(d[54]), "+f"(d[55]), "+f"(d[56]), "+f"(d[57]), "+f"(d[58]), "+f"(d[59]), "+f"(d[60]), "+f"(d[61]), "+f"(d[62]), "+f"(d[63]), "+f"(d[64]), "+f"(d[65]), "+f"(d[66]), "+f"(d[67]), "+f"(d[68]), "+f"(d[69]), "+f"(d[70]), "+f"(d[71]), "+f"(d[72]), "+f"(d[73]), "+f"(d[74]), "+f"(d[75]), "+f"(d[76]), "+f"(d[77]), "+f"(d[78]), "+f"(d[79]), "+f"(d[80]), "+f"(d[81]), "+f"(d[82]), "+f"(d[83]), "+f"(d[84]), "+f"(d[85]), "+f"(d[86]), "+f"(d[87]), "+f"(d[88]), "+f"(d[89]), "+f"(d[90]), "+f"(d[91]), "+f"(d[92]), "+f"(d[93]), "+f"(d[94]), "+f"(d[95])
    : "l"(da), "l"(db), "r"(sc));
}
DEVI void wgmma_n128a(float (&d)[128], uint64_t da, uint64_t db, int sc) {
  asm volatile("{ .reg .pred p; setp.ne.b32 p, %66, 0;\n"
    "wgmma.mma_async.sync.aligned.m64n128k16.f32.bf16.bf16 {%0, %1, %2, %3, %4, %5, %6, %7, %8, %9, %10, %11, %12, %13, %14, %15, %16, %17, %18, %19, %20, %21, %22, %23, %24, %25, %26, %27, %28, %29, %30, %31, %32, %33, %34, %35, %36, %37, %38, %39, %40, %41, %42, %43, %44, %45, %46, %47, %48, %49, %50, %51, %52, %53, %54, %55, %56, %57, %58, %59, %60, %61, %62, %63}, %64, %65, p, 1, 1, 0, 1;\n}"
    : "+f"(d[0]), "+f"(d[1]), "+f"(d[2]), "+f"(d[3]), "+f"(d[4]), "+f"(d[5]), "+f"(d[6]), "+f"(d[7]), "+f"(d[8]), "+f"(d[9]), "+f"(d[10]), "+f"(d[11]), "+f"(d[12]), "+f"(d[13]), "+f"(d[14]), "+f"(d[15]), "+f"(d[16]), "+f"(d[17]), "+f"(d[18]), "+f"(d[19]), "+f"(d[20]), "+f"(d[21]), "+f"(d[22]), "+f"(d[23]), "+f"(d[24]), "+f"(d[25]), "+f"(d[26]), "+f"(d[27]), "+f"(d[28]), "+f"(d[29]), "+f"(d[30]), "+f"(d[31]), "+f"(d[32]), "+f"(d[33]), "+f"(d[34]), "+f"(d[35]), "+f"(d[36]), "+f"(d[37]), "+f"(d[38]), "+f"(d[39]), "+f"(d[40]), "+f"(d[41]), "+f"(d[42]), "+f"(d[43]), "+f"(d[44]), "+f"(d[45]), "+f"(d[46]), "+f"(d[47]), "+f"(d[48]), "+f"(d[49]), "+f"(d[50]), "+f"(d[51]), "+f"(d[52]), "+f"(d[53]), "+f"(d[54]), "+f"(d[55]), "+f"(d[56]), "+f"(d[57]), "+f"(d[58]), "+f"(d[59]), "+f"(d[60]), "+f"(d[61]), "+f"(d[62]), "+f"(d[63])
    : "l"(da), "l"(db), "r"(sc));
}
DEVI void wgmma_n128b(float (&d)[128], uint64_t da, uint64_t db, int sc) {
  asm volatile("{ .reg .pred p; setp.ne.b32 p, %66, 0;\n"
    "wgmma.mma_async.sync.aligned.m64n128k16.f32.bf16.bf16 {%0, %1, %2, %3, %4, %5, %6, %7, %8, %9, %10, %11, %12, %13, %14, %15, %16, %17, %18, %19, %20, %21, %22, %23, %24, %25, %26, %27, %28, %29, %30, %31, %32, %33, %34, %35, %36, %37, %38, %39, %40, %41, %42, %43, %44, %45, %46, %47, %48, %49, %50, %51, %52, %53, %54, %55, %56, %57, %58, %59, %60, %61, %62, %63}, %64, %65, p, 1, 1, 0, 1;\n}"
    : "+f"(d[64]), "+f"(d[65]), "+f"(d[66]), "+f"(d[67]), "+f"(d[68]), "+f"(d[69]), "+f"(d[70]), "+f"(d[71]), "+f"(d[72]), "+f"(d[73]), "+f"(d[74]), "+f"(d[75]), "+f"(d[76]), "+f"(d[77]), "+f"(d[78]), "+f"(d[79]), "+f"(d[80]), "+f"(d[81]), "+f"(d[82]), "+f"(d[83]), "+f"(d[84]), "+f"(d[85]), "+f"(d[86]), "+f"(d[87]), "+f"(d[88]), "+f"(d[89]), "+f"(d[90]), "+f"(d[91]), "+f"(d[92]), "+f"(d[93]), "+f"(d[94]), "+f"(d[95]), "+f"(d[96]), "+f"(d[97]), "+f"(d[98]), "+f"(d[99]), "+f"(d[100]), "+f"(d[101]), "+f"(d[102]), "+f"(d[103]), "+f"(d[104]), "+f"(d[105]), "+f"(d[106]), "+f"(d[107]), "+f"(d[108]), "+f"(d[109]), "+f"(d[110]), "+f"(d[111]), "+f"(d[112]), "+f"(d[113]), "+f"(d[114]), "+f"(d[115]), "+f"(d[116]), "+f"(d[117]), "+f"(d[118]), "+f"(d[119]), "+f"(d[120]), "+f"(d[121]), "+f"(d[122]), "+f"(d[123]), "+f"(d[124]), "+f"(d[125]), "+f"(d[126]), "+f"(d[127])
    : "l"(da), "l"(db), "r"(sc));
}

template <int N> DEVI void wgmma_tile(float (&d)[N / 2], uint64_t da, uint64_t db, int sc) {
  if constexpr (N == 192) wgmma_n192(d, da, db, sc);
  else { wgmma_n128a(d, da, db, sc); wgmma_n128b(d, da, db + (4096 >> 4), sc); }
}

DEVI int h_start(int j) { return (j >> 2) * 14 + ((0xB840 >> ((j & 3) * 4)) & 15); }
DEVI int h_count(int j) { return (j & 2) ? 3 : 4; }
DEVI int o_nchunks(int j) { return (j & 2) ? 10 : 8; }
DEVI int o_chunk(int j, int i) {
  const int jj = j & 3, base = (j >> 2) * 14, n = o_nchunks(j);
  if (i == n - 2) return 28 + j;
  if (i == n - 1) return 28 + (j ^ 1);
  const uint32_t t = jj == 0 ? 0x543210u : jj == 1 ? 0x107654u : jj == 2 ? 0x76DCBA98u : 0x32A98DCBu;
  return base + (int)((t >> (4 * i)) & 15);
}
DEVI int h_owner(int c) {
  const int g = c >= 14, r = c - 14 * g;
  return 4 * g + (r < 4 ? 0 : r < 8 ? 1 : r < 11 ? 2 : 3);
}

struct Ring { int ai, bi; uint32_t aph, bph; };

template <int N>
DEVI void mainloop(float (&acc)[N / 2], int nk, Ring& r, uint32_t sbase, int wg, int lane, uint32_t peer, uint32_t t0) {
  const uint32_t bars = sbase + OFF_BAR;
  int pa = -1, pb = -1;
#pragma unroll
  for (int i = 0; i < N / 2; i++) acc[i] = 0.f;
  for (int kc = 0; kc < nk; kc++) {
    mbar_wait(bars + 8 * (BAR_FULLA + r.ai), r.aph, t0);
    const uint32_t a_addr = sbase + OFF_A + r.ai * SLOT + wg * 8192;
#pragma unroll
    for (int half = 0; half < 2; half++) {
      mbar_wait(bars + 8 * (BAR_FULLB + r.bi), r.bph, t0);
      const uint32_t b_addr = sbase + OFF_B + r.bi * SLOT;
      wgmma_fence();
      wgmma_tile<N>(acc, make_desc(a_addr + half * 64, 16, 1024), make_desc(b_addr, 2048, 1024), 1);
      wgmma_tile<N>(acc, make_desc(a_addr + half * 64 + 32, 16, 1024), make_desc(b_addr + 8192, 2048, 1024), 1);
      wgmma_commit();
      wgmma_wait<1>();
      if (pb >= 0) {
        if (lane == 0) mbar_arrive(bars + 8 * (BAR_EMPTYB + pb));
        if (lane == 1) mbar_arrive_cluster(bars + 8 * (BAR_EMPTYB + pb), peer);
        if (half == 0 && lane == 2) mbar_arrive(bars + 8 * (BAR_EMPTYA + pa));
      }
      pb = r.bi;
      if (++r.bi == NB) { r.bi = 0; r.bph ^= 1; }
    }
    pa = r.ai;
    if (++r.ai == NA) { r.ai = 0; r.aph ^= 1; }
  }
  wgmma_wait<0>();
  if (lane == 0) mbar_arrive(bars + 8 * (BAR_EMPTYB + pb));
  if (lane == 1) mbar_arrive_cluster(bars + 8 * (BAR_EMPTYB + pb), peer);
  if (lane == 2) mbar_arrive(bars + 8 * (BAR_EMPTYA + pa));
}

template <int NCH>
DEVI void epilogue_h(float (&acc)[NCH * 32], const Ring& r, uint32_t sbase, int wg, int wi, int lane, float s0, float s1, uint32_t t0) {
  const uint32_t bars = sbase + OFF_BAR;
  int ai = r.ai; uint32_t aph = r.aph;
  const int mi = lane >> 3;
  const int row = wg * 64 + wi * 16 + (lane & 7) + 8 * (mi & 1);
#pragma unroll
  for (int c = 0; c < NCH; c++) {
    mbar_wait(bars + 8 * (BAR_FULLA + ai), aph, t0);
    const uint32_t base = sbase + OFF_A + ai * SLOT + row * 128;
#pragma unroll
    for (int tp = 0; tp < 4; tp++) {
      const int t = c * 8 + tp * 2;
      const uint32_t r0 = pack_bf16(fmaxf(acc[4 * t + 0], 0.f) * s0, fmaxf(acc[4 * t + 1], 0.f) * s0);
      const uint32_t r1 = pack_bf16(fmaxf(acc[4 * t + 2], 0.f) * s1, fmaxf(acc[4 * t + 3], 0.f) * s1);
      const uint32_t r2 = pack_bf16(fmaxf(acc[4 * t + 4], 0.f) * s0, fmaxf(acc[4 * t + 5], 0.f) * s0);
      const uint32_t r3 = pack_bf16(fmaxf(acc[4 * t + 6], 0.f) * s1, fmaxf(acc[4 * t + 7], 0.f) * s1);
      stsm_x4(base + (((tp * 2 + (mi >> 1)) ^ (lane & 7)) << 4), r0, r1, r2, r3);
    }
    if (++ai == NA) { ai = 0; aph ^= 1; }
  }
}

constexpr float SC = 0.25f * 1.4426950408889634f;

struct AttnT { float o[8]; float m0, m1, l0, l1; };

DEVI void qk16(float (&s)[8], const uint32_t (&q)[4], const uint32_t (&k)[4]) {
  mma_zero(&s[0], q, k[0], k[1]);
  mma_zero(&s[4], q, k[2], k[3]);
}
DEVI void pv16(float (&o)[8], uint32_t a0, uint32_t a1, uint32_t a2, uint32_t a3, const uint32_t (&v)[4]) {
  mma_acc(&o[0], a0, a1, a2, a3, v[0], v[1]);
  mma_acc(&o[4], a0, a1, a2, a3, v[2], v[3]);
}
DEVI float quad_max(float v) {
  v = fmaxf(v, __shfl_xor_sync(0xffffffffu, v, 1));
  return fmaxf(v, __shfl_xor_sync(0xffffffffu, v, 2));
}
template <int NBK>
DEVI void softmax_blocks(AttnT& t, float (&s)[NBK][8], uint32_t (&p)[NBK][4]) {
  float mx0 = t.m0, mx1 = t.m1;
#pragma unroll
  for (int b = 0; b < NBK; b++) {
    mx0 = fmaxf(mx0, fmaxf(fmaxf(s[b][0], s[b][1]), fmaxf(s[b][4], s[b][5])));
    mx1 = fmaxf(mx1, fmaxf(fmaxf(s[b][2], s[b][3]), fmaxf(s[b][6], s[b][7])));
  }
  mx0 = quad_max(mx0); mx1 = quad_max(mx1);
  const float a0 = ex2((t.m0 - mx0) * SC), a1 = ex2((t.m1 - mx1) * SC);
  t.m0 = mx0; t.m1 = mx1;
  const float n0 = -mx0 * SC, n1 = -mx1 * SC;
  float l0 = t.l0 * a0, l1 = t.l1 * a1;
  t.o[0] *= a0; t.o[1] *= a0; t.o[4] *= a0; t.o[5] *= a0;
  t.o[2] *= a1; t.o[3] *= a1; t.o[6] *= a1; t.o[7] *= a1;
#pragma unroll
  for (int b = 0; b < NBK; b++) {
    const float e0 = ex2(fmaf(s[b][0], SC, n0)), e1 = ex2(fmaf(s[b][1], SC, n0));
    const float e2 = ex2(fmaf(s[b][2], SC, n1)), e3 = ex2(fmaf(s[b][3], SC, n1));
    const float e4 = ex2(fmaf(s[b][4], SC, n0)), e5 = ex2(fmaf(s[b][5], SC, n0));
    const float e6 = ex2(fmaf(s[b][6], SC, n1)), e7 = ex2(fmaf(s[b][7], SC, n1));
    l0 += (e0 + e1) + (e4 + e5);
    l1 += (e2 + e3) + (e6 + e7);
    p[b][0] = pack_bf16(e0, e1); p[b][1] = pack_bf16(e2, e3);
    p[b][2] = pack_bf16(e4, e5); p[b][3] = pack_bf16(e6, e7);
  }
  t.l0 = l0; t.l1 = l1;
}

template <int NBK>
DEVI void attn_full(AttnT& t0, AttnT& t1, const uint32_t (&q0)[4], const uint32_t (&q1)[4], uint32_t kaddr, uint32_t vaddr) {
  float s0[NBK][8], s1[NBK][8];
#pragma unroll
  for (int b = 0; b < NBK; b++) {
    uint32_t k[4]; ldsm_x4(k, kaddr + b * 1024);
    qk16(s0[b], q0, k); qk16(s1[b], q1, k);
  }
  uint32_t p0[NBK][4], p1[NBK][4];
  softmax_blocks<NBK>(t0, s0, p0);
  softmax_blocks<NBK>(t1, s1, p1);
#pragma unroll
  for (int b = 0; b < NBK; b++) {
    uint32_t v[4]; ldsm_x4_t(v, vaddr + b * 1024);
    pv16(t0.o, p0[b][0], p0[b][1], p0[b][2], p0[b][3], v);
    pv16(t1.o, p1[b][0], p1[b][1], p1[b][2], p1[b][3], v);
  }
}

DEVI void attn_edge(AttnT& t, const uint32_t (&q)[4], uint32_t kbase, uint32_t vbase, int bF, int bL, int bX, bool vF, bool vX,
                    bool pe0, bool pe1) {
  float s[2][8], f[8];
  uint32_t k[4];
  const float NINF = __int_as_float(0xff800000);
  ldsm_x4(k, kbase + bL * 1024); qk16(s[0], q, k);
  if (vF) { ldsm_x4(k, kbase + bF * 1024); qk16(f, q, k); }
  else {
#pragma unroll
    for (int i = 0; i < 8; i++) f[i] = NINF;
  }
  if (vX) { ldsm_x4(k, kbase + bX * 1024); qk16(s[1], q, k); }
  else {
#pragma unroll
    for (int i = 0; i < 8; i++) s[1][i] = NINF;
  }
  s[0][0] = pe0 ? s[0][0] : f[0]; s[0][1] = pe1 ? s[0][1] : f[1];
  s[0][4] = f[4]; s[0][5] = f[5];
  s[0][6] = pe0 ? s[0][6] : f[6]; s[0][7] = pe1 ? s[0][7] : f[7];
  uint32_t p[2][4];
  softmax_blocks<2>(t, s, p);
  const uint32_t mL = (pe0 ? 0xFFFFu : 0u) | (pe1 ? 0xFFFF0000u : 0u);
  uint32_t v[4];
  ldsm_x4_t(v, vbase + bL * 1024);
  pv16(t.o, p[0][0] & mL, p[0][1], 0u, p[0][3] & mL, v);
  if (vF) { ldsm_x4_t(v, vbase + bF * 1024); pv16(t.o, p[0][0] & ~mL, 0u, p[0][2], p[0][3] & ~mL, v); }
  if (vX) { ldsm_x4_t(v, vbase + bX * 1024); pv16(t.o, p[1][0], p[1][1], p[1][2], p[1][3], v); }
}

DEVI void attn_store(AttnT& t, float g0, float g1, __nv_bfloat16* dst  ) {
  float l0 = t.l0, l1 = t.l1;
  l0 += __shfl_xor_sync(0xffffffffu, l0, 1); l0 += __shfl_xor_sync(0xffffffffu, l0, 2);
  l1 += __shfl_xor_sync(0xffffffffu, l1, 1); l1 += __shfl_xor_sync(0xffffffffu, l1, 2);
  const float c0 = g0 / l0, c1 = g1 / l1;
  *(uint32_t*)(dst) = pack_bf16(t.o[0] * c0, t.o[1] * c0);
  *(uint32_t*)(dst + 8) = pack_bf16(t.o[4] * c0, t.o[5] * c0);
  *(uint32_t*)(dst + 8 * KHO) = pack_bf16(t.o[2] * c1, t.o[3] * c1);
  *(uint32_t*)(dst + 8 * KHO + 8) = pack_bf16(t.o[6] * c1, t.o[7] * c1);
}

__global__ void __cluster_dims__(2, 1, 1) __launch_bounds__(512, 1) fused_kernel(const __grid_constant__ Params P) {
  extern __shared__ uint8_t smem_raw[];
  const uint32_t sbase = (smem_u32(smem_raw) + 1023u) & ~1023u;
  const uint32_t bars = sbase + OFF_BAR;
  const int tid = threadIdx.x, warp = tid >> 5, lane = tid & 31;
  const uint32_t rank = blockIdx.x & 1, peer = rank ^ 1;
  const int j = (blockIdx.x >> 1) & 7, rb = ((blockIdx.x >> 4) << 1) | rank;
  const uint32_t t0 = clk32();

  if (tid == 0) {
    for (int s = 0; s < NA; s++) { mbar_init(bars + 8 * (BAR_FULLA + s), 1); mbar_init(bars + 8 * (BAR_EMPTYA + s), 10); }
    for (int s = 0; s < NB; s++) { mbar_init(bars + 8 * (BAR_FULLB + s), 1); mbar_init(bars + 8 * (BAR_EMPTYB + s), 16); }
    for (int s = 0; s < 2; s++) { mbar_init(bars + 8 * (BAR_KVFULL + s), 1); mbar_init(bars + 8 * (BAR_STG + s), 4); }
    asm volatile("fence.mbarrier_init.release.cluster;" ::: "memory");
  }
  const unsigned ep1 = *(volatile unsigned*)&g_epoch + 1;
  __syncthreads();
  cluster_sync();

  const int hs = h_start(j), hn = h_count(j), on = o_nchunks(j);

  if (warp < 8) {
    asm volatile("setmaxnreg.inc.sync.aligned.u32 168;");
    const int wg = warp >> 2, wi = warp & 3;
    Ring r{0, 0, 0u, 0u};
    {
      float acc[96];
      mainloop<192>(acc, 8, r, sbase, wg, lane, peer, t0);
      uint4* qd = g_q + (((rb * 8 + j) * 4) * 8 + warp) * 32 + lane;
#pragma unroll
      for (int hh = 0; hh < 4; hh++) {
        const int t = 2 * hh;
        uint4 v;
        v.x = pack_bf16(acc[4 * t + 0], acc[4 * t + 1]); v.y = pack_bf16(acc[4 * t + 2], acc[4 * t + 3]);
        v.z = pack_bf16(acc[4 * t + 4], acc[4 * t + 5]); v.w = pack_bf16(acc[4 * t + 6], acc[4 * t + 7]);
        qd[hh * 256] = v;
      }
      const int s0 = r.ai, s1 = (r.ai + 1 == NA) ? 0 : r.ai + 1;
      const uint32_t ph1 = (r.ai + 1 == NA) ? r.aph ^ 1 : r.aph;
      mbar_wait(bars + 8 * (BAR_FULLA + s0), r.aph, t0);
      mbar_wait(bars + 8 * (BAR_FULLA + s1), ph1, t0);
      const int mi = lane >> 3;
      const int row = warp * 16 + (lane & 7) + 8 * (mi & 1);
      const int sw = (row >> 1) & 3;
#pragma unroll
      for (int hh = 0; hh < 4; hh++) {
        const uint32_t base = sbase + OFF_A + (hh < 2 ? s0 : s1) * SLOT + (hh & 1) * 8192 + row * 64;
#pragma unroll
        for (int kv = 0; kv < 2; kv++) {
          const int t = 8 + kv * 8 + 2 * hh;
          stsm_x4(base + (((kv * 2 + (mi >> 1)) ^ sw) << 4),
                  pack_bf16(acc[4 * t + 0], acc[4 * t + 1]), pack_bf16(acc[4 * t + 2], acc[4 * t + 3]),
                  pack_bf16(acc[4 * t + 4], acc[4 * t + 5]), pack_bf16(acc[4 * t + 6], acc[4 * t + 7]));
        }
      }
      fence_async_smem();
      __syncwarp();
      if (lane == 0) { mbar_arrive(bars + 8 * (BAR_STG + wg)); mbar_arrive(bars + 8 * (BAR_EMPTYA + s0)); mbar_arrive(bars + 8 * (BAR_EMPTYA + s1)); }
      for (int i = 0; i < 2; i++) if (++r.ai == NA) { r.ai = 0; r.aph ^= 1; }
    }
    const int row0 = rb * 128 + warp * 16 + (lane >> 2);
    {
      if (lane == 0) flag_wait(&g_flag_g[rb * FS], ep1 * 32, t0);
      __syncwarp();
      const float s0 = 1.f - __ldcg(&g_gate[row0]), s1 = 1.f - __ldcg(&g_gate[row0 + 8]);
      if (hn == 4) {
        float acc[128];
        mainloop<256>(acc, 8, r, sbase, wg, lane, peer, t0);
        epilogue_h<4>(acc, r, sbase, wg, wi, lane, s0, s1, t0);
      } else {
        float acc[96];
        mainloop<192>(acc, 8, r, sbase, wg, lane, peer, t0);
        epilogue_h<3>(acc, r, sbase, wg, wi, lane, s0, s1, t0);
      }
      fence_async_smem();
      named_bar(1 + wg, 128);
      if (lane == 0) mbar_arrive(bars + 8 * (BAR_STG + wg));
    }
    {
      float acc[128];
      mainloop<256>(acc, on, r, sbase, wg, lane, peer, t0);
      const int nh = j & 1, kq = j >> 1;
      float own[32];
      float4* pbase = g_part + (size_t)((rb * 2 + nh) * 4) * (4 * 8 * 8 * 32);
#pragma unroll
      for (int s = 0; s < 4; s++) {
        if (s == kq) {
#pragma unroll
          for (int i = 0; i < 32; i++) own[i] = acc[32 * s + i];
        } else {
          float4* d = pbase + ((s * 4 + kq) * 8 + warp) * 256 + lane;
#pragma unroll
          for (int i = 0; i < 8; i++) __stcg(d + i * 32, make_float4(acc[32 * s + 4 * i], acc[32 * s + 4 * i + 1], acc[32 * s + 4 * i + 2], acc[32 * s + 4 * i + 3]));
        }
      }
      __threadfence();
      __syncwarp();
      unsigned* fb = g_flag_p + ((rb * 2 + nh) * 4) * 8 * FS;
      if (lane < 4 && lane != kq) flag_add(fb + (lane * 8 + warp) * FS);
      if (lane == 0) flag_wait(fb + (kq * 8 + warp) * FS, ep1 * 3, t0);
      __syncwarp();
#pragma unroll
      for (int s = 0; s < 4; s++) {
        if (s != kq) {
          const float4* d = pbase + ((kq * 4 + s) * 8 + warp) * 256 + lane;
#pragma unroll
          for (int i = 0; i < 8; i++) {
            const float4 v = __ldcg(d + i * 32);
            own[4 * i] += v.x; own[4 * i + 1] += v.y; own[4 * i + 2] += v.z; own[4 * i + 3] += v.w;
          }
        }
      }
      __nv_bfloat16* o = P.out + (size_t)row0 * DM + nh * 256 + kq * 64 + (lane & 3) * 2;
#pragma unroll
      for (int i = 0; i < 8; i++) {
        *(uint32_t*)(o + i * 8) = pack_bf16(own[4 * i], own[4 * i + 1]);
        *(uint32_t*)(o + 8 * DM + i * 8) = pack_bf16(own[4 * i + 2], own[4 * i + 3]);
      }
    }
    if (tid == 0) {
      const unsigned old = atomicAdd(&g_done, 1u);
      if (old == gridDim.x - 1) { g_done = 0; *(volatile unsigned*)&g_epoch = ep1; }
    }
    __syncwarp();
    cluster_sync();
  } else if (warp < 12) {
    const int aw = warp - 8;
    {
      const uint4* gw = (const uint4*)P.gate_w;
      const uint4 w0 = __ldg(gw + lane), w1 = __ldg(gw + 32 + lane);
#pragma unroll
      for (int i = 0; i < 4; i++) {
        const int row = rb * 128 + j * 16 + aw * 4 + i;
        const uint4* xr = (const uint4*)(P.x + (size_t)row * DM);
        const uint4 x0 = __ldg(xr + lane), x1 = __ldg(xr + 32 + lane);
        const uint32_t xa[8] = {x0.x, x0.y, x0.z, x0.w, x1.x, x1.y, x1.z, x1.w};
        const uint32_t wa[8] = {w0.x, w0.y, w0.z, w0.w, w1.x, w1.y, w1.z, w1.w};
        float z = 0.f;
#pragma unroll
        for (int e = 0; e < 8; e++) {
          z = fmaf(__uint_as_float(xa[e] << 16), __uint_as_float(wa[e] << 16), z);
          z = fmaf(__uint_as_float(xa[e] & 0xffff0000u), __uint_as_float(wa[e] & 0xffff0000u), z);
        }
#pragma unroll
        for (int o = 16; o > 0; o >>= 1) z += __shfl_xor_sync(0xffffffffu, z, o);
        if (lane == 0) __stcg(&g_gate[row], 1.f / (1.f + __expf(-z)));
      }
      if (lane == 0) flag_add(&g_flag_g[rb * FS]);
      if (lane == 0) {
        const int b = blockIdx.x;
        if (aw == 0) l2_prefetch((const uint8_t*)P.w1 + b * 14336, 14336);
        if (aw == 1) l2_prefetch((const uint8_t*)P.w2 + b * 14336, 14336);
        if (aw == 2) l2_prefetch((const uint8_t*)P.wo + b * 4096, 4096);
      }
    }
    const int nblk = rb >= 2 ? 3 : rb + 1;
    const int bmin = (3 - nblk) * 8;
    const uint32_t kvbytes = nblk * 8192;
    const uint8_t* kvsrc = g_kv + ((size_t)(4 * j) * SEQ + (rb + 1 - nblk) * 128) * 64;
    if (tid == 256) {
      for (int i = 0; i < nblk; i++) flag_wait(&g_flag_kv[((rb - i) * 8 + j) * FS], ep1 * 2, t0);
      fence_async_all();
      for (int h = 0; h < 2; h++) {
        mbar_expect_tx(bars + 8 * (BAR_KVFULL + h), kvbytes);
        bulk_load(sbase + OFF_KV + h * KVBUF + bmin * 1024, kvsrc + (size_t)h * SEQ * 64, kvbytes, bars + 8 * (BAR_KVFULL + h));
      }
    }
    if (lane == 0) flag_wait(&g_flag_g[rb * FS], ep1 * 32, t0);
    __syncwarp();
    const int row0 = rb * 128 + aw * 32 + (lane >> 2);
    const float g00 = __ldcg(&g_gate[row0]), g01 = __ldcg(&g_gate[row0 + 8]), g10 = __ldcg(&g_gate[row0 + 16]), g11 = __ldcg(&g_gate[row0 + 24]);
    const int mi = lane >> 3, l7 = lane & 7;
    const uint32_t koff = (l7 + 8 * (mi >> 1)) * 64 + (((mi & 1) ^ ((l7 >> 1) & 3)) << 4);
    const uint32_t voff = (l7 + 8 * (mi & 1)) * 64 + (((2 + (mi >> 1)) ^ ((l7 >> 1) & 3)) << 4);
    const bool pe0 = (lane & 3) * 2 <= (lane >> 2), pe1 = (lane & 3) * 2 + 1 <= (lane >> 2);
    const int kb0 = 2 * aw;
#pragma unroll 1
    for (int hh = 0; hh < 4; hh++) {
      mbar_wait(bars + 8 * (BAR_KVFULL + (hh & 1)), hh >> 1, t0);
      const uint4* qs = g_q + (((rb * 8 + j) * 4 + hh) * 8 + aw * 2) * 32 + lane;
      const uint4 qa = __ldcg(qs), qb = __ldcg(qs + 32);
      const uint32_t q0[4] = {qa.x, qa.y, qa.z, qa.w}, q1[4] = {qb.x, qb.y, qb.z, qb.w};
      const uint32_t kbase = sbase + OFF_KV + (hh & 1) * KVBUF + koff, vbase = sbase + OFF_KV + (hh & 1) * KVBUF + voff;
      AttnT ta, tb;
      const float NINF = __int_as_float(0xff800000);
#pragma unroll
      for (int i = 0; i < 8; i++) { ta.o[i] = 0.f; tb.o[i] = 0.f; }
      ta.m0 = ta.m1 = tb.m0 = tb.m1 = NINF; ta.l0 = ta.l1 = tb.l0 = tb.l1 = 0.f;
      attn_edge(ta, q0, kbase, vbase, kb0, kb0 + 16, kb0 + 1, kb0 >= bmin, kb0 + 1 >= bmin, pe0, pe1);
      attn_edge(tb, q1, kbase, vbase, kb0 + 1, kb0 + 17, kb0 + 16, kb0 + 1 >= bmin, true, pe0, pe1);
      int b = max(kb0 + 2, bmin);
#pragma unroll 1
      for (; b + 4 <= kb0 + 16; b += 4) attn_full<4>(ta, tb, q0, q1, kbase + b * 1024, vbase + b * 1024);
      if (b + 2 <= kb0 + 16) attn_full<2>(ta, tb, q0, q1, kbase + b * 1024, vbase + b * 1024);
      __nv_bfloat16* od = g_ho + (size_t)row0 * KHO + DFF + (4 * j + hh) * 16 + (lane & 3) * 2;
      attn_store(ta, g00, g01, od);
      attn_store(tb, g10, g11, od + 16 * KHO);
      if (hh < 2) {
        named_bar(3, 128);
        if (tid == 256) {
          mbar_expect_tx(bars + 8 * (BAR_KVFULL + (hh & 1)), kvbytes);
          bulk_load(sbase + OFF_KV + (hh & 1) * KVBUF + bmin * 1024, kvsrc + (size_t)(hh + 2) * SEQ * 64, kvbytes, bars + 8 * (BAR_KVFULL + (hh & 1)));
        }
      }
    }
    __threadfence();
    __syncwarp();
    if (lane == 0) flag_add(&g_flag_o[(rb * 8 + j) * FS]);
    __syncwarp();
    cluster_sync();
  } else {
    asm volatile("setmaxnreg.dec.sync.aligned.u32 40;");
    if (warp == 12) {
      if (lane == 0) {
        int bi = 0; uint32_t ph = 1;
        const int total = 16 + on;
        for (int kc = 0; kc < total; kc++) {
          const CUtensorMap* m; int c0 = 0, krow, c2; uint32_t bytes = 16384;
          if (kc < 8) { m = &P.tmWqkv; c0 = 64 * j; krow = kc * 64; c2 = 0; bytes = 12288; }
          else if (kc < 16) { m = hn == 4 ? &P.tmW1a : &P.tmW1b; krow = (kc - 8) * 64; c2 = hs; bytes = hn * 4096; }
          else {
            const int c = o_chunk(j, kc - 16);
            if (c < 28) { m = &P.tmW2; krow = c * 64; } else { m = &P.tmWo; krow = (c - 28) * 64; }
            c2 = (j & 1) * 4;
          }
          for (int half = 0; half < 2; half++) {
            mbar_wait(bars + 8 * (BAR_EMPTYB + bi), ph, t0);
            mbar_expect_tx(bars + 8 * (BAR_FULLB + bi), bytes);
            tma_load_3d_mc(sbase + OFF_B + bi * SLOT + rank * 8192, m, c0, krow + half * 32 + rank * 16, c2, bars + 8 * (BAR_FULLB + bi));
            if (++bi == NB) { bi = 0; ph ^= 1; }
          }
        }
      }
    } else if (warp == 13) {
      if (lane == 0) {
        int ai = 0; uint32_t ph = 1;
        const int total = 18 + on;
        for (int e = 0; e < total; e++) {
          mbar_wait(bars + 8 * (BAR_EMPTYA + ai), ph, t0);
          const uint32_t fb = bars + 8 * (BAR_FULLA + ai), dst = sbase + OFF_A + ai * SLOT;
          const bool grant = (e == 8 || e == 9 || (e >= 18 && e < 18 + hn));
          if (grant) mbar_arrive(fb);
          else {
            mbar_arrive_n(bars + 8 * (BAR_EMPTYA + ai), 2);
            if (e < 18) {
              mbar_expect_tx(fb, 16384);
              tma_load_2d(dst, &P.tmX, (e < 8 ? e : e - 10) * 64, rb * 128, fb);
            } else {
              const int c = o_chunk(j, e - 18);
              if (c < 28) flag_wait(&g_flag_h[(rb * 8 + h_owner(c)) * FS], ep1 * 2, t0);
              else flag_wait(&g_flag_o[(rb * 8 + c - 28) * FS], ep1 * 4, t0);
              fence_async_all();
              mbar_expect_tx(fb, 16384);
              tma_load_2d(dst, &P.tmHO, c * 64, rb * 128, fb);
            }
          }
          if (++ai == NA) { ai = 0; ph ^= 1; }
        }
      }
    } else {
      if (lane == 0) {
        const int wg = warp - 14;
        mbar_wait(bars + 8 * (BAR_STG + wg), 0, t0);
        constexpr int s0 = 8 % NA, s1 = 9 % NA;
        for (int hh = 0; hh < 4; hh++)
          bulk_store(g_kv + ((size_t)(4 * j + hh) * SEQ + rb * 128 + wg * 64) * 64,
                     sbase + OFF_A + (hh < 2 ? s0 : s1) * SLOT + (hh & 1) * 8192 + wg * 4096, 4096);
        bulk_commit();
        bulk_wait_read();
        mbar_arrive(bars + 8 * (BAR_EMPTYA + s0)); mbar_arrive(bars + 8 * (BAR_EMPTYA + s1));
        bulk_wait_all();
        fence_async_all();
        __threadfence();
        flag_add(&g_flag_kv[(rb * 8 + j) * FS]);
        mbar_wait(bars + 8 * (BAR_STG + wg), 1, t0);
        for (int i = 0; i < hn; i++)
          tma_store_2d(&P.tmHOs, (hs + i) * 64, rb * 128 + wg * 64, sbase + OFF_A + ((18 + i) % NA) * SLOT + wg * 8192);
        bulk_commit();
        bulk_wait_read();
        for (int i = 0; i < hn; i++) mbar_arrive(bars + 8 * (BAR_EMPTYA + (18 + i) % NA));
        bulk_wait_all();
        fence_async_all();
        __threadfence();
        flag_add(&g_flag_h[(rb * 8 + j) * FS]);
      }
    }
    __syncwarp();
    cluster_sync();
  }
}

typedef CUresult (*EncodeFn)(CUtensorMap*, CUtensorMapDataType, cuuint32_t, void*, const cuuint64_t*, const cuuint64_t*, const cuuint32_t*,
                             const cuuint32_t*, CUtensorMapInterleave, CUtensorMapSwizzle, CUtensorMapL2promotion, CUtensorMapFloatOOBfill);

void make_map(EncodeFn enc, CUtensorMap* m, const void* ptr, int rank, const cuuint64_t* dims, const cuuint64_t* strides, const cuuint32_t* box) {
  cuuint32_t es[3] = {1, 1, 1};
  enc(m, CU_TENSOR_MAP_DATA_TYPE_BFLOAT16, rank, const_cast<void*>(ptr), dims, strides, box, es, CU_TENSOR_MAP_INTERLEAVE_NONE,
      CU_TENSOR_MAP_SWIZZLE_128B, CU_TENSOR_MAP_L2_PROMOTION_L2_256B, CU_TENSOR_MAP_FLOAT_OOB_FILL_NONE);
}

}

extern "C" void kernel_launch(void* const* d_in, const int* in_sizes, int n_in, void* d_out, int out_size) {
  (void)in_sizes; (void)n_in; (void)out_size;
  static EncodeFn enc = nullptr;
  static void* ho_ptr = nullptr;
  if (!enc) {
    void* fn = nullptr; cudaDriverEntryPointQueryResult st;
    cudaGetDriverEntryPoint("cuTensorMapEncodeTiled", &fn, cudaEnableDefault, &st);
    enc = (EncodeFn)fn;
    cudaGetSymbolAddress(&ho_ptr, g_ho);
    cudaFuncSetAttribute(fused_kernel, cudaFuncAttributeMaxDynamicSharedMemorySize, SMEM_BYTES);
  }
  const __nv_bfloat16* x = (const __nv_bfloat16*)d_in[0];
  const __nv_bfloat16* wqkv = (const __nv_bfloat16*)d_in[1];
  const __nv_bfloat16* wo = (const __nv_bfloat16*)d_in[2];
  const __nv_bfloat16* w1 = (const __nv_bfloat16*)d_in[4];
  const __nv_bfloat16* w2 = (const __nv_bfloat16*)d_in[5];
  const __nv_bfloat16* gate_w = (const __nv_bfloat16*)d_in[6];
  Params P;
  { cuuint64_t d[2] = {DM, SEQ}, s[1] = {DM * 2}; cuuint32_t b[2] = {64, 128}; make_map(enc, &P.tmX, x, 2, d, s, b); }
  { cuuint64_t d[3] = {512, 512, 3}, s[2] = {1536 * 2, 512 * 2}; cuuint32_t b[3] = {64, 16, 3}; make_map(enc, &P.tmWqkv, wqkv, 3, d, s, b); }
  { cuuint64_t d[3] = {64, 512, 28}, s[2] = {DFF * 2, 128}; cuuint32_t b[3] = {64, 16, 4}; make_map(enc, &P.tmW1a, w1, 3, d, s, b);
    b[2] = 3; make_map(enc, &P.tmW1b, w1, 3, d, s, b); }
  { cuuint64_t d[3] = {64, DFF, 8}, s[2] = {DM * 2, 128}; cuuint32_t b[3] = {64, 16, 4}; make_map(enc, &P.tmW2, w2, 3, d, s, b); }
  { cuuint64_t d[3] = {64, DM, 8}, s[2] = {DM * 2, 128}; cuuint32_t b[3] = {64, 16, 4}; make_map(enc, &P.tmWo, wo, 3, d, s, b); }
  { cuuint64_t d[2] = {KHO, SEQ}, s[1] = {KHO * 2}; cuuint32_t b[2] = {64, 128}; make_map(enc, &P.tmHO, ho_ptr, 2, d, s, b);
    b[1] = 64; make_map(enc, &P.tmHOs, ho_ptr, 2, d, s, b); }
  P.x = x; P.gate_w = gate_w; P.w1 = w1; P.w2 = w2; P.wo = wo; P.out = (__nv_bfloat16*)d_out;
  fused_kernel<<<128, 512, SMEM_BYTES>>>(P);
}
```

```cpp
#include <cuda_runtime.h>
#include <cuda_bf16.h>
#include <cuda.h>
#include <stdint.h>

#define DEVI __device__ __forceinline__

namespace {

constexpr int SEQ = 2048, DM = 512, DFF = 1792, KHO = 2304;
constexpr int NA = 5, NB = 6, SLOT = 16384, KVBUF = 24576;
constexpr int OFF_A = 0, OFF_B = NA * SLOT, OFF_KV = OFF_B + NB * SLOT, OFF_BAR = OFF_KV + 2 * KVBUF;
constexpr int OFF_GST = OFF_BAR + 512;
constexpr int OFF_ONES = OFF_BAR + 1024;
constexpr int SMEM_BYTES = OFF_BAR + 1280 + 1024;
constexpr uint32_t TIMEOUT = 1u << 28;
constexpr int FS = 8;

constexpr int BAR_FULLA = 0, BAR_EMPTYA = BAR_FULLA + NA, BAR_FULLB = BAR_EMPTYA + NA, BAR_EMPTYB = BAR_FULLB + NB,
              BAR_KVFULL = BAR_EMPTYB + NB, BAR_KVEMPTY = BAR_KVFULL + 2, BAR_STG = BAR_KVEMPTY + 2, BAR_PIN = BAR_STG + 2, BAR_GATE = BAR_PIN + 1;

__device__ __align__(1024) uint8_t g_kv[32 * SEQ * 64];
__device__ __align__(1024) __nv_bfloat16 g_ho[SEQ * KHO];
__device__ __align__(1024) uint8_t g_part[128 * 16384];
__device__ __align__(128) float g_gate[SEQ];
__device__ unsigned g_flag_kv[128 * FS], g_flag_h[128 * FS], g_flag_o[128 * FS], g_flag_g[16 * FS], g_flag_p[128 * FS];
__device__ unsigned g_epoch, g_done;
#define TR(i) do {} while (0)

struct Params {
  CUtensorMap tmX, tmWqkv, tmW1a, tmW1b, tmW2, tmWo, tmHO, tmHOs, tmOs;
  const __nv_bfloat16* x;
  const __nv_bfloat16* gate_w;
  const __nv_bfloat16* w1;
  const __nv_bfloat16* w2;
  const __nv_bfloat16* wo;
  __nv_bfloat16* out;
};

DEVI uint32_t smem_u32(const void* p) { return (uint32_t)__cvta_generic_to_shared(p); }
DEVI uint32_t clk32() { uint32_t c; asm volatile("mov.u32 %0, %%clock;" : "=r"(c)); return c; }
DEVI void mbar_init(uint32_t bar, uint32_t cnt) { asm volatile("mbarrier.init.shared::cta.b64 [%0], %1;" ::"r"(bar), "r"(cnt)); }
DEVI void mbar_expect_tx(uint32_t bar, uint32_t bytes) { asm volatile("mbarrier.arrive.expect_tx.shared::cta.b64 _, [%0], %1;" ::"r"(bar), "r"(bytes) : "memory"); }
DEVI void mbar_arrive(uint32_t bar) { asm volatile("mbarrier.arrive.shared::cta.b64 _, [%0];" ::"r"(bar) : "memory"); }
DEVI void mbar_arrive_n(uint32_t bar, uint32_t n) { asm volatile("mbarrier.arrive.shared::cta.b64 _, [%0], %1;" ::"r"(bar), "r"(n) : "memory"); }
DEVI void mbar_arrive_cluster(uint32_t bar, uint32_t cta) {
  asm volatile("{ .reg .b32 ra; mapa.shared::cluster.u32 ra, %0, %1; mbarrier.arrive.shared::cluster.b64 _, [ra]; }" ::"r"(bar), "r"(cta) : "memory");
}
DEVI void mbar_wait(uint32_t bar, uint32_t parity, uint32_t t0) {
  asm volatile("{ .reg .pred p; .reg .u32 c;\n"
               "mbarrier.try_wait.parity.shared::cta.b64 p, [%0], %1;\n"
               "@p bra DONE_%=;\n"
               "WAIT_%=:\n"
               "mbarrier.try_wait.parity.shared::cta.b64 p, [%0], %1;\n"
               "@p bra DONE_%=;\n"
               "mov.u32 c, %%clock; sub.u32 c, c, %2; setp.lt.u32 p, c, %3;\n"
               "@p bra WAIT_%=;\n"
               "DONE_%=: }" ::"r"(bar), "r"(parity), "r"(t0), "n"(TIMEOUT) : "memory");
}
DEVI unsigned ld_relaxed(const unsigned* p) { unsigned v; asm volatile("ld.relaxed.gpu.global.u32 %0, [%1];" : "=r"(v) : "l"(p) : "memory"); return v; }
DEVI float ld_relaxed_f(const float* p) { float v; asm volatile("ld.relaxed.gpu.global.f32 %0, [%1];" : "=f"(v) : "l"(p) : "memory"); return v; }
DEVI void flag_wait(const unsigned* p, unsigned target, uint32_t t0) {
  while ((int)(ld_relaxed(p) - target) < 0) { if (clk32() - t0 > TIMEOUT) break; }
}
DEVI void flag_add(unsigned* p) { asm volatile("red.relaxed.gpu.global.add.u32 [%0], 1;" ::"l"(p) : "memory"); }
DEVI void fence_async_smem() { asm volatile("fence.proxy.async.shared::cta;" ::: "memory"); }
DEVI void fence_async_global() { asm volatile("fence.proxy.async.global;" ::: "memory"); }
DEVI void tma_load_2d(uint32_t dst, const CUtensorMap* m, int c0, int c1, uint32_t bar) {
  asm volatile("cp.async.bulk.tensor.2d.shared::cluster.global.mbarrier::complete_tx::bytes [%0], [%1, {%3, %4}], [%2];" ::"r"(dst), "l"(m), "r"(bar), "r"(c0), "r"(c1) : "memory");
}
DEVI void tma_load_3d_mc(uint32_t dst, const CUtensorMap* m, int c0, int c1, int c2, uint32_t bar) {
  asm volatile("cp.async.bulk.tensor.3d.shared::cluster.global.mbarrier::complete_tx::bytes.multicast::cluster [%0], [%1, {%3, %4, %5}], [%2], %6;"
               ::"r"(dst), "l"(m), "r"(bar), "r"(c0), "r"(c1), "r"(c2), "h"((uint16_t)3) : "memory");
}
DEVI void tma_load_4d_mc(uint32_t dst, const CUtensorMap* m, int c0, int c1, int c2, int c3, uint32_t bar) {
  asm volatile("cp.async.bulk.tensor.4d.shared::cluster.global.mbarrier::complete_tx::bytes.multicast::cluster [%0], [%1, {%3, %4, %5, %6}], [%2], %7;"
               ::"r"(dst), "l"(m), "r"(bar), "r"(c0), "r"(c1), "r"(c2), "r"(c3), "h"((uint16_t)3) : "memory");
}
DEVI void tma_store_2d(const CUtensorMap* m, int c0, int c1, uint32_t src) {
  asm volatile("cp.async.bulk.tensor.2d.global.shared::cta.bulk_group [%0, {%1, %2}], [%3];" ::"l"(m), "r"(c0), "r"(c1), "r"(src) : "memory");
}
DEVI void bulk_store(void* dst, uint32_t src, uint32_t bytes) {
  asm volatile("cp.async.bulk.global.shared::cta.bulk_group [%0], [%1], %2;" ::"l"(dst), "r"(src), "r"(bytes) : "memory");
}
DEVI void bulk_load(uint32_t dst, const void* src, uint32_t bytes, uint32_t bar) {
  asm volatile("cp.async.bulk.shared::cluster.global.mbarrier::complete_tx::bytes [%0], [%1], %2, [%3];" ::"r"(dst), "l"(src), "r"(bytes), "r"(bar) : "memory");
}
DEVI void bulk_commit() { asm volatile("cp.async.bulk.commit_group;" ::: "memory"); }
DEVI void bulk_wait_all() { asm volatile("cp.async.bulk.wait_group 0;" ::: "memory"); }
DEVI void l2_prefetch(const void* p, uint32_t bytes) { asm volatile("cp.async.bulk.prefetch.L2.global [%0], %1;" ::"l"(p), "r"(bytes) : "memory"); }
DEVI void cluster_arrive() { asm volatile("barrier.cluster.arrive.relaxed.aligned;" ::: "memory"); }
DEVI void cluster_wait() { asm volatile("barrier.cluster.wait.aligned;" ::: "memory"); }
template <int ID> DEVI void named_bar(int n) { asm volatile("bar.sync %0, %1;" ::"n"(ID), "r"(n) : "memory"); }
DEVI void turn_wait(int wg) { if (wg == 0) asm volatile("bar.sync 4, 256;" ::: "memory"); else asm volatile("bar.sync 5, 256;" ::: "memory"); }
DEVI void turn_pass(int wg) { if (wg == 0) asm volatile("bar.arrive 5, 256;" ::: "memory"); else asm volatile("bar.arrive 4, 256;" ::: "memory"); }
DEVI void wg_bar(int wg) { if (wg == 0) named_bar<1>(128); else named_bar<2>(128); }
DEVI void wgmma_fence() { asm volatile("wgmma.fence.sync.aligned;" ::: "memory"); }
DEVI void wgmma_commit() { asm volatile("wgmma.commit_group.sync.aligned;" ::: "memory"); }
template <int N> DEVI void wgmma_wait() { asm volatile("wgmma.wait_group.sync.aligned %0;" ::"n"(N) : "memory"); }
template <uint32_t LBO> DEVI uint64_t desc_sw128(uint32_t a16) {
  return ((uint64_t)(0x40000000u | (1024 >> 4)) << 32) | (a16 + ((LBO >> 4) << 16));
}
DEVI uint64_t desc_sw64(uint32_t a16) {
  return ((uint64_t)(0x80000000u | (512 >> 4)) << 32) | (a16 + ((512 >> 4) << 16));
}
DEVI uint32_t pack_bf16(float lo, float hi) { uint32_t r; asm("cvt.rn.bf16x2.f32 %0, %1, %2;" : "=r"(r) : "f"(hi), "f"(lo)); return r; }
DEVI void stsm_x4(uint32_t addr, uint32_t r0, uint32_t r1, uint32_t r2, uint32_t r3) {
  asm volatile("stmatrix.sync.aligned.m8n8.x4.shared.b16 [%0], {%1, %2, %3, %4};" ::"r"(addr), "r"(r0), "r"(r1), "r"(r2), "r"(r3) : "memory");
}
DEVI void sts128(uint32_t addr, uint32_t r0, uint32_t r1, uint32_t r2, uint32_t r3) {
  asm volatile("st.shared.v4.b32 [%0], {%1, %2, %3, %4};" ::"r"(addr), "r"(r0), "r"(r1), "r"(r2), "r"(r3) : "memory");
}
DEVI uint4 lds128(uint32_t addr) {
  uint4 v; asm volatile("ld.shared.v4.b32 {%0, %1, %2, %3}, [%4];" : "=r"(v.x), "=r"(v.y), "=r"(v.z), "=r"(v.w) : "r"(addr) : "memory"); return v;
}
DEVI float ex2(float x) { float y; asm("ex2.approx.ftz.f32 %0, %1;" : "=f"(y) : "f"(x)); return y; }

DEVI void wgmma_ss_n64(float (&d)[32], uint64_t da, uint64_t db) {
  asm volatile("wgmma.mma_async.sync.aligned.m64n64k16.f32.bf16.bf16 {%0, %1, %2, %3, %4, %5, %6, %7, %8, %9, %10, %11, %12, %13, %14, %15, %16, %17, %18, %19, %20, %21, %22, %23, %24, %25, %26, %27, %28, %29, %30, %31}, %32, %33, 1, 1, 1, 0, 1;"
    : "+f"(d[0]), "+f"(d[1]), "+f"(d[2]), "+f"(d[3]), "+f"(d[4]), "+f"(d[5]), "+f"(d[6]), "+f"(d[7]), "+f"(d[8]), "+f"(d[9]), "+f"(d[10]), "+f"(d[11]), "+f"(d[12]), "+f"(d[13]), "+f"(d[14]), "+f"(d[15]), "+f"(d[16]), "+f"(d[17]), "+f"(d[18]), "+f"(d[19]), "+f"(d[20]), "+f"(d[21]), "+f"(d[22]), "+f"(d[23]), "+f"(d[24]), "+f"(d[25]), "+f"(d[26]), "+f"(d[27]), "+f"(d[28]), "+f"(d[29]), "+f"(d[30]), "+f"(d[31])
    : "l"(da), "l"(db));
}
DEVI void wgmma_ss_n128(float (&d)[64], uint64_t da, uint64_t db) {
  asm volatile("wgmma.mma_async.sync.aligned.m64n128k16.f32.bf16.bf16 {%0, %1, %2, %3, %4, %5, %6, %7, %8, %9, %10, %11, %12, %13, %14, %15, %16, %17, %18, %19, %20, %21, %22, %23, %24, %25, %26, %27, %28, %29, %30, %31, %32, %33, %34, %35, %36, %37, %38, %39, %40, %41, %42, %43, %44, %45, %46, %47, %48, %49, %50, %51, %52, %53, %54, %55, %56, %57, %58, %59, %60, %61, %62, %63}, %64, %65, 1, 1, 1, 0, 1;"
    : "+f"(d[0]), "+f"(d[1]), "+f"(d[2]), "+f"(d[3]), "+f"(d[4]), "+f"(d[5]), "+f"(d[6]), "+f"(d[7]), "+f"(d[8]), "+f"(d[9]), "+f"(d[10]), "+f"(d[11]), "+f"(d[12]), "+f"(d[13]), "+f"(d[14]), "+f"(d[15]), "+f"(d[16]), "+f"(d[17]), "+f"(d[18]), "+f"(d[19]), "+f"(d[20]), "+f"(d[21]), "+f"(d[22]), "+f"(d[23]), "+f"(d[24]), "+f"(d[25]), "+f"(d[26]), "+f"(d[27]), "+f"(d[28]), "+f"(d[29]), "+f"(d[30]), "+f"(d[31]), "+f"(d[32]), "+f"(d[33]), "+f"(d[34]), "+f"(d[35]), "+f"(d[36]), "+f"(d[37]), "+f"(d[38]), "+f"(d[39]), "+f"(d[40]), "+f"(d[41]), "+f"(d[42]), "+f"(d[43]), "+f"(d[44]), "+f"(d[45]), "+f"(d[46]), "+f"(d[47]), "+f"(d[48]), "+f"(d[49]), "+f"(d[50]), "+f"(d[51]), "+f"(d[52]), "+f"(d[53]), "+f"(d[54]), "+f"(d[55]), "+f"(d[56]), "+f"(d[57]), "+f"(d[58]), "+f"(d[59]), "+f"(d[60]), "+f"(d[61]), "+f"(d[62]), "+f"(d[63])
    : "l"(da), "l"(db));
}
DEVI void wgmma_ss_n192(float (&d)[96], uint64_t da, uint64_t db) {
  asm volatile("wgmma.mma_async.sync.aligned.m64n192k16.f32.bf16.bf16 {%0, %1, %2, %3, %4, %5, %6, %7, %8, %9, %10, %11, %12, %13, %14, %15, %16, %17, %18, %19, %20, %21, %22, %23, %24, %25, %26, %27, %28, %29, %30, %31, %32, %33, %34, %35, %36, %37, %38, %39, %40, %41, %42, %43, %44, %45, %46, %47, %48, %49, %50, %51, %52, %53, %54, %55, %56, %57, %58, %59, %60, %61, %62, %63, %64, %65, %66, %67, %68, %69, %70, %71, %72, %73, %74, %75, %76, %77, %78, %79, %80, %81, %82, %83, %84, %85, %86, %87, %88, %89, %90, %91, %92, %93, %94, %95}, %96, %97, 1, 1, 1, 0, 1;"
    : "+f"(d[0]), "+f"(d[1]), "+f"(d[2]), "+f"(d[3]), "+f"(d[4]), "+f"(d[5]), "+f"(d[6]), "+f"(d[7]), "+f"(d[8]), "+f"(d[9]), "+f"(d[10]), "+f"(d[11]), "+f"(d[12]), "+f"(d[13]), "+f"(d[14]), "+f"(d[15]), "+f"(d[16]), "+f"(d[17]), "+f"(d[18]), "+f"(d[19]), "+f"(d[20]), "+f"(d[21]), "+f"(d[22]), "+f"(d[23]), "+f"(d[24]), "+f"(d[25]), "+f"(d[26]), "+f"(d[27]), "+f"(d[28]), "+f"(d[29]), "+f"(d[30]), "+f"(d[31]), "+f"(d[32]), "+f"(d[33]), "+f"(d[34]), "+f"(d[35]), "+f"(d[36]), "+f"(d[37]), "+f"(d[38]), "+f"(d[39]), "+f"(d[40]), "+f"(d[41]), "+f"(d[42]), "+f"(d[43]), "+f"(d[44]), "+f"(d[45]), "+f"(d[46]), "+f"(d[47]), "+f"(d[48]), "+f"(d[49]), "+f"(d[50]), "+f"(d[51]), "+f"(d[52]), "+f"(d[53]), "+f"(d[54]), "+f"(d[55]), "+f"(d[56]), "+f"(d[57]), "+f"(d[58]), "+f"(d[59]), "+f"(d[60]), "+f"(d[61]), "+f"(d[62]), "+f"(d[63]), "+f"(d[64]), "+f"(d[65]), "+f"(d[66]), "+f"(d[67]), "+f"(d[68]), "+f"(d[69]), "+f"(d[70]), "+f"(d[71]), "+f"(d[72]), "+f"(d[73]), "+f"(d[74]), "+f"(d[75]), "+f"(d[76]), "+f"(d[77]), "+f"(d[78]), "+f"(d[79]), "+f"(d[80]), "+f"(d[81]), "+f"(d[82]), "+f"(d[83]), "+f"(d[84]), "+f"(d[85]), "+f"(d[86]), "+f"(d[87]), "+f"(d[88]), "+f"(d[89]), "+f"(d[90]), "+f"(d[91]), "+f"(d[92]), "+f"(d[93]), "+f"(d[94]), "+f"(d[95])
    : "l"(da), "l"(db));
}
DEVI void wgmma_ss_n256(float (&d)[128], uint64_t da, uint64_t db) {
  asm volatile("wgmma.mma_async.sync.aligned.m64n256k16.f32.bf16.bf16 {%0, %1, %2, %3, %4, %5, %6, %7, %8, %9, %10, %11, %12, %13, %14, %15, %16, %17, %18, %19, %20, %21, %22, %23, %24, %25, %26, %27, %28, %29, %30, %31, %32, %33, %34, %35, %36, %37, %38, %39, %40, %41, %42, %43, %44, %45, %46, %47, %48, %49, %50, %51, %52, %53, %54, %55, %56, %57, %58, %59, %60, %61, %62, %63, %64, %65, %66, %67, %68, %69, %70, %71, %72, %73, %74, %75, %76, %77, %78, %79, %80, %81, %82, %83, %84, %85, %86, %87, %88, %89, %90, %91, %92, %93, %94, %95, %96, %97, %98, %99, %100, %101, %102, %103, %104, %105, %106, %107, %108, %109, %110, %111, %112, %113, %114, %115, %116, %117, %118, %119, %120, %121, %122, %123, %124, %125, %126, %127}, %128, %129, 1, 1, 1, 0, 1;"
    : "+f"(d[0]), "+f"(d[1]), "+f"(d[2]), "+f"(d[3]), "+f"(d[4]), "+f"(d[5]), "+f"(d[6]), "+f"(d[7]), "+f"(d[8]), "+f"(d[9]), "+f"(d[10]), "+f"(d[11]), "+f"(d[12]), "+f"(d[13]), "+f"(d[14]), "+f"(d[15]), "+f"(d[16]), "+f"(d[17]), "+f"(d[18]), "+f"(d[19]), "+f"(d[20]), "+f"(d[21]), "+f"(d[22]), "+f"(d[23]), "+f"(d[24]), "+f"(d[25]), "+f"(d[26]), "+f"(d[27]), "+f"(d[28]), "+f"(d[29]), "+f"(d[30]), "+f"(d[31]), "+f"(d[32]), "+f"(d[33]), "+f"(d[34]), "+f"(d[35]), "+f"(d[36]), "+f"(d[37]), "+f"(d[38]), "+f"(d[39]), "+f"(d[40]), "+f"(d[41]), "+f"(d[42]), "+f"(d[43]), "+f"(d[44]), "+f"(d[45]), "+f"(d[46]), "+f"(d[47]), "+f"(d[48]), "+f"(d[49]), "+f"(d[50]), "+f"(d[51]), "+f"(d[52]), "+f"(d[53]), "+f"(d[54]), "+f"(d[55]), "+f"(d[56]), "+f"(d[57]), "+f"(d[58]), "+f"(d[59]), "+f"(d[60]), "+f"(d[61]), "+f"(d[62]), "+f"(d[63]), "+f"(d[64]), "+f"(d[65]), "+f"(d[66]), "+f"(d[67]), "+f"(d[68]), "+f"(d[69]), "+f"(d[70]), "+f"(d[71]), "+f"(d[72]), "+f"(d[73]), "+f"(d[74]), "+f"(d[75]), "+f"(d[76]), "+f"(d[77]), "+f"(d[78]), "+f"(d[79]), "+f"(d[80]), "+f"(d[81]), "+f"(d[82]), "+f"(d[83]), "+f"(d[84]), "+f"(d[85]), "+f"(d[86]), "+f"(d[87]), "+f"(d[88]), "+f"(d[89]), "+f"(d[90]), "+f"(d[91]), "+f"(d[92]), "+f"(d[93]), "+f"(d[94]), "+f"(d[95]), "+f"(d[96]), "+f"(d[97]), "+f"(d[98]), "+f"(d[99]), "+f"(d[100]), "+f"(d[101]), "+f"(d[102]), "+f"(d[103]), "+f"(d[104]), "+f"(d[105]), "+f"(d[106]), "+f"(d[107]), "+f"(d[108]), "+f"(d[109]), "+f"(d[110]), "+f"(d[111]), "+f"(d[112]), "+f"(d[113]), "+f"(d[114]), "+f"(d[115]), "+f"(d[116]), "+f"(d[117]), "+f"(d[118]), "+f"(d[119]), "+f"(d[120]), "+f"(d[121]), "+f"(d[122]), "+f"(d[123]), "+f"(d[124]), "+f"(d[125]), "+f"(d[126]), "+f"(d[127])
    : "l"(da), "l"(db));
}
DEVI void wgmma_qk64(float (&d)[32], uint32_t a0, uint32_t a1, uint32_t a2, uint32_t a3, uint64_t db) {
  asm volatile("wgmma.mma_async.sync.aligned.m64n64k16.f32.bf16.bf16 {%0, %1, %2, %3, %4, %5, %6, %7, %8, %9, %10, %11, %12, %13, %14, %15, %16, %17, %18, %19, %20, %21, %22, %23, %24, %25, %26, %27, %28, %29, %30, %31}, {%32, %33, %34, %35}, %36, 0, 1, 1, 0;"
    : "=f"(d[0]), "=f"(d[1]), "=f"(d[2]), "=f"(d[3]), "=f"(d[4]), "=f"(d[5]), "=f"(d[6]), "=f"(d[7]), "=f"(d[8]), "=f"(d[9]), "=f"(d[10]), "=f"(d[11]), "=f"(d[12]), "=f"(d[13]), "=f"(d[14]), "=f"(d[15]), "=f"(d[16]), "=f"(d[17]), "=f"(d[18]), "=f"(d[19]), "=f"(d[20]), "=f"(d[21]), "=f"(d[22]), "=f"(d[23]), "=f"(d[24]), "=f"(d[25]), "=f"(d[26]), "=f"(d[27]), "=f"(d[28]), "=f"(d[29]), "=f"(d[30]), "=f"(d[31])
    : "r"(a0), "r"(a1), "r"(a2), "r"(a3), "l"(db));
}
DEVI void wgmma_qk128(float (&d)[64], uint32_t a0, uint32_t a1, uint32_t a2, uint32_t a3, uint64_t db) {
  asm volatile("wgmma.mma_async.sync.aligned.m64n128k16.f32.bf16.bf16 {%0, %1, %2, %3, %4, %5, %6, %7, %8, %9, %10, %11, %12, %13, %14, %15, %16, %17, %18, %19, %20, %21, %22, %23, %24, %25, %26, %27, %28, %29, %30, %31, %32, %33, %34, %35, %36, %37, %38, %39, %40, %41, %42, %43, %44, %45, %46, %47, %48, %49, %50, %51, %52, %53, %54, %55, %56, %57, %58, %59, %60, %61, %62, %63}, {%64, %65, %66, %67}, %68, 0, 1, 1, 0;"
    : "=f"(d[0]), "=f"(d[1]), "=f"(d[2]), "=f"(d[3]), "=f"(d[4]), "=f"(d[5]), "=f"(d[6]), "=f"(d[7]), "=f"(d[8]), "=f"(d[9]), "=f"(d[10]), "=f"(d[11]), "=f"(d[12]), "=f"(d[13]), "=f"(d[14]), "=f"(d[15]), "=f"(d[16]), "=f"(d[17]), "=f"(d[18]), "=f"(d[19]), "=f"(d[20]), "=f"(d[21]), "=f"(d[22]), "=f"(d[23]), "=f"(d[24]), "=f"(d[25]), "=f"(d[26]), "=f"(d[27]), "=f"(d[28]), "=f"(d[29]), "=f"(d[30]), "=f"(d[31]), "=f"(d[32]), "=f"(d[33]), "=f"(d[34]), "=f"(d[35]), "=f"(d[36]), "=f"(d[37]), "=f"(d[38]), "=f"(d[39]), "=f"(d[40]), "=f"(d[41]), "=f"(d[42]), "=f"(d[43]), "=f"(d[44]), "=f"(d[45]), "=f"(d[46]), "=f"(d[47]), "=f"(d[48]), "=f"(d[49]), "=f"(d[50]), "=f"(d[51]), "=f"(d[52]), "=f"(d[53]), "=f"(d[54]), "=f"(d[55]), "=f"(d[56]), "=f"(d[57]), "=f"(d[58]), "=f"(d[59]), "=f"(d[60]), "=f"(d[61]), "=f"(d[62]), "=f"(d[63])
    : "r"(a0), "r"(a1), "r"(a2), "r"(a3), "l"(db));
}
DEVI void wgmma_qk64a(float (&d)[32], uint32_t a0, uint32_t a1, uint32_t a2, uint32_t a3, uint64_t db) {
  asm volatile("wgmma.mma_async.sync.aligned.m64n64k16.f32.bf16.bf16 {%0, %1, %2, %3, %4, %5, %6, %7, %8, %9, %10, %11, %12, %13, %14, %15, %16, %17, %18, %19, %20, %21, %22, %23, %24, %25, %26, %27, %28, %29, %30, %31}, {%32, %33, %34, %35}, %36, 1, 1, 1, 0;"
    : "+f"(d[0]), "+f"(d[1]), "+f"(d[2]), "+f"(d[3]), "+f"(d[4]), "+f"(d[5]), "+f"(d[6]), "+f"(d[7]), "+f"(d[8]), "+f"(d[9]), "+f"(d[10]), "+f"(d[11]), "+f"(d[12]), "+f"(d[13]), "+f"(d[14]), "+f"(d[15]), "+f"(d[16]), "+f"(d[17]), "+f"(d[18]), "+f"(d[19]), "+f"(d[20]), "+f"(d[21]), "+f"(d[22]), "+f"(d[23]), "+f"(d[24]), "+f"(d[25]), "+f"(d[26]), "+f"(d[27]), "+f"(d[28]), "+f"(d[29]), "+f"(d[30]), "+f"(d[31])
    : "r"(a0), "r"(a1), "r"(a2), "r"(a3), "l"(db));
}
DEVI void wgmma_qk128a(float (&d)[64], uint32_t a0, uint32_t a1, uint32_t a2, uint32_t a3, uint64_t db) {
  asm volatile("wgmma.mma_async.sync.aligned.m64n128k16.f32.bf16.bf16 {%0, %1, %2, %3, %4, %5, %6, %7, %8, %9, %10, %11, %12, %13, %14, %15, %16, %17, %18, %19, %20, %21, %22, %23, %24, %25, %26, %27, %28, %29, %30, %31, %32, %33, %34, %35, %36, %37, %38, %39, %40, %41, %42, %43, %44, %45, %46, %47, %48, %49, %50, %51, %52, %53, %54, %55, %56, %57, %58, %59, %60, %61, %62, %63}, {%64, %65, %66, %67}, %68, 1, 1, 1, 0;"
    : "+f"(d[0]), "+f"(d[1]), "+f"(d[2]), "+f"(d[3]), "+f"(d[4]), "+f"(d[5]), "+f"(d[6]), "+f"(d[7]), "+f"(d[8]), "+f"(d[9]), "+f"(d[10]), "+f"(d[11]), "+f"(d[12]), "+f"(d[13]), "+f"(d[14]), "+f"(d[15]), "+f"(d[16]), "+f"(d[17]), "+f"(d[18]), "+f"(d[19]), "+f"(d[20]), "+f"(d[21]), "+f"(d[22]), "+f"(d[23]), "+f"(d[24]), "+f"(d[25]), "+f"(d[26]), "+f"(d[27]), "+f"(d[28]), "+f"(d[29]), "+f"(d[30]), "+f"(d[31]), "+f"(d[32]), "+f"(d[33]), "+f"(d[34]), "+f"(d[35]), "+f"(d[36]), "+f"(d[37]), "+f"(d[38]), "+f"(d[39]), "+f"(d[40]), "+f"(d[41]), "+f"(d[42]), "+f"(d[43]), "+f"(d[44]), "+f"(d[45]), "+f"(d[46]), "+f"(d[47]), "+f"(d[48]), "+f"(d[49]), "+f"(d[50]), "+f"(d[51]), "+f"(d[52]), "+f"(d[53]), "+f"(d[54]), "+f"(d[55]), "+f"(d[56]), "+f"(d[57]), "+f"(d[58]), "+f"(d[59]), "+f"(d[60]), "+f"(d[61]), "+f"(d[62]), "+f"(d[63])
    : "r"(a0), "r"(a1), "r"(a2), "r"(a3), "l"(db));
}
DEVI void wgmma_pv(float (&d)[8], uint32_t a0, uint32_t a1, uint32_t a2, uint32_t a3, uint64_t db) {
  asm volatile("wgmma.mma_async.sync.aligned.m64n16k16.f32.bf16.bf16 {%0, %1, %2, %3, %4, %5, %6, %7}, {%8, %9, %10, %11}, %12, 1, 1, 1, 1;"
    : "+f"(d[0]), "+f"(d[1]), "+f"(d[2]), "+f"(d[3]), "+f"(d[4]), "+f"(d[5]), "+f"(d[6]), "+f"(d[7])
    : "r"(a0), "r"(a1), "r"(a2), "r"(a3), "l"(db));
}
DEVI void wgmma_pv0(float (&d)[8], uint32_t a0, uint32_t a1, uint32_t a2, uint32_t a3, uint64_t db) {
  asm volatile("wgmma.mma_async.sync.aligned.m64n16k16.f32.bf16.bf16 {%0, %1, %2, %3, %4, %5, %6, %7}, {%8, %9, %10, %11}, %12, 0, 1, 1, 1;"
    : "=f"(d[0]), "=f"(d[1]), "=f"(d[2]), "=f"(d[3]), "=f"(d[4]), "=f"(d[5]), "=f"(d[6]), "=f"(d[7])
    : "r"(a0), "r"(a1), "r"(a2), "r"(a3), "l"(db));
}

template <int N> DEVI void wgmma_ss(float (&d)[N / 2], uint64_t da, uint64_t db) {
  if constexpr (N == 64) wgmma_ss_n64(d, da, db);
  else if constexpr (N == 128) wgmma_ss_n128(d, da, db);
  else if constexpr (N == 192) wgmma_ss_n192(d, da, db);
  else wgmma_ss_n256(d, da, db);
}

DEVI int oh_chunk(int j, int i, int& need) {
  if (j & 1) {
    if (i >= 3 && i < 7) { need = 16 + 2 * (i - 3); return 24 + (i - 3); }
    if (i >= 7) i -= 4;
  }
  const int g = i / 3, o = (j + 2 * g) & 7;
  need = o;
  return 3 * o + (i - 3 * g);
}

struct Ctx {
  uint32_t sbase, bars, peer, t0, a16, b16;
  int wg, lane;
  int ai, bi; uint32_t aph, bph;
  int pa, pb;
};

DEVI void release_prev(Ctx& c) {
  if (c.pb >= 0) {
    if (c.lane == 0) mbar_arrive(c.bars + 8 * (BAR_EMPTYB + c.pb));
    if (c.lane == 1) mbar_arrive_cluster(c.bars + 8 * (BAR_EMPTYB + c.pb), c.peer);
  }
  if (c.pa >= 0 && c.lane == 2) mbar_arrive(c.bars + 8 * (BAR_EMPTYA + c.pa));
}

DEVI void gemm_wait(Ctx& c) {
  asm volatile("{ .reg .pred p, q; .reg .u32 c;\n"
               "WAIT_%=:\n"
               "mbarrier.try_wait.parity.shared::cta.b64 p, [%0], %1;\n"
               "mbarrier.try_wait.parity.shared::cta.b64 q, [%2], %3;\n"
               "and.pred p, p, q;\n"
               "@p bra DONE_%=;\n"
               "mov.u32 c, %%clock; sub.u32 c, c, %4; setp.lt.u32 p, c, %5;\n"
               "@p bra WAIT_%=;\n"
               "DONE_%=: }" ::"r"(c.bars + 8 * (BAR_FULLA + c.ai)), "r"(c.aph), "r"(c.bars + 8 * (BAR_FULLB + c.bi)), "r"(c.bph), "r"(c.t0), "n"(TIMEOUT) : "memory");
}
template <int N>
DEVI void gemm_group(float (&acc)[N / 2], Ctx& c, int g, int& npa, int& npb) {
  const uint32_t a16 = c.a16 + c.ai * (SLOT >> 4);
  const uint32_t b16 = c.b16 + c.bi * (SLOT >> 4);
  bool adv;
  if constexpr (N >= 192) {
    const uint32_t a2 = a16 + (g & 1) * 4;
    wgmma_ss<N>(acc, desc_sw128<16>(a2), desc_sw128<2048>(b16));
    wgmma_ss<N>(acc, desc_sw128<16>(a2 + 2), desc_sw128<2048>(b16 + 512));
    adv = g & 1;
  } else {
#pragma unroll
    for (int s = 0; s < 4; s++) wgmma_ss<N>(acc, desc_sw128<16>(a16 + s * 2), desc_sw128<4096>(b16 + (s >> 1) * 512 + (s & 1) * 128));
    adv = true;
  }
  wgmma_commit();
  npb = c.bi;
  if (++c.bi == NB) { c.bi = 0; c.bph ^= 1; }
  npa = -1;
  if (adv) { npa = c.ai; if (++c.ai == NA) { c.ai = 0; c.aph ^= 1; } }
}

template <int N>
DEVI void bare_groups(float (&acc)[N / 2], Ctx& c, int g0, int g1) {
  for (int g = g0; g < g1; g++) {
    int npa, npb;
    gemm_wait(c);
    wgmma_fence();
    gemm_group<N>(acc, c, g, npa, npb);
    wgmma_wait<1>();
    release_prev(c);
    c.pa = npa; c.pb = npb;
  }
}
DEVI void drain(Ctx& c) {
  wgmma_wait<0>();
  release_prev(c);
  c.pa = c.pb = -1;
}

constexpr float SC = 0.25f * 1.4426950408889634f;

#define ONCE _Pragma("unroll 1") for (unsigned once_ = 0; once_ < gridDim.y; once_++)

struct Attn {
  uint32_t q[4][4];
  uint32_t nm[4];
  float g0, g1;
  int cmin;
  int rowc;
};

template <int O0, int NS>
DEVI void kill32(float (&S)[NS]) {
#pragma unroll
  for (int i = 0; i < 32; i++) S[O0 + i] = __int_as_float(0xff800000);
}
DEVI void row_max(const float (&S)[64], float& x0, float& x1) {
#pragma unroll
  for (int n = 0; n < 16; n++) {
    x0 = fmaxf(x0, fmaxf(S[4 * n], S[4 * n + 1])); x1 = fmaxf(x1, fmaxf(S[4 * n + 2], S[4 * n + 3]));
  }
}
DEVI void exp64(float (&S)[64]) {
#pragma unroll
  for (int n = 0; n < 64; n++) S[n] = ex2(S[n]);
}
DEVI void pack64(const float (&S)[64], uint32_t (&P)[32], float& l0, float& l1) {
  float k0 = 0.f, k1 = 0.f;
#pragma unroll
  for (int n = 0; n < 16; n++) {
    l0 += S[4 * n]; k0 += S[4 * n + 1]; l1 += S[4 * n + 2]; k1 += S[4 * n + 3];
    P[2 * n] = pack_bf16(S[4 * n], S[4 * n + 1]); P[2 * n + 1] = pack_bf16(S[4 * n + 2], S[4 * n + 3]);
  }
  l0 += k0; l1 += k1;
}
DEVI void merge_fl(float (&S)[64], const float (&F)[32], int rowc) {
#pragma unroll
  for (int n = 0; n < 8; n++) {
    if (n * 8 > rowc) S[32 + 4 * n] = F[4 * n];
    if (n * 8 + 1 > rowc) S[32 + 4 * n + 1] = F[4 * n + 1];
    if (n * 8 > rowc + 8) S[32 + 4 * n + 2] = F[4 * n + 2];
    if (n * 8 + 1 > rowc + 8) S[32 + 4 * n + 3] = F[4 * n + 3];
  }
}
DEVI uint32_t split3(float v, int ql) {
  const uint32_t hi = pack_bf16(v, 0.f);
  const float r1 = v - __uint_as_float(hi << 16);
  const uint32_t mid = pack_bf16(r1, 0.f);
  const uint32_t lo = pack_bf16(r1 - __uint_as_float(mid << 16), 0.f);
  return ql == 0 ? (hi | (mid << 16)) : ql == 1 ? lo : 0u;
}
DEVI bool wg_any(int wg, bool v) {
  uint32_t r;
  if (wg == 0) asm volatile("{ .reg .pred p, q; setp.ne.u32 p, %1, 0; bar.red.or.pred q, 1, 128, p; selp.u32 %0, 1, 0, q; }" : "=r"(r) : "r"((uint32_t)v) : "memory");
  else asm volatile("{ .reg .pred p, q; setp.ne.u32 p, %1, 0; bar.red.or.pred q, 2, 128, p; selp.u32 %0, 1, 0, q; }" : "=r"(r) : "r"((uint32_t)v) : "memory");
  return r != 0;
}

DEVI void attention(const Ctx& c, Attn& at, int wi) {
  const uint32_t kvb = ((c.sbase & 0x3FFFF) + OFF_KV + c.wg * 4096) >> 4;
  const uint64_t ones = (uint64_t)(((c.sbase & 0x3FFFF) + OFF_ONES) >> 4) | ((uint64_t)(128 >> 4) << 16);
  const bool q0lane = (c.lane & 3) == 0;
#pragma unroll 1
  for (int h = 0; h < 4; h++) {
    const uint32_t kb = kvb + (h & 1) * (KVBUF >> 4);
    const uint32_t q0 = at.q[0][0], q1 = at.q[0][1], q2 = at.q[0][2], q3 = at.q[0][3];
    uint32_t b0 = q0lane ? (at.nm[0] & 0xFFFFu) : 0u, b1 = q0lane ? (at.nm[0] >> 16) : 0u;
    float O[8], l0, l1;
    mbar_wait(c.bars + 8 * (BAR_KVFULL + (h & 1)), h >> 1, c.t0);
#pragma unroll 1
    for (int attempt = 0; attempt < 2; attempt++) {
      float S[64];
      uint32_t P[32];
      {
        float F[32];
        wgmma_fence();
        wgmma_qk128(S, q0, q1, q2, q3, desc_sw64(kb + 3 * 256));
        wgmma_qk128a(S, b0, b1, 0u, 0u, ones);
        wgmma_qk64(F, q0, q1, q2, q3, desc_sw64(kb));
        wgmma_qk64a(F, b0, b1, 0u, 0u, ones);
        wgmma_commit();
        wgmma_wait<0>();
        if (at.cmin > 0) { kill32<0>(F); if (at.cmin > 3) kill32<0>(S); }
        ONCE { merge_fl(S, F, at.rowc); }
      }
      if (attempt == 0) turn_wait(c.wg);
      ONCE { exp64(S); }
      if (attempt == 0) turn_pass(c.wg);
      l0 = 0.f; l1 = 0.f;
      pack64(S, P, l0, l1);
      {
        uint32_t PF[16];
#pragma unroll
        for (int n = 0; n < 8; n++) {
          const uint32_t k0 = (n * 8 > at.rowc ? 0xFFFFu : 0u) | (n * 8 + 1 > at.rowc ? 0xFFFF0000u : 0u);
          const uint32_t k1 = (n * 8 > at.rowc + 8 ? 0xFFFFu : 0u) | (n * 8 + 1 > at.rowc + 8 ? 0xFFFF0000u : 0u);
          PF[2 * n] = P[16 + 2 * n] & k0; P[16 + 2 * n] &= ~k0;
          PF[2 * n + 1] = P[16 + 2 * n + 1] & k1; P[16 + 2 * n + 1] &= ~k1;
        }
        wgmma_fence();
        wgmma_qk128(S, q0, q1, q2, q3, desc_sw64(kb + 256));
        wgmma_qk128a(S, b0, b1, 0u, 0u, ones);
        wgmma_commit();
        wgmma_pv0(O, P[0], P[1], P[2], P[3], desc_sw64(kb + 3 * 256 + 2));
#pragma unroll
        for (int k = 1; k < 8; k++) wgmma_pv(O, P[4 * k], P[4 * k + 1], P[4 * k + 2], P[4 * k + 3], desc_sw64(kb + 3 * 256 + 2 + k * 64));
#pragma unroll
        for (int k = 0; k < 4; k++) wgmma_pv(O, PF[4 * k], PF[4 * k + 1], PF[4 * k + 2], PF[4 * k + 3], desc_sw64(kb + 2 + k * 64));
        wgmma_commit();
        wgmma_wait<1>();
        if (at.cmin > 1) { kill32<0>(S); if (at.cmin > 2) kill32<32>(S); }
        if (attempt == 0) turn_wait(c.wg);
        ONCE { exp64(S); }
        if (attempt == 0) turn_pass(c.wg);
        wgmma_wait<0>();
      }
      pack64(S, P, l0, l1);
      wgmma_fence();
#pragma unroll
      for (int k = 0; k < 8; k++) wgmma_pv(O, P[4 * k], P[4 * k + 1], P[4 * k + 2], P[4 * k + 3], desc_sw64(kb + 256 + 2 + k * 64));
      wgmma_commit();
      l0 += __shfl_xor_sync(0xffffffffu, l0, 1); l1 += __shfl_xor_sync(0xffffffffu, l1, 1);
      l0 += __shfl_xor_sync(0xffffffffu, l0, 2); l1 += __shfl_xor_sync(0xffffffffu, l1, 2);
      wgmma_wait<0>();
      const bool bad = !(l0 > 1e-6f && l0 < 1e18f && l1 > 1e-6f && l1 < 1e18f);
      if (!wg_any(c.wg, bad) || attempt == 1) break;
      float x0 = __int_as_float(0xff800000), x1 = x0;
      {
        float F[32];
        wgmma_fence();
        wgmma_qk128(S, q0, q1, q2, q3, desc_sw64(kb + 3 * 256));
        wgmma_qk64(F, q0, q1, q2, q3, desc_sw64(kb));
        wgmma_commit();
        wgmma_wait<0>();
        if (at.cmin > 0) { kill32<0>(F); if (at.cmin > 3) kill32<0>(S); }
        merge_fl(S, F, at.rowc);
        row_max(S, x0, x1);
        wgmma_fence();
        wgmma_qk128(S, q0, q1, q2, q3, desc_sw64(kb + 256));
        wgmma_commit();
        wgmma_wait<0>();
        if (at.cmin > 1) { kill32<0>(S); if (at.cmin > 2) kill32<32>(S); }
        row_max(S, x0, x1);
      }
      x0 = fmaxf(x0, __shfl_xor_sync(0xffffffffu, x0, 1)); x1 = fmaxf(x1, __shfl_xor_sync(0xffffffffu, x1, 1));
      x0 = fmaxf(x0, __shfl_xor_sync(0xffffffffu, x0, 2)); x1 = fmaxf(x1, __shfl_xor_sync(0xffffffffu, x1, 2));
      b0 = split3(-x0, c.lane & 3); b1 = split3(-x1, c.lane & 3);
    }
    const float c0 = at.g0 / l0, c1 = at.g1 / l1;
    const uint32_t ost = c.sbase + OFF_KV + (h & 1) * KVBUF + c.wg * 20480;
    const int mi = c.lane >> 3;
    const int srow = wi * 16 + (c.lane & 7) + 8 * (mi & 1);
    stsm_x4(ost + srow * 32 + (mi >> 1) * 16, pack_bf16(O[0] * c0, O[1] * c0), pack_bf16(O[2] * c1, O[3] * c1),
            pack_bf16(O[4] * c0, O[5] * c0), pack_bf16(O[6] * c1, O[7] * c1));
    fence_async_smem();
    __syncwarp();
    if (c.lane == 0) mbar_arrive(c.bars + 8 * (BAR_STG + c.wg));
#pragma unroll
    for (int i = 0; i < 4; i++) { at.q[0][i] = at.q[1][i]; at.q[1][i] = at.q[2][i]; at.q[2][i] = at.q[3][i]; }
    at.nm[0] = at.nm[1]; at.nm[1] = at.nm[2]; at.nm[2] = at.nm[3];
  }
}

template <int CH, int NACC>
DEVI void store_h_chunk(const float (&acc)[NACC], uint32_t base  , int lane, float s0, float s1) {
  const int mi = lane >> 3;
#pragma unroll
  for (int tp = 0; tp < 4; tp++) {
    const int t = CH * 8 + tp * 2;
    const uint32_t r0 = pack_bf16(fmaxf(acc[4 * t + 0], 0.f) * s0, fmaxf(acc[4 * t + 1], 0.f) * s0);
    const uint32_t r1 = pack_bf16(fmaxf(acc[4 * t + 2], 0.f) * s1, fmaxf(acc[4 * t + 3], 0.f) * s1);
    const uint32_t r2 = pack_bf16(fmaxf(acc[4 * t + 4], 0.f) * s0, fmaxf(acc[4 * t + 5], 0.f) * s0);
    const uint32_t r3 = pack_bf16(fmaxf(acc[4 * t + 6], 0.f) * s1, fmaxf(acc[4 * t + 7], 0.f) * s1);
    stsm_x4(base + (((tp * 2 + (mi >> 1)) ^ (lane & 7)) << 4), r0, r1, r2, r3);
  }
}

template <int N>
DEVI void phase_q(Ctx& c, Attn& at, int warp, const unsigned* gflag, unsigned gtgt, const float* gp) {
  float acc[N / 2];
#pragma unroll
  for (int i = 0; i < N / 2; i++) acc[i] = 0.f;
  bare_groups<N>(acc, c, 0, 12);
  if (c.lane == 0) flag_wait(gflag, gtgt, c.t0);
  __syncwarp();
  at.g0 = ld_relaxed_f(gp); at.g1 = ld_relaxed_f(gp + 8);
  bare_groups<N>(acc, c, 12, 16);
  drain(c);
  const int lane = c.lane, mi = lane >> 3;
  const int row = warp * 16 + (lane & 7) + 8 * (mi & 1);
  const int sw = (row >> 1) & 3;
#pragma unroll
  for (int hh = 0; hh < 4; hh++) {
    const uint32_t base = c.sbase + OFF_KV + hh * 8192 + row * 64;
#pragma unroll
    for (int kv = 0; kv < 2; kv++) {
      const int t = 8 + kv * 8 + 2 * hh;
      stsm_x4(base + (((kv * 2 + (mi >> 1)) ^ sw) << 4),
              pack_bf16(acc[4 * t + 0], acc[4 * t + 1]), pack_bf16(acc[4 * t + 2], acc[4 * t + 3]),
              pack_bf16(acc[4 * t + 4], acc[4 * t + 5]), pack_bf16(acc[4 * t + 6], acc[4 * t + 7]));
    }
  }
  if constexpr (N == 256) store_h_chunk<3>(acc, c.sbase + OFF_KV + 32768 + row * 128, lane, 1.f - at.g0, 1.f - at.g1);
  fence_async_smem();
  __syncwarp();
  if (lane == 0) mbar_arrive(c.bars + 8 * (BAR_STG + c.wg));
#pragma unroll
  for (int hh = 0; hh < 4; hh++) {
#pragma unroll
    for (int i = 0; i < 4; i++) at.q[hh][i] = pack_bf16(acc[8 * hh + 2 * i] * SC, acc[8 * hh + 2 * i + 1] * SC);
    const float* q = &acc[8 * hh];
    const float* k = &acc[32 + 8 * hh];
    float d0 = q[0] * k[0] + q[1] * k[1] + q[4] * k[4] + q[5] * k[5], d1 = q[2] * k[2] + q[3] * k[3] + q[6] * k[6] + q[7] * k[7];
    d0 += __shfl_xor_sync(0xffffffffu, d0, 1); d1 += __shfl_xor_sync(0xffffffffu, d1, 1);
    d0 += __shfl_xor_sync(0xffffffffu, d0, 2); d1 += __shfl_xor_sync(0xffffffffu, d1, 2);
    at.nm[hh] = pack_bf16(-d0 * SC, -d1 * SC);
  }
}

__global__ void __cluster_dims__(2, 1, 1) __launch_bounds__(384, 1) fused_kernel(const __grid_constant__ Params P) {
  extern __shared__ uint8_t smem_raw[];
  const uint32_t sbase = (smem_u32(smem_raw) + 1023u) & ~1023u;
  const uint32_t bars = sbase + OFF_BAR;
  const int tid = threadIdx.x, warp = tid >> 5, lane = tid & 31;
  const uint32_t rank = blockIdx.x & 1, peer = rank ^ 1;
  const int j = (blockIdx.x >> 1) & 7, rb = ((blockIdx.x >> 4) << 1) | rank;
  const uint32_t t0 = clk32();

  if (tid == 0) {
    for (int s = 0; s < NA; s++) { mbar_init(bars + 8 * (BAR_FULLA + s), 1); mbar_init(bars + 8 * (BAR_EMPTYA + s), 10); }
    for (int s = 0; s < NB; s++) { mbar_init(bars + 8 * (BAR_FULLB + s), 1); mbar_init(bars + 8 * (BAR_EMPTYB + s), 16); }
    for (int s = 0; s < 2; s++) { mbar_init(bars + 8 * (BAR_KVFULL + s), 1); mbar_init(bars + 8 * (BAR_KVEMPTY + s), 2); mbar_init(bars + 8 * (BAR_STG + s), 4); }
    mbar_init(bars + 8 * BAR_PIN, 1); mbar_init(bars + 8 * BAR_GATE, 1); mbar_init(bars + 8 * (BAR_GATE + 1), 1);
    asm volatile("fence.mbarrier_init.release.cluster;" ::: "memory");
  }
  const unsigned ep1 = ld_relaxed(&g_epoch) + 1;
  __syncthreads();
  cluster_arrive();

  const int typeB = j & 1;
  const int on = 12 + 4 * typeB;

  if (warp < 8) {
    asm volatile("setmaxnreg.inc.sync.aligned.u32 232;");
    cluster_wait();
    const int wg = __shfl_sync(0xffffffffu, warp >> 2, 0), wi = warp & 3;
    Ctx c{sbase, bars, peer, t0, ((sbase & 0x3FFFF) + OFF_A + wg * 8192) >> 4, ((sbase & 0x3FFFF) + OFF_B) >> 4, wg, lane, 0, 0, 0u, 0u, -1, -1};
    Attn at;
    at.cmin = 4 - 2 * rb - wg;
    at.rowc = wi * 16 + (lane >> 2) - (lane & 3) * 2;
    const int row0 = rb * 128 + warp * 16 + (lane >> 2);
    if (tid == 0) TR(0);
    if (typeB) phase_q<192>(c, at, warp, &g_flag_g[rb * FS], ep1 * 16, &g_gate[row0]);
    else phase_q<256>(c, at, warp, &g_flag_g[rb * FS], ep1 * 16, &g_gate[row0]);
    if (tid == 0) TR(2);
    {
      float acc[96];
#pragma unroll
      for (int i = 0; i < 96; i++) acc[i] = 0.f;
      bare_groups<192>(acc, c, 0, 16);
      drain(c);
      if (tid == 0) TR(1);
      const uint32_t rowoff = (warp * 16 + (lane & 7) + 8 * ((lane >> 3) & 1)) * 128;
      const float s0 = 1.f - at.g0, s1 = 1.f - at.g1;
      constexpr int e0 = 16 % NA, e1 = 17 % NA, e2 = 18 % NA;
      mbar_wait(bars + 8 * (BAR_FULLA + e0), (16 / NA) & 1, t0);
      store_h_chunk<0>(acc, sbase + OFF_A + e0 * SLOT + rowoff, lane, s0, s1);
      mbar_wait(bars + 8 * (BAR_FULLA + e1), (17 / NA) & 1, t0);
      store_h_chunk<1>(acc, sbase + OFF_A + e1 * SLOT + rowoff, lane, s0, s1);
      mbar_wait(bars + 8 * (BAR_FULLA + e2), (18 / NA) & 1, t0);
      store_h_chunk<2>(acc, sbase + OFF_A + e2 * SLOT + rowoff, lane, s0, s1);
    }
    fence_async_smem();
    wg_bar(wg);
    if (lane == 0) mbar_arrive(bars + 8 * (BAR_STG + wg));
    if (tid == 0) TR(4);
    if (wg == 1) turn_pass(1);
    attention(c, at, wi);
    if (wg == 0) turn_wait(0);
    if (tid == 0) TR(3);
    float own[32];
    {
      float acc[64];
#pragma unroll
      for (int i = 0; i < 64; i++) acc[i] = 0.f;
      bare_groups<128>(acc, c, 0, on);
      drain(c);
      if (tid == 0) TR(5);
      mbar_wait(bars + 8 * (BAR_KVEMPTY + 0), 1, t0);
      const uint32_t pst = sbase + OFF_KV + wg * 8192 + (tid & 127) * 16;
#pragma unroll
      for (int i = 0; i < 4; i++) {
        uint32_t r[4];
#pragma unroll
        for (int k = 0; k < 4; k++) {
          const int idx = 8 * i + 2 * k;
          const float lo = typeB ? acc[idx] : acc[32 + idx], hi = typeB ? acc[idx + 1] : acc[32 + idx + 1];
          r[k] = pack_bf16(lo, hi);
        }
        sts128(pst + i * 2048, r[0], r[1], r[2], r[3]);
      }
#pragma unroll
      for (int i = 0; i < 32; i++) own[i] = typeB ? acc[32 + i] : acc[i];
      fence_async_smem();
      __syncwarp();
      if (lane == 0) mbar_arrive(bars + 8 * (BAR_STG + wg));
    }
    for (int g = 0; g < 8; g++) {
      const uint32_t a16 = c.a16 + c.ai * (SLOT >> 4);
      const uint32_t b16 = c.b16 + c.bi * (SLOT >> 4) + (g & 1) * 512;
      mbar_wait(bars + 8 * (BAR_FULLB + c.bi), c.bph, t0);
      mbar_wait(bars + 8 * (BAR_FULLA + c.ai), c.aph, t0);
      wgmma_fence();
#pragma unroll
      for (int s = 0; s < 4; s++) wgmma_ss<64>(own, desc_sw128<16>(a16 + s * 2), desc_sw128<2048>(b16 + s * 128));
      wgmma_commit();
      wgmma_wait<1>();
      release_prev(c);
      c.pa = c.ai; c.pb = -1;
      if (++c.ai == NA) { c.ai = 0; c.aph ^= 1; }
      if (g & 1) { if (++c.bi == NB) { c.bi = 0; c.bph ^= 1; } }
    }
    wgmma_wait<0>();
    if (tid == 0) TR(6);
    mbar_wait(bars + 8 * BAR_PIN, 0, t0);
    if (tid == 0) TR(7);
    {
      const uint32_t pin = sbase + OFF_KV + KVBUF + wg * 8192 + (tid & 127) * 16;
      __nv_bfloat16* o = P.out + (size_t)row0 * DM + j * 64 + (lane & 3) * 2;
#pragma unroll
      for (int i = 0; i < 4; i++) {
        const uint4 v = lds128(pin + i * 2048);
        const uint32_t r[4] = {v.x, v.y, v.z, v.w};
#pragma unroll
        for (int k = 0; k < 4; k++) {
          const int idx = 8 * i + 2 * k;
          const float lo = own[idx] + __uint_as_float(r[k] << 16), hi = own[idx + 1] + __uint_as_float(r[k] & 0xffff0000u);
          *(uint32_t*)(o + (k & 1) * 8 * DM + (2 * i + (k >> 1)) * 8) = pack_bf16(lo, hi);
        }
      }
    }
    if (tid == 0) TR(8);
    if (tid == 0) {
      const unsigned old = atomicAdd(&g_done, 1u);
      if (old == gridDim.x - 1) { g_done = 0; *(volatile unsigned*)&g_epoch = ep1; }
    }
    __syncwarp();
    cluster_arrive(); cluster_wait();
  } else {
    asm volatile("setmaxnreg.dec.sync.aligned.u32 40;");
    if (warp == 8) {
      cluster_wait();
      if (lane == 0) {
        int bi = 0; uint32_t bph = 1;
        const int nb = 32 + on + 4;
        for (int eb = 0; eb < nb; eb++) {
          const uint32_t fb = bars + 8 * (BAR_FULLB + bi), dst = sbase + OFF_B + bi * SLOT + rank * 8192;
          mbar_wait(bars + 8 * (BAR_EMPTYB + bi), bph, t0);
          if (eb < 16) {
            mbar_expect_tx(fb, typeB ? 12288 : 16384);
            tma_load_3d_mc(dst, &P.tmWqkv, 64 * j, eb * 32 + rank * 16, 0, fb);
            if (!typeB) tma_load_3d_mc(dst + 6144, &P.tmW1a, 0, eb * 32 + rank * 16, 24 + (j >> 1), fb);
          }
          else if (eb < 32) { mbar_expect_tx(fb, 12288); tma_load_3d_mc(dst, &P.tmW1b, 0, (eb - 16) * 32 + rank * 16, 3 * j, fb); }
          else if (eb < 32 + on) { int ow; const int ch = oh_chunk(j, eb - 32, ow); mbar_expect_tx(fb, 16384); tma_load_3d_mc(dst, &P.tmW2, 0, ch * 64 + rank * 32, (j >> 1) * 2, fb); }
          else { mbar_expect_tx(fb, 16384); tma_load_4d_mc(dst, &P.tmWo, 64 * j, 0, eb - 32 - on, rank * 4, fb); }
          if (++bi == NB) { bi = 0; bph ^= 1; }
          if (eb == 5) {
            const int b = blockIdx.x;
            l2_prefetch((const uint8_t*)P.w1 + b * 14336, 14336);
            l2_prefetch((const uint8_t*)P.w2 + b * 14336, 14336);
            l2_prefetch((const uint8_t*)P.wo + b * 4096, 4096);
          }
        }
      }
    } else if (warp == 9) {
      if (lane == 0) {
        for (int ea = 0; ea < NA; ea++) {
          mbar_arrive_n(bars + 8 * (BAR_EMPTYA + ea), 2);
          mbar_expect_tx(bars + 8 * (BAR_FULLA + ea), 16384);
          tma_load_2d(sbase + OFF_A + ea * SLOT, &P.tmX, ea * 64, rb * 128, bars + 8 * (BAR_FULLA + ea));
        }
      }
      __syncwarp();
      cluster_wait();
      for (int i = 0; i < 32; i++) sts128(sbase + OFF_KV + 32768 + i * 512 + lane * 16, 0u, 0u, 0u, 0u);
      if (lane < 16) sts128(sbase + OFF_ONES + lane * 16, lane < 8 ? 0x3F803F80u : 0u, lane < 8 ? 0x3F80u : 0u, 0u, 0u);
      fence_async_smem();
      __syncwarp();
      if (lane == 0) {
        int ai = 0; uint32_t aph = 0;
        const int na = 16 + on + 8;
        unsigned ready = 0;
        for (int ea = NA; ea < na; ea++) {
          const uint32_t fb = bars + 8 * (BAR_FULLA + ai), dst = sbase + OFF_A + ai * SLOT;
          int ch = ea & 7, need = -1;
          if (ea >= 16 + on) { need = 8 + ea - 16 - on; ch = 20 + need; }
          else if (ea >= 19) ch = oh_chunk(j, ea - 16, need);
          if (need >= 0 && !((ready >> need) & 1)) {
            const unsigned* fp = need < 8 ? &g_flag_h[rb * 8 * FS] : need < 16 ? &g_flag_o[rb * 8 * FS] : &g_flag_kv[rb * 8 * FS];
            const unsigned tgt = (need & 8) ? ep1 * 8 : ep1 * 2;
            do {
              unsigned v[8];
#pragma unroll
              for (int i = 0; i < 8; i++) v[i] = ld_relaxed(fp + i * FS);
#pragma unroll
              for (int i = 0; i < 8; i++) if ((int)(v[i] - tgt) >= 0) ready |= 1u << (i + (need & 24));
            } while (!((ready >> need) & 1) && clk32() - t0 < TIMEOUT);
            fence_async_global();
          }
          mbar_wait(bars + 8 * (BAR_EMPTYA + ai), aph, t0);
          if (ea >= 16 && ea < 19) mbar_arrive(fb);
          else {
            mbar_arrive_n(bars + 8 * (BAR_EMPTYA + ai), 2);
            mbar_expect_tx(fb, 16384);
            tma_load_2d(dst, ea < 16 ? &P.tmX : &P.tmHO, ch * 64, rb * 128, fb);
          }
          TR(24 + ea);
          if (++ai == NA) { ai = 0; aph ^= 1; }
        }
      }
    } else {
      const int wg = warp - 10;
      {
        const int rowg = rb * 128 + j * 16 + wg * 8;
        const uint32_t xs = sbase + OFF_KV + wg * 8192;
        if (lane == 0) {
          mbar_expect_tx(bars + 8 * (BAR_GATE + wg), 8192);
          bulk_load(xs, P.x + (size_t)rowg * DM, 8192, bars + 8 * (BAR_GATE + wg));
        }
        const uint4* gw = (const uint4*)P.gate_w;
        const uint4 w0 = __ldg(gw + lane), w1 = __ldg(gw + 32 + lane);
        const uint32_t wa[8] = {w0.x, w0.y, w0.z, w0.w, w1.x, w1.y, w1.z, w1.w};
        cluster_wait();
        mbar_wait(bars + 8 * (BAR_GATE + wg), 0, t0);
        float zz = 0.f;
#pragma unroll 1
        for (int i = 0; i < 8; i++) {
          const uint4 x0 = lds128(xs + i * 1024 + lane * 16), x1 = lds128(xs + i * 1024 + 512 + lane * 16);
          const uint32_t xa[8] = {x0.x, x0.y, x0.z, x0.w, x1.x, x1.y, x1.z, x1.w};
          float z = 0.f;
#pragma unroll
          for (int e = 0; e < 8; e++) {
            z = fmaf(__uint_as_float(xa[e] << 16), __uint_as_float(wa[e] << 16), z);
            z = fmaf(__uint_as_float(xa[e] & 0xffff0000u), __uint_as_float(wa[e] & 0xffff0000u), z);
          }
#pragma unroll
          for (int o = 16; o > 0; o >>= 1) z += __shfl_xor_sync(0xffffffffu, z, o);
          if (lane == i) zz = z;
        }
        if (lane < 8) asm volatile("st.shared.f32 [%0], %1;" ::"r"(sbase + OFF_GST + wg * 32 + lane * 4), "f"(1.f / (1.f + __expf(-zz))) : "memory");
        fence_async_smem();
        __syncwarp();
        if (lane == 0) {
          bulk_store(&g_gate[rowg], sbase + OFF_GST + wg * 32, 32);
          bulk_commit(); bulk_wait_all();
          flag_add(&g_flag_g[rb * FS]);
          if (wg == 0) TR(10);
        }
      }
      if (lane == 0) {
        const uint32_t stg = bars + 8 * (BAR_STG + wg);
        mbar_wait(stg, 0, t0);
        for (int hh = 0; hh < 4; hh++)
          bulk_store(g_kv + ((size_t)(4 * j + hh) * SEQ + rb * 128 + wg * 64) * 64, sbase + OFF_KV + hh * 8192 + wg * 4096, 4096);
        if (!typeB) tma_store_2d(&P.tmHOs, (24 + (j >> 1)) * 64, rb * 128 + wg * 64, sbase + OFF_KV + 32768 + wg * 8192);
        bulk_commit(); bulk_wait_all();
        flag_add(&g_flag_kv[(rb * 8 + j) * FS]);
        if (wg == 0) TR(21);
        const int nblk = rb >= 2 ? 3 : rb + 1;
        const uint32_t kvbytes = nblk * 8192;
        const uint8_t* kvsrc = g_kv + ((size_t)(4 * j) * SEQ + (rb + 1 - nblk) * 128) * 64;
        const uint32_t kvdst = sbase + OFF_KV + wg * KVBUF + (3 - nblk) * 8192;
        {
          const unsigned* f0 = &g_flag_kv[(rb * 8 + j) * FS];
          const unsigned* f1 = rb >= 1 ? f0 - 8 * FS : f0;
          const unsigned* f2 = rb >= 2 ? f0 - 16 * FS : f0;
          unsigned v0, v1, v2;
          do { v0 = ld_relaxed(f0); v1 = ld_relaxed(f1); v2 = ld_relaxed(f2); }
          while (((int)(v0 - ep1 * 2) < 0 || (int)(v1 - ep1 * 2) < 0 || (int)(v2 - ep1 * 2) < 0) && clk32() - t0 < TIMEOUT);
        }
        if (wg == 0) TR(11);
        fence_async_global();
        mbar_expect_tx(bars + 8 * (BAR_KVFULL + wg), kvbytes);
        bulk_load(kvdst, kvsrc + (size_t)wg * SEQ * 64, kvbytes, bars + 8 * (BAR_KVFULL + wg));
        for (int ev = 1; ev < 7; ev++) {
          mbar_wait(stg, ev & 1, t0);
          if (ev == 1) {
            for (int i = 0; i < 3; i++)
              tma_store_2d(&P.tmHOs, (3 * j + i) * 64, rb * 128 + wg * 64, sbase + OFF_A + ((16 + i) % NA) * SLOT + wg * 8192);
            bulk_commit(); bulk_wait_all();
            flag_add(&g_flag_h[(rb * 8 + j) * FS]);
            for (int i = 0; i < 3; i++) mbar_arrive(bars + 8 * (BAR_EMPTYA + (16 + i) % NA));
            if (wg == 0) TR(22);
          } else if (ev == 6) {
            bulk_store(g_part + (size_t)(rb * 8 + (j ^ 1)) * 16384 + wg * 8192, sbase + OFF_KV + wg * 8192, 8192);
            bulk_commit(); bulk_wait_all();
            flag_add(&g_flag_p[(rb * 8 + (j ^ 1)) * FS]);
            if (wg == 0) TR(23);
            if (wg == 1) {
              mbar_wait(bars + 8 * (BAR_KVEMPTY + 1), 1, t0);
              flag_wait(&g_flag_p[(rb * 8 + j) * FS], ep1 * 2, t0);
              fence_async_global();
              mbar_expect_tx(bars + 8 * BAR_PIN, 16384);
              bulk_load(sbase + OFF_KV + KVBUF, g_part + (size_t)(rb * 8 + j) * 16384, 16384, bars + 8 * BAR_PIN);
            }
          } else {
            const int hh = ev - 2;
            tma_store_2d(&P.tmOs, DFF + hh * 128 + j * 16, rb * 128 + wg * 64, sbase + OFF_KV + (hh & 1) * KVBUF + wg * 20480);
            bulk_commit(); bulk_wait_all();
            flag_add(&g_flag_o[(rb * 8 + hh * 2 + (j >> 2)) * FS]);
            mbar_arrive(bars + 8 * (BAR_KVEMPTY + (hh & 1)));
            if (wg == 0) TR(12 + hh);
            if (hh == wg) {
              mbar_wait(bars + 8 * (BAR_KVEMPTY + wg), 0, t0);
              mbar_expect_tx(bars + 8 * (BAR_KVFULL + wg), kvbytes);
              bulk_load(kvdst, kvsrc + (size_t)(wg + 2) * SEQ * 64, kvbytes, bars + 8 * (BAR_KVFULL + wg));
            }
          }
        }
      }
    }
    __syncwarp();
    cluster_arrive(); cluster_wait();
  }
}

typedef CUresult (*EncodeFn)(CUtensorMap*, CUtensorMapDataType, cuuint32_t, void*, const cuuint64_t*, const cuuint64_t*, const cuuint32_t*,
                             const cuuint32_t*, CUtensorMapInterleave, CUtensorMapSwizzle, CUtensorMapL2promotion, CUtensorMapFloatOOBfill);

void make_map(EncodeFn enc, CUtensorMap* m, const void* ptr, int rank, const cuuint64_t* dims, const cuuint64_t* strides, const cuuint32_t* box,
              CUtensorMapSwizzle sw = CU_TENSOR_MAP_SWIZZLE_128B) {
  cuuint32_t es[4] = {1, 1, 1, 1};
  enc(m, CU_TENSOR_MAP_DATA_TYPE_BFLOAT16, rank, const_cast<void*>(ptr), dims, strides, box, es, CU_TENSOR_MAP_INTERLEAVE_NONE, sw,
      CU_TENSOR_MAP_L2_PROMOTION_L2_256B, CU_TENSOR_MAP_FLOAT_OOB_FILL_NONE);
}

}

extern "C" void kernel_launch(void* const* d_in, const int* in_sizes, int n_in, void* d_out, int out_size) {
  (void)in_sizes; (void)n_in; (void)out_size;
  static EncodeFn enc = nullptr;
  static void* ho_ptr = nullptr;
  if (!enc) {
    void* fn = nullptr; cudaDriverEntryPointQueryResult st;
    cudaGetDriverEntryPoint("cuTensorMapEncodeTiled", &fn, cudaEnableDefault, &st);
    enc = (EncodeFn)fn;
    cudaGetSymbolAddress(&ho_ptr, g_ho);
    cudaFuncSetAttribute(fused_kernel, cudaFuncAttributeMaxDynamicSharedMemorySize, SMEM_BYTES);
  }
  const __nv_bfloat16* x = (const __nv_bfloat16*)d_in[0];
  const __nv_bfloat16* wqkv = (const __nv_bfloat16*)d_in[1];
  const __nv_bfloat16* wo = (const __nv_bfloat16*)d_in[2];
  const __nv_bfloat16* w1 = (const __nv_bfloat16*)d_in[4];
  const __nv_bfloat16* w2 = (const __nv_bfloat16*)d_in[5];
  const __nv_bfloat16* gate_w = (const __nv_bfloat16*)d_in[6];
  Params P;
  { cuuint64_t d[2] = {DM, SEQ}, s[1] = {DM * 2}; cuuint32_t b[2] = {64, 128}; make_map(enc, &P.tmX, x, 2, d, s, b); }
  { cuuint64_t d[3] = {512, 512, 3}, s[2] = {1536 * 2, 512 * 2}; cuuint32_t b[3] = {64, 16, 3}; make_map(enc, &P.tmWqkv, wqkv, 3, d, s, b); }
  { cuuint64_t d[3] = {64, 512, 28}, s[2] = {DFF * 2, 128}; cuuint32_t b[3] = {64, 16, 1}; make_map(enc, &P.tmW1a, w1, 3, d, s, b);
    b[2] = 3; make_map(enc, &P.tmW1b, w1, 3, d, s, b); }
  { cuuint64_t d[3] = {64, DFF, 8}, s[2] = {DM * 2, 128}; cuuint32_t b[3] = {64, 32, 2}; make_map(enc, &P.tmW2, w2, 3, d, s, b); }
  { cuuint64_t d[4] = {DM, 16, 4, 8}, s[3] = {DM * 2, 16 * DM * 2, 64 * DM * 2}; cuuint32_t b[4] = {64, 16, 1, 4}; make_map(enc, &P.tmWo, wo, 4, d, s, b); }
  { cuuint64_t d[2] = {KHO, SEQ}, s[1] = {KHO * 2}; cuuint32_t b[2] = {64, 128}; make_map(enc, &P.tmHO, ho_ptr, 2, d, s, b);
    b[1] = 64; make_map(enc, &P.tmHOs, ho_ptr, 2, d, s, b);
    b[0] = 16; make_map(enc, &P.tmOs, ho_ptr, 2, d, s, b, CU_TENSOR_MAP_SWIZZLE_NONE); }
  P.x = x; P.gate_w = gate_w; P.w1 = w1; P.w2 = w2; P.wo = wo; P.out = (__nv_bfloat16*)d_out;
  fused_kernel<<<128, 384, SMEM_BYTES>>>(P);
}
```

```cpp
#include <cuda_runtime.h>
#include <cuda_bf16.h>
#include <cuda.h>
#include <stdint.h>

#define DEVI __device__ __forceinline__

namespace {

constexpr int SEQ = 2048, DM = 512, DFF = 1792, KHO = 2304;
constexpr int NA = 5, NB = 6, SLOT = 16384, KVBUF = 24576;
constexpr int OFF_A = 0, OFF_B = NA * SLOT, OFF_KV = OFF_B + NB * SLOT, OFF_BAR = OFF_KV + 2 * KVBUF;
constexpr int OFF_GST = OFF_BAR + 512;
constexpr int SMEM_BYTES = OFF_BAR + 1024 + 1024;
constexpr uint32_t TIMEOUT = 1u << 28;
#define WAIT_HINT_NS 20000u
#define PFAT 8
constexpr int FS = 8;

constexpr int BAR_FULLA = 0, BAR_EMPTYA = BAR_FULLA + NA, BAR_FULLB = BAR_EMPTYA + NA, BAR_EMPTYB = BAR_FULLB + NB,
              BAR_KVFULL = BAR_EMPTYB + NB, BAR_KVEMPTY = BAR_KVFULL + 2, BAR_STG = BAR_KVEMPTY + 2, BAR_PIN = BAR_STG + 2, BAR_GATE = BAR_PIN + 1, BAR_STE = BAR_GATE + 2;

__device__ __align__(1024) uint8_t g_kv[32 * SEQ * 64];
__device__ __align__(1024) __nv_bfloat16 g_ho[SEQ * KHO];
__device__ __align__(1024) uint8_t g_part[128 * 16384];
__device__ __align__(128) float g_gate[SEQ];
__device__ unsigned g_flag_kv[128 * FS], g_flag_h[128 * FS], g_flag_o[128 * FS], g_flag_g[16 * FS], g_flag_p[128 * FS], g_flag_e[128 * FS];
__device__ unsigned g_epoch, g_done;
#define TR(i) do {} while (0)

struct Params {
  CUtensorMap tmX, tmWqkv, tmW1a, tmW1b, tmW2, tmWo, tmHO, tmHOs, tmOs;
  const __nv_bfloat16* x;
  const __nv_bfloat16* gate_w;
  const __nv_bfloat16* w1;
  const __nv_bfloat16* w2;
  const __nv_bfloat16* wo;
  __nv_bfloat16* out;
};

DEVI uint32_t smem_u32(const void* p) { return (uint32_t)__cvta_generic_to_shared(p); }
DEVI uint32_t clk32() { uint32_t c; asm volatile("mov.u32 %0, %%clock;" : "=r"(c)); return c; }
DEVI void mbar_init(uint32_t bar, uint32_t cnt) { asm volatile("mbarrier.init.shared::cta.b64 [%0], %1;" ::"r"(bar), "r"(cnt)); }
DEVI void mbar_expect_tx(uint32_t bar, uint32_t bytes) { asm volatile("mbarrier.arrive.expect_tx.shared::cta.b64 _, [%0], %1;" ::"r"(bar), "r"(bytes) : "memory"); }
DEVI void mbar_arrive(uint32_t bar) { asm volatile("mbarrier.arrive.shared::cta.b64 _, [%0];" ::"r"(bar) : "memory"); }
DEVI void mbar_arrive_n(uint32_t bar, uint32_t n) { asm volatile("mbarrier.arrive.shared::cta.b64 _, [%0], %1;" ::"r"(bar), "r"(n) : "memory"); }
DEVI void mbar_arrive_cluster(uint32_t bar, uint32_t cta) {
  asm volatile("{ .reg .b32 ra; mapa.shared::cluster.u32 ra, %0, %1; mbarrier.arrive.shared::cluster.b64 _, [ra]; }" ::"r"(bar), "r"(cta) : "memory");
}
DEVI void mbar_wait(uint32_t bar, uint32_t parity, uint32_t t0) {
  asm volatile("{ .reg .pred p; .reg .u32 c;\n"
               "mbarrier.try_wait.parity.shared::cta.b64 p, [%0], %1;\n"
               "@p bra DONE_%=;\n"
               "WAIT_%=:\n"
               "mbarrier.try_wait.parity.shared::cta.b64 p, [%0], %1, %4;\n"
               "@p bra DONE_%=;\n"
               "mov.u32 c, %%clock; sub.u32 c, c, %2; setp.lt.u32 p, c, %3;\n"
               "@p bra WAIT_%=;\n"
               "DONE_%=: }" ::"r"(bar), "r"(parity), "r"(t0), "n"(TIMEOUT), "r"(WAIT_HINT_NS) : "memory");
}
DEVI unsigned ld_relaxed(const unsigned* p) { unsigned v; asm volatile("ld.relaxed.gpu.global.u32 %0, [%1];" : "=r"(v) : "l"(p) : "memory"); return v; }
DEVI float ld_relaxed_f(const float* p) { float v; asm volatile("ld.relaxed.gpu.global.f32 %0, [%1];" : "=f"(v) : "l"(p) : "memory"); return v; }
DEVI void flag_wait(const unsigned* p, unsigned target, uint32_t t0) {
  while ((int)(ld_relaxed(p) - target) < 0) { if (clk32() - t0 > TIMEOUT) break; }
}
DEVI void flag_add(unsigned* p) { asm volatile("red.relaxed.gpu.global.add.u32 [%0], 1;" ::"l"(p) : "memory"); }
DEVI void fence_async_smem() { asm volatile("fence.proxy.async.shared::cta;" ::: "memory"); }
DEVI void fence_async_global() { asm volatile("fence.proxy.async.global;" ::: "memory"); }
DEVI void tma_load_2d(uint32_t dst, const CUtensorMap* m, int c0, int c1, uint32_t bar) {
  asm volatile("cp.async.bulk.tensor.2d.shared::cluster.global.mbarrier::complete_tx::bytes [%0], [%1, {%3, %4}], [%2];" ::"r"(dst), "l"(m), "r"(bar), "r"(c0), "r"(c1) : "memory");
}
DEVI void tma_load_3d(uint32_t dst, const CUtensorMap* m, int c0, int c1, int c2, uint32_t bar) {
  asm volatile("cp.async.bulk.tensor.3d.shared::cluster.global.mbarrier::complete_tx::bytes [%0], [%1, {%3, %4, %5}], [%2];"
               ::"r"(dst), "l"(m), "r"(bar), "r"(c0), "r"(c1), "r"(c2) : "memory");
}
DEVI void tma_load_3d_mc(uint32_t dst, const CUtensorMap* m, int c0, int c1, int c2, uint32_t bar) {
  asm volatile("cp.async.bulk.tensor.3d.shared::cluster.global.mbarrier::complete_tx::bytes.multicast::cluster [%0], [%1, {%3, %4, %5}], [%2], %6;"
               ::"r"(dst), "l"(m), "r"(bar), "r"(c0), "r"(c1), "r"(c2), "h"((uint16_t)3) : "memory");
}
DEVI void tma_load_4d_mc(uint32_t dst, const CUtensorMap* m, int c0, int c1, int c2, int c3, uint32_t bar) {
  asm volatile("cp.async.bulk.tensor.4d.shared::cluster.global.mbarrier::complete_tx::bytes.multicast::cluster [%0], [%1, {%3, %4, %5, %6}], [%2], %7;"
               ::"r"(dst), "l"(m), "r"(bar), "r"(c0), "r"(c1), "r"(c2), "r"(c3), "h"((uint16_t)3) : "memory");
}
DEVI void tma_store_2d(const CUtensorMap* m, int c0, int c1, uint32_t src) {
  asm volatile("cp.async.bulk.tensor.2d.global.shared::cta.bulk_group [%0, {%1, %2}], [%3];" ::"l"(m), "r"(c0), "r"(c1), "r"(src) : "memory");
}
DEVI void bulk_store(void* dst, uint32_t src, uint32_t bytes) {
  asm volatile("cp.async.bulk.global.shared::cta.bulk_group [%0], [%1], %2;" ::"l"(dst), "r"(src), "r"(bytes) : "memory");
}
DEVI void bulk_load(uint32_t dst, const void* src, uint32_t bytes, uint32_t bar) {
  asm volatile("cp.async.bulk.shared::cluster.global.mbarrier::complete_tx::bytes [%0], [%1], %2, [%3];" ::"r"(dst), "l"(src), "r"(bytes), "r"(bar) : "memory");
}
DEVI void bulk_commit() { asm volatile("cp.async.bulk.commit_group;" ::: "memory"); }
DEVI void bulk_wait_all() { asm volatile("cp.async.bulk.wait_group 0;" ::: "memory"); }
DEVI void l2_prefetch(const void* p, uint32_t bytes) { asm volatile("cp.async.bulk.prefetch.L2.global [%0], %1;" ::"l"(p), "r"(bytes) : "memory"); }
DEVI void cluster_arrive() { asm volatile("barrier.cluster.arrive.relaxed.aligned;" ::: "memory"); }
DEVI void cluster_wait() { asm volatile("barrier.cluster.wait.aligned;" ::: "memory"); }
template <int ID> DEVI void named_bar(int n) { asm volatile("bar.sync %0, %1;" ::"n"(ID), "r"(n) : "memory"); }
DEVI void wg_bar(int wg) { if (wg == 0) named_bar<1>(128); else named_bar<2>(128); }
DEVI void wgmma_fence() { asm volatile("wgmma.fence.sync.aligned;" ::: "memory"); }
DEVI void wgmma_commit() { asm volatile("wgmma.commit_group.sync.aligned;" ::: "memory"); }
template <int N> DEVI void wgmma_wait() { asm volatile("wgmma.wait_group.sync.aligned %0;" ::"n"(N) : "memory"); }
template <uint32_t LBO> DEVI uint64_t desc_sw128(uint32_t a16) {
  return ((uint64_t)(0x40000000u | (1024 >> 4)) << 32) | (a16 + ((LBO >> 4) << 16));
}
DEVI uint64_t desc_sw64(uint32_t a16) {
  return ((uint64_t)(0x80000000u | (512 >> 4)) << 32) | (a16 + ((512 >> 4) << 16));
}
DEVI uint32_t pack_bf16(float lo, float hi) { uint32_t r; asm("cvt.rn.bf16x2.f32 %0, %1, %2;" : "=r"(r) : "f"(hi), "f"(lo)); return r; }
DEVI void stsm_x4(uint32_t addr, uint32_t r0, uint32_t r1, uint32_t r2, uint32_t r3) {
  asm volatile("stmatrix.sync.aligned.m8n8.x4.shared.b16 [%0], {%1, %2, %3, %4};" ::"r"(addr), "r"(r0), "r"(r1), "r"(r2), "r"(r3) : "memory");
}
DEVI void sts128(uint32_t addr, uint32_t r0, uint32_t r1, uint32_t r2, uint32_t r3) {
  asm volatile("st.shared.v4.b32 [%0], {%1, %2, %3, %4};" ::"r"(addr), "r"(r0), "r"(r1), "r"(r2), "r"(r3) : "memory");
}
DEVI uint4 lds128(uint32_t addr) {
  uint4 v; asm volatile("ld.shared.v4.b32 {%0, %1, %2, %3}, [%4];" : "=r"(v.x), "=r"(v.y), "=r"(v.z), "=r"(v.w) : "r"(addr) : "memory"); return v;
}
DEVI float ex2(float x) { float y; asm("ex2.approx.ftz.f32 %0, %1;" : "=f"(y) : "f"(x)); return y; }

DEVI void wgmma_ss_n64(float (&d)[32], uint64_t da, uint64_t db) {
  asm volatile("wgmma.mma_async.sync.aligned.m64n64k16.f32.bf16.bf16 {%0, %1, %2, %3, %4, %5, %6, %7, %8, %9, %10, %11, %12, %13, %14, %15, %16, %17, %18, %19, %20, %21, %22, %23, %24, %25, %26, %27, %28, %29, %30, %31}, %32, %33, 1, 1, 1, 0, 1;"
    : "+f"(d[0]), "+f"(d[1]), "+f"(d[2]), "+f"(d[3]), "+f"(d[4]), "+f"(d[5]), "+f"(d[6]), "+f"(d[7]), "+f"(d[8]), "+f"(d[9]), "+f"(d[10]), "+f"(d[11]), "+f"(d[12]), "+f"(d[13]), "+f"(d[14]), "+f"(d[15]), "+f"(d[16]), "+f"(d[17]), "+f"(d[18]), "+f"(d[19]), "+f"(d[20]), "+f"(d[21]), "+f"(d[22]), "+f"(d[23]), "+f"(d[24]), "+f"(d[25]), "+f"(d[26]), "+f"(d[27]), "+f"(d[28]), "+f"(d[29]), "+f"(d[30]), "+f"(d[31])
    : "l"(da), "l"(db));
}
DEVI void wgmma_ss_n128(float (&d)[64], uint64_t da, uint64_t db) {
  asm volatile("wgmma.mma_async.sync.aligned.m64n128k16.f32.bf16.bf16 {%0, %1, %2, %3, %4, %5, %6, %7, %8, %9, %10, %11, %12, %13, %14, %15, %16, %17, %18, %19, %20, %21, %22, %23, %24, %25, %26, %27, %28, %29, %30, %31, %32, %33, %34, %35, %36, %37, %38, %39, %40, %41, %42, %43, %44, %45, %46, %47, %48, %49, %50, %51, %52, %53, %54, %55, %56, %57, %58, %59, %60, %61, %62, %63}, %64, %65, 1, 1, 1, 0, 1;"
    : "+f"(d[0]), "+f"(d[1]), "+f"(d[2]), "+f"(d[3]), "+f"(d[4]), "+f"(d[5]), "+f"(d[6]), "+f"(d[7]), "+f"(d[8]), "+f"(d[9]), "+f"(d[10]), "+f"(d[11]), "+f"(d[12]), "+f"(d[13]), "+f"(d[14]), "+f"(d[15]), "+f"(d[16]), "+f"(d[17]), "+f"(d[18]), "+f"(d[19]), "+f"(d[20]), "+f"(d[21]), "+f"(d[22]), "+f"(d[23]), "+f"(d[24]), "+f"(d[25]), "+f"(d[26]), "+f"(d[27]), "+f"(d[28]), "+f"(d[29]), "+f"(d[30]), "+f"(d[31]), "+f"(d[32]), "+f"(d[33]), "+f"(d[34]), "+f"(d[35]), "+f"(d[36]), "+f"(d[37]), "+f"(d[38]), "+f"(d[39]), "+f"(d[40]), "+f"(d[41]), "+f"(d[42]), "+f"(d[43]), "+f"(d[44]), "+f"(d[45]), "+f"(d[46]), "+f"(d[47]), "+f"(d[48]), "+f"(d[49]), "+f"(d[50]), "+f"(d[51]), "+f"(d[52]), "+f"(d[53]), "+f"(d[54]), "+f"(d[55]), "+f"(d[56]), "+f"(d[57]), "+f"(d[58]), "+f"(d[59]), "+f"(d[60]), "+f"(d[61]), "+f"(d[62]), "+f"(d[63])
    : "l"(da), "l"(db));
}
DEVI void wgmma_ss_n192(float (&d)[96], uint64_t da, uint64_t db) {
  asm volatile("wgmma.mma_async.sync.aligned.m64n192k16.f32.bf16.bf16 {%0, %1, %2, %3, %4, %5, %6, %7, %8, %9, %10, %11, %12, %13, %14, %15, %16, %17, %18, %19, %20, %21, %22, %23, %24, %25, %26, %27, %28, %29, %30, %31, %32, %33, %34, %35, %36, %37, %38, %39, %40, %41, %42, %43, %44, %45, %46, %47, %48, %49, %50, %51, %52, %53, %54, %55, %56, %57, %58, %59, %60, %61, %62, %63, %64, %65, %66, %67, %68, %69, %70, %71, %72, %73, %74, %75, %76, %77, %78, %79, %80, %81, %82, %83, %84, %85, %86, %87, %88, %89, %90, %91, %92, %93, %94, %95}, %96, %97, 1, 1, 1, 0, 1;"
    : "+f"(d[0]), "+f"(d[1]), "+f"(d[2]), "+f"(d[3]), "+f"(d[4]), "+f"(d[5]), "+f"(d[6]), "+f"(d[7]), "+f"(d[8]), "+f"(d[9]), "+f"(d[10]), "+f"(d[11]), "+f"(d[12]), "+f"(d[13]), "+f"(d[14]), "+f"(d[15]), "+f"(d[16]), "+f"(d[17]), "+f"(d[18]), "+f"(d[19]), "+f"(d[20]), "+f"(d[21]), "+f"(d[22]), "+f"(d[23]), "+f"(d[24]), "+f"(d[25]), "+f"(d[26]), "+f"(d[27]), "+f"(d[28]), "+f"(d[29]), "+f"(d[30]), "+f"(d[31]), "+f"(d[32]), "+f"(d[33]), "+f"(d[34]), "+f"(d[35]), "+f"(d[36]), "+f"(d[37]), "+f"(d[38]), "+f"(d[39]), "+f"(d[40]), "+f"(d[41]), "+f"(d[42]), "+f"(d[43]), "+f"(d[44]), "+f"(d[45]), "+f"(d[46]), "+f"(d[47]), "+f"(d[48]), "+f"(d[49]), "+f"(d[50]), "+f"(d[51]), "+f"(d[52]), "+f"(d[53]), "+f"(d[54]), "+f"(d[55]), "+f"(d[56]), "+f"(d[57]), "+f"(d[58]), "+f"(d[59]), "+f"(d[60]), "+f"(d[61]), "+f"(d[62]), "+f"(d[63]), "+f"(d[64]), "+f"(d[65]), "+f"(d[66]), "+f"(d[67]), "+f"(d[68]), "+f"(d[69]), "+f"(d[70]), "+f"(d[71]), "+f"(d[72]), "+f"(d[73]), "+f"(d[74]), "+f"(d[75]), "+f"(d[76]), "+f"(d[77]), "+f"(d[78]), "+f"(d[79]), "+f"(d[80]), "+f"(d[81]), "+f"(d[82]), "+f"(d[83]), "+f"(d[84]), "+f"(d[85]), "+f"(d[86]), "+f"(d[87]), "+f"(d[88]), "+f"(d[89]), "+f"(d[90]), "+f"(d[91]), "+f"(d[92]), "+f"(d[93]), "+f"(d[94]), "+f"(d[95])
    : "l"(da), "l"(db));
}
DEVI void wgmma_ss_n256(float (&d)[128], uint64_t da, uint64_t db) {
  asm volatile("wgmma.mma_async.sync.aligned.m64n256k16.f32.bf16.bf16 {%0, %1, %2, %3, %4, %5, %6, %7, %8, %9, %10, %11, %12, %13, %14, %15, %16, %17, %18, %19, %20, %21, %22, %23, %24, %25, %26, %27, %28, %29, %30, %31, %32, %33, %34, %35, %36, %37, %38, %39, %40, %41, %42, %43, %44, %45, %46, %47, %48, %49, %50, %51, %52, %53, %54, %55, %56, %57, %58, %59, %60, %61, %62, %63, %64, %65, %66, %67, %68, %69, %70, %71, %72, %73, %74, %75, %76, %77, %78, %79, %80, %81, %82, %83, %84, %85, %86, %87, %88, %89, %90, %91, %92, %93, %94, %95, %96, %97, %98, %99, %100, %101, %102, %103, %104, %105, %106, %107, %108, %109, %110, %111, %112, %113, %114, %115, %116, %117, %118, %119, %120, %121, %122, %123, %124, %125, %126, %127}, %128, %129, 1, 1, 1, 0, 1;"
    : "+f"(d[0]), "+f"(d[1]), "+f"(d[2]), "+f"(d[3]), "+f"(d[4]), "+f"(d[5]), "+f"(d[6]), "+f"(d[7]), "+f"(d[8]), "+f"(d[9]), "+f"(d[10]), "+f"(d[11]), "+f"(d[12]), "+f"(d[13]), "+f"(d[14]), "+f"(d[15]), "+f"(d[16]), "+f"(d[17]), "+f"(d[18]), "+f"(d[19]), "+f"(d[20]), "+f"(d[21]), "+f"(d[22]), "+f"(d[23]), "+f"(d[24]), "+f"(d[25]), "+f"(d[26]), "+f"(d[27]), "+f"(d[28]), "+f"(d[29]), "+f"(d[30]), "+f"(d[31]), "+f"(d[32]), "+f"(d[33]), "+f"(d[34]), "+f"(d[35]), "+f"(d[36]), "+f"(d[37]), "+f"(d[38]), "+f"(d[39]), "+f"(d[40]), "+f"(d[41]), "+f"(d[42]), "+f"(d[43]), "+f"(d[44]), "+f"(d[45]), "+f"(d[46]), "+f"(d[47]), "+f"(d[48]), "+f"(d[49]), "+f"(d[50]), "+f"(d[51]), "+f"(d[52]), "+f"(d[53]), "+f"(d[54]), "+f"(d[55]), "+f"(d[56]), "+f"(d[57]), "+f"(d[58]), "+f"(d[59]), "+f"(d[60]), "+f"(d[61]), "+f"(d[62]), "+f"(d[63]), "+f"(d[64]), "+f"(d[65]), "+f"(d[66]), "+f"(d[67]), "+f"(d[68]), "+f"(d[69]), "+f"(d[70]), "+f"(d[71]), "+f"(d[72]), "+f"(d[73]), "+f"(d[74]), "+f"(d[75]), "+f"(d[76]), "+f"(d[77]), "+f"(d[78]), "+f"(d[79]), "+f"(d[80]), "+f"(d[81]), "+f"(d[82]), "+f"(d[83]), "+f"(d[84]), "+f"(d[85]), "+f"(d[86]), "+f"(d[87]), "+f"(d[88]), "+f"(d[89]), "+f"(d[90]), "+f"(d[91]), "+f"(d[92]), "+f"(d[93]), "+f"(d[94]), "+f"(d[95]), "+f"(d[96]), "+f"(d[97]), "+f"(d[98]), "+f"(d[99]), "+f"(d[100]), "+f"(d[101]), "+f"(d[102]), "+f"(d[103]), "+f"(d[104]), "+f"(d[105]), "+f"(d[106]), "+f"(d[107]), "+f"(d[108]), "+f"(d[109]), "+f"(d[110]), "+f"(d[111]), "+f"(d[112]), "+f"(d[113]), "+f"(d[114]), "+f"(d[115]), "+f"(d[116]), "+f"(d[117]), "+f"(d[118]), "+f"(d[119]), "+f"(d[120]), "+f"(d[121]), "+f"(d[122]), "+f"(d[123]), "+f"(d[124]), "+f"(d[125]), "+f"(d[126]), "+f"(d[127])
    : "l"(da), "l"(db));
}
DEVI void wgmma_qk64(float (&d)[32], uint32_t a0, uint32_t a1, uint32_t a2, uint32_t a3, uint64_t db) {
  asm volatile("wgmma.mma_async.sync.aligned.m64n64k16.f32.bf16.bf16 {%0, %1, %2, %3, %4, %5, %6, %7, %8, %9, %10, %11, %12, %13, %14, %15, %16, %17, %18, %19, %20, %21, %22, %23, %24, %25, %26, %27, %28, %29, %30, %31}, {%32, %33, %34, %35}, %36, 0, 1, 1, 0;"
    : "=f"(d[0]), "=f"(d[1]), "=f"(d[2]), "=f"(d[3]), "=f"(d[4]), "=f"(d[5]), "=f"(d[6]), "=f"(d[7]), "=f"(d[8]), "=f"(d[9]), "=f"(d[10]), "=f"(d[11]), "=f"(d[12]), "=f"(d[13]), "=f"(d[14]), "=f"(d[15]), "=f"(d[16]), "=f"(d[17]), "=f"(d[18]), "=f"(d[19]), "=f"(d[20]), "=f"(d[21]), "=f"(d[22]), "=f"(d[23]), "=f"(d[24]), "=f"(d[25]), "=f"(d[26]), "=f"(d[27]), "=f"(d[28]), "=f"(d[29]), "=f"(d[30]), "=f"(d[31])
    : "r"(a0), "r"(a1), "r"(a2), "r"(a3), "l"(db));
}
DEVI void wgmma_qk128(float (&d)[64], uint32_t a0, uint32_t a1, uint32_t a2, uint32_t a3, uint64_t db) {
  asm volatile("wgmma.mma_async.sync.aligned.m64n128k16.f32.bf16.bf16 {%0, %1, %2, %3, %4, %5, %6, %7, %8, %9, %10, %11, %12, %13, %14, %15, %16, %17, %18, %19, %20, %21, %22, %23, %24, %25, %26, %27, %28, %29, %30, %31, %32, %33, %34, %35, %36, %37, %38, %39, %40, %41, %42, %43, %44, %45, %46, %47, %48, %49, %50, %51, %52, %53, %54, %55, %56, %57, %58, %59, %60, %61, %62, %63}, {%64, %65, %66, %67}, %68, 0, 1, 1, 0;"
    : "=f"(d[0]), "=f"(d[1]), "=f"(d[2]), "=f"(d[3]), "=f"(d[4]), "=f"(d[5]), "=f"(d[6]), "=f"(d[7]), "=f"(d[8]), "=f"(d[9]), "=f"(d[10]), "=f"(d[11]), "=f"(d[12]), "=f"(d[13]), "=f"(d[14]), "=f"(d[15]), "=f"(d[16]), "=f"(d[17]), "=f"(d[18]), "=f"(d[19]), "=f"(d[20]), "=f"(d[21]), "=f"(d[22]), "=f"(d[23]), "=f"(d[24]), "=f"(d[25]), "=f"(d[26]), "=f"(d[27]), "=f"(d[28]), "=f"(d[29]), "=f"(d[30]), "=f"(d[31]), "=f"(d[32]), "=f"(d[33]), "=f"(d[34]), "=f"(d[35]), "=f"(d[36]), "=f"(d[37]), "=f"(d[38]), "=f"(d[39]), "=f"(d[40]), "=f"(d[41]), "=f"(d[42]), "=f"(d[43]), "=f"(d[44]), "=f"(d[45]), "=f"(d[46]), "=f"(d[47]), "=f"(d[48]), "=f"(d[49]), "=f"(d[50]), "=f"(d[51]), "=f"(d[52]), "=f"(d[53]), "=f"(d[54]), "=f"(d[55]), "=f"(d[56]), "=f"(d[57]), "=f"(d[58]), "=f"(d[59]), "=f"(d[60]), "=f"(d[61]), "=f"(d[62]), "=f"(d[63])
    : "r"(a0), "r"(a1), "r"(a2), "r"(a3), "l"(db));
}
DEVI void wgmma_pv(float (&d)[8], uint32_t a0, uint32_t a1, uint32_t a2, uint32_t a3, uint64_t db) {
  asm volatile("wgmma.mma_async.sync.aligned.m64n16k16.f32.bf16.bf16 {%0, %1, %2, %3, %4, %5, %6, %7}, {%8, %9, %10, %11}, %12, 1, 1, 1, 1;"
    : "+f"(d[0]), "+f"(d[1]), "+f"(d[2]), "+f"(d[3]), "+f"(d[4]), "+f"(d[5]), "+f"(d[6]), "+f"(d[7])
    : "r"(a0), "r"(a1), "r"(a2), "r"(a3), "l"(db));
}
DEVI void wgmma_pv0(float (&d)[8], uint32_t a0, uint32_t a1, uint32_t a2, uint32_t a3, uint64_t db) {
  asm volatile("wgmma.mma_async.sync.aligned.m64n16k16.f32.bf16.bf16 {%0, %1, %2, %3, %4, %5, %6, %7}, {%8, %9, %10, %11}, %12, 0, 1, 1, 1;"
    : "=f"(d[0]), "=f"(d[1]), "=f"(d[2]), "=f"(d[3]), "=f"(d[4]), "=f"(d[5]), "=f"(d[6]), "=f"(d[7])
    : "r"(a0), "r"(a1), "r"(a2), "r"(a3), "l"(db));
}

template <int N> DEVI void wgmma_ss(float (&d)[N / 2], uint64_t da, uint64_t db) {
  if constexpr (N == 64) wgmma_ss_n64(d, da, db);
  else if constexpr (N == 128) wgmma_ss_n128(d, da, db);
  else if constexpr (N == 192) wgmma_ss_n192(d, da, db);
  else wgmma_ss_n256(d, da, db);
}

DEVI int oh_chunk(int j, int i, int& need) {
  if (j & 1) {
    if (i >= 3 && i < 7) { need = 16 + 2 * (i - 3); return 24 + (i - 3); }
    if (i >= 7) i -= 4;
  }
  const int g = i / 3, o = (j + 2 * g) & 7;
  need = o;
  return 3 * o + (i - 3 * g);
}

struct Ctx {
  uint32_t sbase, bars, peer, t0, a16, b16;
  int wg, lane;
  int ai, bi; uint32_t aph, bph;
  int brem;
  int pa, pb;
};

DEVI void release_prev(Ctx& c) {
  if (c.pb >= 0) {
    if (c.lane == 0) mbar_arrive(c.bars + 8 * (BAR_EMPTYB + c.pb));
    if (c.lane == 1) mbar_arrive_cluster(c.bars + 8 * (BAR_EMPTYB + c.pb), c.peer);
  }
  if (c.pa >= 0 && c.lane == 2) mbar_arrive(c.bars + 8 * (BAR_EMPTYA + c.pa));
}

DEVI void gemm_wait(Ctx& c) {
  asm volatile("{ .reg .pred p, q; .reg .u32 c;\n"
               "WAIT_%=:\n"
               "mbarrier.try_wait.parity.shared::cta.b64 p, [%0], %1;\n"
               "mbarrier.try_wait.parity.shared::cta.b64 q, [%2], %3;\n"
               "and.pred p, p, q;\n"
               "@p bra DONE_%=;\n"
               "mov.u32 c, %%clock; sub.u32 c, c, %4; setp.lt.u32 p, c, %5;\n"
               "@p bra WAIT_%=;\n"
               "DONE_%=: }" ::"r"(c.bars + 8 * (BAR_FULLA + c.ai)), "r"(c.aph), "r"(c.bars + 8 * (BAR_FULLB + c.bi)), "r"(c.bph), "r"(c.t0), "n"(TIMEOUT) : "memory");
}
template <int N>
DEVI void gemm_group(float (&acc)[N / 2], Ctx& c, int g, int& npa, int& npb) {
  const uint32_t a16 = c.a16 + c.ai * (SLOT >> 4);
  const uint32_t b16 = c.b16 + c.bi * (SLOT >> 4);
  bool adv;
  if constexpr (N >= 192) {
    const uint32_t a2 = a16 + (g & 1) * 4;
    wgmma_ss<N>(acc, desc_sw128<16>(a2), desc_sw128<2048>(b16));
    wgmma_ss<N>(acc, desc_sw128<16>(a2 + 2), desc_sw128<2048>(b16 + 512));
    adv = g & 1;
  } else {
#pragma unroll
    for (int s = 0; s < 4; s++) wgmma_ss<N>(acc, desc_sw128<16>(a16 + s * 2), desc_sw128<4096>(b16 + (s >> 1) * 512 + (s & 1) * 128));
    adv = true;
  }
  wgmma_commit();
  npb = c.brem > 0 ? c.bi : -1;
  c.brem--;
  if (++c.bi == NB) { c.bi = 0; c.bph ^= 1; }
  npa = -1;
  if (adv) { npa = c.ai; if (++c.ai == NA) { c.ai = 0; c.aph ^= 1; } }
}

template <int N>
DEVI void bare_groups(float (&acc)[N / 2], Ctx& c, int g0, int g1) {
  for (int g = g0; g < g1; g++) {
    int npa, npb;
    gemm_wait(c);
    wgmma_fence();
    gemm_group<N>(acc, c, g, npa, npb);
    wgmma_wait<1>();
    release_prev(c);
    c.pa = npa; c.pb = npb;
  }
}
DEVI void drain(Ctx& c) {
  wgmma_wait<0>();
  release_prev(c);
  c.pa = c.pb = -1;
}

constexpr float SC = 0.25f * 1.4426950408889634f;

#define ONCE _Pragma("unroll 1") for (unsigned once_ = 0; once_ < gridDim.y; once_++)

struct Attn {
  uint32_t q[4][4];
  uint32_t nm[4];
  float g0, g1;
  int cmin;
  int rowc;
};

template <int O0, int NS>
DEVI void kill32(float (&S)[NS]) {
#pragma unroll
  for (int i = 0; i < 32; i++) S[O0 + i] = __int_as_float(0xff800000);
}
DEVI void row_max(const float (&S)[64], float& x0, float& x1) {
#pragma unroll
  for (int n = 0; n < 16; n++) {
    x0 = fmaxf(x0, fmaxf(S[4 * n], S[4 * n + 1])); x1 = fmaxf(x1, fmaxf(S[4 * n + 2], S[4 * n + 3]));
  }
}
template <int K, bool PRE = false>
DEVI void exp8(const float (&S)[64], uint32_t (&P)[4], float n0, float n1, float (&l)[4]) {
  float e[8];
#pragma unroll
  for (int i = 0; i < 8; i++) e[i] = ex2(PRE ? S[8 * K + i] : fmaf(S[8 * K + i], SC, (i & 2) ? n1 : n0));
  l[0] += e[0]; l[1] += e[1]; l[2] += e[2]; l[3] += e[3];
  l[0] += e[4]; l[1] += e[5]; l[2] += e[6]; l[3] += e[7];
#pragma unroll
  for (int i = 0; i < 4; i++) P[i] = pack_bf16(e[2 * i], e[2 * i + 1]) | (__float_as_uint(l[i]) & blockIdx.y);
}
DEVI void merge_fl(float (&S)[64], const float (&F)[32], int rowc) {
#pragma unroll
  for (int n = 0; n < 8; n++) {
    if (n * 8 > rowc) S[32 + 4 * n] = F[4 * n];
    if (n * 8 + 1 > rowc) S[32 + 4 * n + 1] = F[4 * n + 1];
    if (n * 8 > rowc + 8) S[32 + 4 * n + 2] = F[4 * n + 2];
    if (n * 8 + 1 > rowc + 8) S[32 + 4 * n + 3] = F[4 * n + 3];
  }
}
DEVI bool wg_any(int wg, bool v) {
  uint32_t r;
  if (wg == 0) asm volatile("{ .reg .pred p, q; setp.ne.u32 p, %1, 0; bar.red.or.pred q, 1, 128, p; selp.u32 %0, 1, 0, q; }" : "=r"(r) : "r"((uint32_t)v) : "memory");
  else asm volatile("{ .reg .pred p, q; setp.ne.u32 p, %1, 0; bar.red.or.pred q, 2, 128, p; selp.u32 %0, 1, 0, q; }" : "=r"(r) : "r"((uint32_t)v) : "memory");
  return r != 0;
}

template <bool FIRST> DEVI void pv_step(float (&O)[8], const uint32_t (&P)[4], uint32_t v16) {
  wgmma_wait<0>();
  wgmma_fence();
  if (FIRST) wgmma_pv0(O, P[0], P[1], P[2], P[3], desc_sw64(v16)); else wgmma_pv(O, P[0], P[1], P[2], P[3], desc_sw64(v16));
  wgmma_commit();
}
template <int K> DEVI void pv_merged(float (&O)[8], const uint32_t (&P)[4], uint32_t (&PL)[4], uint32_t (&PF)[4], int rowc, uint32_t kb) {
#pragma unroll
  for (int i = 0; i < 4; i++) {
    const int col = (K - 4) * 16 + (i >> 1) * 8, r = rowc + (i & 1) * 8;
    const uint32_t m = (col > r ? 0xFFFFu : 0u) | (col + 1 > r ? 0xFFFF0000u : 0u);
    PF[i] = P[i] & m; PL[i] = P[i] & ~m;
  }
  wgmma_wait<0>();
  wgmma_fence();
  wgmma_pv(O, PL[0], PL[1], PL[2], PL[3], desc_sw64(kb + 3 * 256 + 2 + K * 64));
  wgmma_pv(O, PF[0], PF[1], PF[2], PF[3], desc_sw64(kb + 2 + (K - 4) * 64));
  wgmma_commit();
}
DEVI void qk_a(float (&S)[64], float (&F)[32], const uint32_t (&q)[4], uint32_t kb) {
  wgmma_fence();
  wgmma_qk128(S, q[0], q[1], q[2], q[3], desc_sw64(kb + 3 * 256));
  wgmma_qk64(F, q[0], q[1], q[2], q[3], desc_sw64(kb));
}
DEVI void fix_a(float (&S)[64], float (&F)[32], const Attn& at) {
  if (at.cmin > 0) { kill32<0>(F); if (at.cmin > 3) kill32<0>(S); }
  merge_fl(S, F, at.rowc);
}
DEVI void scale64(float (&S)[64], float n0, float n1) {
#pragma unroll
  for (int i = 0; i < 64; i++) S[i] = fmaf(S[i], SC, (i & 2) ? n1 : n0);
}
DEVI void fix_b(float (&S)[64], const Attn& at) {
  if (at.cmin > 1) { kill32<0>(S); if (at.cmin > 2) kill32<32>(S); }
}
DEVI void half_a(const float (&SA)[64], float (&SB)[64], float (&O)[8], float (&l)[4], const Attn& at, uint32_t kb, float n0, float n1) {
  uint32_t P[8][4], PL[4][4], PF[4][4];
  wgmma_fence();
  wgmma_qk128(SB, at.q[0][0], at.q[0][1], at.q[0][2], at.q[0][3], desc_sw64(kb + 256));
  wgmma_commit();
  const uint32_t v = kb + 3 * 256 + 2;
  exp8<0, true>(SA, P[0], n0, n1, l); exp8<1, true>(SA, P[1], n0, n1, l);
  pv_step<true>(O, P[0], v);         exp8<2, true>(SA, P[2], n0, n1, l);
  pv_step<false>(O, P[1], v + 64);   exp8<3, true>(SA, P[3], n0, n1, l);
  pv_step<false>(O, P[2], v + 128);  exp8<4, true>(SA, P[4], n0, n1, l);
  pv_step<false>(O, P[3], v + 192);  exp8<5, true>(SA, P[5], n0, n1, l);
  pv_merged<4>(O, P[4], PL[0], PF[0], at.rowc, kb); exp8<6, true>(SA, P[6], n0, n1, l);
  pv_merged<5>(O, P[5], PL[1], PF[1], at.rowc, kb); exp8<7, true>(SA, P[7], n0, n1, l);
  pv_merged<6>(O, P[6], PL[2], PF[2], at.rowc, kb);
  pv_merged<7>(O, P[7], PL[3], PF[3], at.rowc, kb);
  fix_b(SB, at);
}

DEVI void attention(const Ctx& c, Attn& at, int wi) {
  const uint32_t kvb = ((c.sbase & 0x3FFFF) + OFF_KV + c.wg * 4096) >> 4;
  float SA[64];
  float n0 = __uint_as_float(at.nm[0] << 16), n1 = __uint_as_float(at.nm[0] & 0xffff0000u);
  bool exact = false;
  mbar_wait(c.bars + 8 * BAR_KVFULL, 0, c.t0);
  {
    float F[32];
    qk_a(SA, F, at.q[0], kvb);
    wgmma_commit();
    wgmma_wait<0>();
    fix_a(SA, F, at);
    scale64(SA, n0, n1);
  }
  int h = 0;
#pragma unroll 1
  while (h < 4) {
    const uint32_t kb = kvb + (h & 1) * (KVBUF >> 4);
    const uint32_t kn = h == 3 ? kb : kvb + ((h & 1) ^ 1) * (KVBUF >> 4);
    float O[8], l[4] = {0.f, 0.f, 0.f, 0.f};
    float SN[64], F[32];
    {
      float SB[64];
      half_a(SA, SB, O, l, at, kb, n0, n1);
      uint32_t P[8][4];
      const uint32_t v = kb + 256 + 2;
      exp8<0>(SB, P[0], n0, n1, l); exp8<1>(SB, P[1], n0, n1, l);
      pv_step<false>(O, P[0], v);        exp8<2>(SB, P[2], n0, n1, l);
      pv_step<false>(O, P[1], v + 64);   exp8<3>(SB, P[3], n0, n1, l);
      pv_step<false>(O, P[2], v + 128);  exp8<4>(SB, P[4], n0, n1, l);
      if (h < 3) mbar_wait(c.bars + 8 * (BAR_KVFULL + ((h + 1) & 1)), (h + 1) >> 1, c.t0);
      wgmma_wait<0>();
      qk_a(SN, F, at.q[1], kn);
      wgmma_pv(O, P[3][0], P[3][1], P[3][2], P[3][3], desc_sw64(v + 192));
      wgmma_commit();
      ONCE { exp8<5>(SB, P[5], n0, n1, l); }
      pv_step<false>(O, P[4], v + 256);
      fix_a(SN, F, at);
      exp8<6>(SB, P[6], n0, n1, l);
      pv_step<false>(O, P[5], v + 320);
      scale64(SN, __uint_as_float(at.nm[1] << 16), __uint_as_float(at.nm[1] & 0xffff0000u));
      exp8<7>(SB, P[7], n0, n1, l);
      wgmma_wait<0>();
      wgmma_fence();
      wgmma_pv(O, P[6][0], P[6][1], P[6][2], P[6][3], desc_sw64(v + 384));
      wgmma_pv(O, P[7][0], P[7][1], P[7][2], P[7][3], desc_sw64(v + 448));
      wgmma_commit();
    }
    float l0 = l[0] + l[1], l1 = l[2] + l[3];
    l0 += __shfl_xor_sync(0xffffffffu, l0, 1); l1 += __shfl_xor_sync(0xffffffffu, l1, 1);
    l0 += __shfl_xor_sync(0xffffffffu, l0, 2); l1 += __shfl_xor_sync(0xffffffffu, l1, 2);
    const bool bad = !exact && !(l0 > 1e-6f && l0 < 1e18f && l1 > 1e-6f && l1 < 1e18f);
    const bool redo = wg_any(c.wg, bad);
    wgmma_wait<0>();
    if (redo) {
      float x0 = __int_as_float(0xff800000), x1 = x0;
      {
        float T[64];
        wgmma_fence();
        wgmma_qk128(T, at.q[0][0], at.q[0][1], at.q[0][2], at.q[0][3], desc_sw64(kb + 256));
        wgmma_commit();
        wgmma_wait<0>();
        fix_b(T, at);
        row_max(T, x0, x1);
      }
      float T[64], G[32];
      qk_a(T, G, at.q[0], kb);
      wgmma_commit();
      wgmma_wait<0>();
      fix_a(T, G, at);
      row_max(T, x0, x1);
      x0 = fmaxf(x0, __shfl_xor_sync(0xffffffffu, x0, 1)); x1 = fmaxf(x1, __shfl_xor_sync(0xffffffffu, x1, 1));
      x0 = fmaxf(x0, __shfl_xor_sync(0xffffffffu, x0, 2)); x1 = fmaxf(x1, __shfl_xor_sync(0xffffffffu, x1, 2));
      n0 = -x0 * SC; n1 = -x1 * SC;
      scale64(T, n0, n1);
#pragma unroll
      for (int i = 0; i < 64; i++) SA[i] = T[i];
      exact = true;
    } else {
      if (c.lane == 0) mbar_arrive(c.bars + 8 * (BAR_KVEMPTY + (h & 1)));
      const float c0 = __fdividef(at.g0, l0), c1 = __fdividef(at.g1, l1);
      const uint32_t ost = c.sbase + OFF_A + (15 % NA) * SLOT + c.wg * 8192 + h * 2048;
      const int mi = c.lane >> 3;
      const int srow = wi * 16 + (c.lane & 7) + 8 * (mi & 1);
      stsm_x4(ost + srow * 32 + (mi >> 1) * 16, pack_bf16(O[0] * c0, O[1] * c0), pack_bf16(O[2] * c1, O[3] * c1),
              pack_bf16(O[4] * c0, O[5] * c0), pack_bf16(O[6] * c1, O[7] * c1));
      fence_async_smem();
      __syncwarp();
      if (c.lane == 0) mbar_arrive(c.bars + 8 * (BAR_STG + c.wg));
      n0 = __uint_as_float(at.nm[1] << 16); n1 = __uint_as_float(at.nm[1] & 0xffff0000u);
#pragma unroll
      for (int i = 0; i < 64; i++) SA[i] = SN[i];
#pragma unroll
      for (int i = 0; i < 4; i++) { at.q[0][i] = at.q[1][i]; at.q[1][i] = at.q[2][i]; at.q[2][i] = at.q[3][i]; }
      at.nm[1] = at.nm[2]; at.nm[2] = at.nm[3];
      exact = false;
      h++;
    }
  }
}

template <int CH, int NACC>
DEVI void store_h_chunk(const float (&acc)[NACC], uint32_t base  , int lane, float s0, float s1) {
  const int mi = lane >> 3;
#pragma unroll
  for (int tp = 0; tp < 4; tp++) {
    const int t = CH * 8 + tp * 2;
    const uint32_t r0 = pack_bf16(fmaxf(acc[4 * t + 0], 0.f) * s0, fmaxf(acc[4 * t + 1], 0.f) * s0);
    const uint32_t r1 = pack_bf16(fmaxf(acc[4 * t + 2], 0.f) * s1, fmaxf(acc[4 * t + 3], 0.f) * s1);
    const uint32_t r2 = pack_bf16(fmaxf(acc[4 * t + 4], 0.f) * s0, fmaxf(acc[4 * t + 5], 0.f) * s0);
    const uint32_t r3 = pack_bf16(fmaxf(acc[4 * t + 6], 0.f) * s1, fmaxf(acc[4 * t + 7], 0.f) * s1);
    stsm_x4(base + (((tp * 2 + (mi >> 1)) ^ (lane & 7)) << 4), r0, r1, r2, r3);
  }
}

DEVI void get_gate(Attn& at, const Ctx& c, const unsigned* gflag, unsigned gtgt, const float* gp) {
  if (c.lane == 0) flag_wait(gflag, gtgt, c.t0);
  __syncwarp();
  at.g0 = ld_relaxed_f(gp); at.g1 = ld_relaxed_f(gp + 8);
}

template <int N>
DEVI void phase_q(Ctx& c, Attn& at, int warp, const unsigned* gflag, unsigned gtgt, const float* gp) {
  float acc[N / 2];
#pragma unroll
  for (int i = 0; i < N / 2; i++) acc[i] = 0.f;
  bare_groups<N>(acc, c, 0, 16);
  drain(c);
  const int lane = c.lane, mi = lane >> 3;
  const int row = warp * 16 + (lane & 7) + 8 * (mi & 1);
  const int sw = (row >> 1) & 3;
#pragma unroll
  for (int hh = 0; hh < 4; hh++) {
    const uint32_t base = c.sbase + OFF_KV + hh * 8192 + row * 64;
#pragma unroll
    for (int kv = 0; kv < 2; kv++) {
      const int t = 8 + kv * 8 + 2 * hh;
      stsm_x4(base + (((kv * 2 + (mi >> 1)) ^ sw) << 4),
              pack_bf16(acc[4 * t + 0], acc[4 * t + 1]), pack_bf16(acc[4 * t + 2], acc[4 * t + 3]),
              pack_bf16(acc[4 * t + 4], acc[4 * t + 5]), pack_bf16(acc[4 * t + 6], acc[4 * t + 7]));
    }
  }
  fence_async_smem();
  __syncwarp();
  if (lane == 0) mbar_arrive(c.bars + 8 * (BAR_STG + c.wg));
  if constexpr (N == 256) {
    get_gate(at, c, gflag, gtgt, gp);
    store_h_chunk<3>(acc, c.sbase + OFF_KV + 32768 + row * 128, lane, 1.f - at.g0, 1.f - at.g1);
    fence_async_smem();
    __syncwarp();
    if (lane == 0) mbar_arrive(c.bars + 8 * (BAR_STE + c.wg));
  }
#pragma unroll
  for (int hh = 0; hh < 4; hh++) {
#pragma unroll
    for (int i = 0; i < 4; i++) at.q[hh][i] = pack_bf16(acc[8 * hh + 2 * i], acc[8 * hh + 2 * i + 1]);
    const float* q = &acc[8 * hh];
    const float* k = &acc[32 + 8 * hh];
    float d0 = q[0] * k[0] + q[1] * k[1] + q[4] * k[4] + q[5] * k[5], d1 = q[2] * k[2] + q[3] * k[3] + q[6] * k[6] + q[7] * k[7];
    d0 += __shfl_xor_sync(0xffffffffu, d0, 1); d1 += __shfl_xor_sync(0xffffffffu, d1, 1);
    d0 += __shfl_xor_sync(0xffffffffu, d0, 2); d1 += __shfl_xor_sync(0xffffffffu, d1, 2);
    at.nm[hh] = pack_bf16(-d0 * SC, -d1 * SC);
  }
}

__global__ void __cluster_dims__(2, 1, 1) __launch_bounds__(384, 1) fused_kernel(const __grid_constant__ Params P) {
  extern __shared__ uint8_t smem_raw[];
  const uint32_t sbase = (smem_u32(smem_raw) + 1023u) & ~1023u;
  const uint32_t bars = sbase + OFF_BAR;
  const int tid = threadIdx.x, warp = tid >> 5, lane = tid & 31;
  const uint32_t rank = blockIdx.x & 1, peer = rank ^ 1;
  const int j = (blockIdx.x >> 1) & 7, rb = ((blockIdx.x >> 4) << 1) | rank;
  const uint32_t t0 = clk32();

  const int typeB = j & 1;
  if (tid < 9) asm volatile("prefetch.tensormap [%0];" ::"l"(&P.tmX + tid) : "memory");
  if (tid == 256) {
    for (int s = 0; s < NA; s++) mbar_init(bars + 8 * (BAR_FULLA + s), 1);
    for (int s = 0; s < NB; s++) mbar_init(bars + 8 * (BAR_FULLB + s), 1);
    fence_async_smem();
  } else if (tid == 288) {
    for (int s = 0; s < NA; s++) mbar_init(bars + 8 * (BAR_EMPTYA + s), 10);
    for (int s = 0; s < NB; s++) mbar_init(bars + 8 * (BAR_EMPTYB + s), 16);
  } else if (tid == 320) {
    for (int s = 0; s < 2; s++) { mbar_init(bars + 8 * (BAR_KVFULL + s), 1); mbar_init(bars + 8 * (BAR_KVEMPTY + s), 8); mbar_init(bars + 8 * (BAR_STG + s), 4); mbar_init(bars + 8 * (BAR_STE + s), 4); }
    mbar_init(bars + 8 * BAR_PIN, 1); mbar_init(bars + 8 * BAR_GATE, 1); mbar_init(bars + 8 * (BAR_GATE + 1), 1);
  }
  if (tid >= 256 && lane == 0) asm volatile("fence.mbarrier_init.release.cluster;" ::: "memory");
  const unsigned ep1 = ld_relaxed(&g_epoch) + 1;
  __syncwarp();
  cluster_arrive();

  const int on = 12 + 4 * typeB;

  if (warp < 8) {
    asm volatile("setmaxnreg.inc.sync.aligned.u32 232;");
    cluster_wait();
    const int wg = __shfl_sync(0xffffffffu, warp >> 2, 0), wi = warp & 3;
    Ctx c{sbase, bars, peer, t0, ((sbase & 0x3FFFF) + OFF_A + wg * 8192) >> 4, ((sbase & 0x3FFFF) + OFF_B) >> 4, wg, lane, 0, 0, 0u, 0u, 32 + on + 4 - NB, -1, -1};
    Attn at;
    at.cmin = 4 - 2 * rb - wg;
    at.rowc = wi * 16 + (lane >> 2) - (lane & 3) * 2;
    const int row0 = rb * 128 + warp * 16 + (lane >> 2);
    if (tid == 0) TR(0);
    if (typeB) phase_q<192>(c, at, warp, &g_flag_g[rb * FS], ep1 * 16, &g_gate[row0]);
    else phase_q<256>(c, at, warp, &g_flag_g[rb * FS], ep1 * 16, &g_gate[row0]);
    if (tid == 0) TR(2);
    {
      float acc[96];
#pragma unroll
      for (int i = 0; i < 96; i++) acc[i] = 0.f;
      bare_groups<192>(acc, c, 0, 8);
      if (typeB) get_gate(at, c, &g_flag_g[rb * FS], ep1 * 16, &g_gate[row0]);
      bare_groups<192>(acc, c, 8, 16);
      drain(c);
      if (tid == 0) TR(1);
      const uint32_t rowoff = (warp * 16 + (lane & 7) + 8 * ((lane >> 3) & 1)) * 128;
      const float s0 = 1.f - at.g0, s1 = 1.f - at.g1;
      constexpr int e0 = 16 % NA, e1 = 17 % NA, e2 = 18 % NA;
      mbar_wait(bars + 8 * (BAR_FULLA + e0), (16 / NA) & 1, t0);
      store_h_chunk<0>(acc, sbase + OFF_A + e0 * SLOT + rowoff, lane, s0, s1);
      mbar_wait(bars + 8 * (BAR_FULLA + e1), (17 / NA) & 1, t0);
      store_h_chunk<1>(acc, sbase + OFF_A + e1 * SLOT + rowoff, lane, s0, s1);
      mbar_wait(bars + 8 * (BAR_FULLA + e2), (18 / NA) & 1, t0);
      store_h_chunk<2>(acc, sbase + OFF_A + e2 * SLOT + rowoff, lane, s0, s1);
    }
    fence_async_smem();
    wg_bar(wg);
    if (lane == 0) mbar_arrive(bars + 8 * (BAR_STG + wg));
    if (tid == 0) TR(4);
    attention(c, at, wi);
    if (tid == 0) TR(3);
    float own[32];
    {
      float acc[64];
#pragma unroll
      for (int i = 0; i < 64; i++) acc[i] = 0.f;
      bare_groups<128>(acc, c, 0, on);
      drain(c);
      if (tid == 0) TR(5);
      mbar_wait(bars + 8 * (BAR_KVEMPTY + 0), 1, t0);
      const uint32_t pst = sbase + OFF_KV + wg * 8192 + (tid & 127) * 16;
#pragma unroll
      for (int i = 0; i < 4; i++) {
        uint32_t r[4];
#pragma unroll
        for (int k = 0; k < 4; k++) {
          const int idx = 8 * i + 2 * k;
          const float lo = typeB ? acc[idx] : acc[32 + idx], hi = typeB ? acc[idx + 1] : acc[32 + idx + 1];
          r[k] = pack_bf16(lo, hi);
        }
        sts128(pst + i * 2048, r[0], r[1], r[2], r[3]);
      }
#pragma unroll
      for (int i = 0; i < 32; i++) own[i] = typeB ? acc[32 + i] : acc[i];
      fence_async_smem();
      __syncwarp();
      if (lane == 0) mbar_arrive(bars + 8 * (BAR_STG + wg));
    }
    for (int g = 0; g < 8; g++) {
      const uint32_t a16 = c.a16 + c.ai * (SLOT >> 4);
      const uint32_t b16 = c.b16 + c.bi * (SLOT >> 4) + (g & 1) * 512;
      mbar_wait(bars + 8 * (BAR_FULLB + c.bi), c.bph, t0);
      mbar_wait(bars + 8 * (BAR_FULLA + c.ai), c.aph, t0);
      wgmma_fence();
#pragma unroll
      for (int s = 0; s < 4; s++) wgmma_ss<64>(own, desc_sw128<16>(a16 + s * 2), desc_sw128<2048>(b16 + s * 128));
      wgmma_commit();
      wgmma_wait<1>();
      release_prev(c);
      c.pa = c.ai; c.pb = -1;
      if (++c.ai == NA) { c.ai = 0; c.aph ^= 1; }
      if (g & 1) { if (++c.bi == NB) { c.bi = 0; c.bph ^= 1; } }
    }
    wgmma_wait<0>();
    if (tid == 0) TR(6);
    mbar_wait(bars + 8 * BAR_PIN, 0, t0);
    if (tid == 0) TR(7);
    {
      const uint32_t pin = sbase + OFF_KV + KVBUF + wg * 8192 + (tid & 127) * 16;
      __nv_bfloat16* o = P.out + (size_t)row0 * DM + j * 64 + (lane & 3) * 2;
#pragma unroll
      for (int i = 0; i < 4; i++) {
        const uint4 v = lds128(pin + i * 2048);
        const uint32_t r[4] = {v.x, v.y, v.z, v.w};
#pragma unroll
        for (int k = 0; k < 4; k++) {
          const int idx = 8 * i + 2 * k;
          const float lo = own[idx] + __uint_as_float(r[k] << 16), hi = own[idx + 1] + __uint_as_float(r[k] & 0xffff0000u);
          *(uint32_t*)(o + (k & 1) * 8 * DM + (2 * i + (k >> 1)) * 8) = pack_bf16(lo, hi);
        }
      }
    }
    if (tid == 0) TR(8);
  } else {
    asm volatile("setmaxnreg.dec.sync.aligned.u32 40;");
    if (warp == 8) {
      if (lane == 0) {
        mbar_expect_tx(bars + 8 * BAR_FULLA, 16384);
        tma_load_2d(sbase + OFF_A, &P.tmX, 0, rb * 128, bars + 8 * BAR_FULLA);
#pragma unroll
        for (int e = 0; e < 2; e++) {
          const uint32_t fb = bars + 8 * (BAR_FULLB + e);
          mbar_expect_tx(fb, typeB ? 12288 : 16384);
#pragma unroll
          for (int r = 0; r < 2; r++) {
            tma_load_3d(sbase + OFF_B + e * SLOT + r * 8192, &P.tmWqkv, 64 * j, e * 32 + r * 16, 0, fb);
            if (!typeB) tma_load_3d(sbase + OFF_B + e * SLOT + r * 8192 + 6144, &P.tmW1a, 0, e * 32 + r * 16, 24 + (j >> 1), fb);
          }
        }
        mbar_expect_tx(bars + 8 * (BAR_FULLA + 1), 16384);
        tma_load_2d(sbase + OFF_A + SLOT, &P.tmX, 64, rb * 128, bars + 8 * (BAR_FULLA + 1));
      }
      __syncwarp();
      cluster_wait();
      if (lane == 0) {
        int bi = 2; uint32_t bph = 1;
        const int nb = 32 + on + 4;
        for (int eb = 2; eb < nb; eb++) {
          if (eb == 4 || eb == 6) {
            for (int ea = eb - 2 - (eb == 6 ? 1 : 0); ea < (eb == 4 ? 3 : NA); ea++) {
              mbar_expect_tx(bars + 8 * (BAR_FULLA + ea), 16384);
              tma_load_2d(sbase + OFF_A + ea * SLOT, &P.tmX, ea * 64, rb * 128, bars + 8 * (BAR_FULLA + ea));
            }
          }
          const uint32_t fb = bars + 8 * (BAR_FULLB + bi), dst = sbase + OFF_B + bi * SLOT + rank * 8192;
          mbar_wait(bars + 8 * (BAR_EMPTYB + bi), bph, t0);
          if (eb < 16) {
            mbar_expect_tx(fb, typeB ? 12288 : 16384);
            tma_load_3d_mc(dst, &P.tmWqkv, 64 * j, eb * 32 + rank * 16, 0, fb);
            if (!typeB) tma_load_3d_mc(dst + 6144, &P.tmW1a, 0, eb * 32 + rank * 16, 24 + (j >> 1), fb);
          }
          else if (eb < 32) { mbar_expect_tx(fb, 12288); tma_load_3d_mc(dst, &P.tmW1b, 0, (eb - 16) * 32 + rank * 16, 3 * j, fb); }
          else if (eb < 32 + on) { int ow; const int ch = oh_chunk(j, eb - 32, ow); mbar_expect_tx(fb, 16384); tma_load_3d_mc(dst, &P.tmW2, 0, ch * 64 + rank * 32, (j >> 1) * 2, fb); }
          else { mbar_expect_tx(fb, 16384); tma_load_4d_mc(dst, &P.tmWo, 64 * j, 0, eb - 32 - on, rank * 4, fb); }
          if (++bi == NB) { bi = 0; bph ^= 1; }
          if (eb == PFAT) {
            const int b = blockIdx.x;
            l2_prefetch((const uint8_t*)P.w1 + b * 14336, 14336);
            l2_prefetch((const uint8_t*)P.w2 + b * 14336, 14336);
            l2_prefetch((const uint8_t*)P.wo + b * 4096, 4096);
          }
        }
      }
    } else if (warp == 9) {
      cluster_wait();
      if (lane == 0) {
        for (int ea = 0; ea < NA; ea++) mbar_arrive_n(bars + 8 * (BAR_EMPTYA + ea), 2);
        int ai = 0; uint32_t aph = 0;
        const int na = 16 + on + 8;
        unsigned ready = 0;
        for (int ea = NA; ea < na; ea++) {
          const uint32_t fb = bars + 8 * (BAR_FULLA + ai), dst = sbase + OFF_A + ai * SLOT;
          int ch = ea & 7, need = -1;
          if (ea >= 16 + on) { need = 8 + ea - 16 - on; ch = 20 + need; }
          else if (ea >= 19) ch = oh_chunk(j, ea - 16, need);
          if (need >= 0 && !((ready >> need) & 1)) {
            const unsigned* fp = need < 8 ? &g_flag_h[rb * 8 * FS] : need < 16 ? &g_flag_o[rb * 8 * FS] : &g_flag_e[rb * 8 * FS];
            const unsigned tgt = (need & 8) ? ep1 * 8 : ep1 * 2;
            do {
              unsigned v[8];
#pragma unroll
              for (int i = 0; i < 8; i++) v[i] = ld_relaxed(fp + i * FS);
#pragma unroll
              for (int i = 0; i < 8; i++) if ((int)(v[i] - tgt) >= 0) ready |= 1u << (i + (need & 24));
            } while (!((ready >> need) & 1) && clk32() - t0 < TIMEOUT);
            fence_async_global();
          }
          mbar_wait(bars + 8 * (BAR_EMPTYA + ai), aph, t0);
          if (ea >= 16 && ea < 19) mbar_arrive(fb);
          else {
            if (ea != 15) mbar_arrive_n(bars + 8 * (BAR_EMPTYA + ai), 2);
            mbar_expect_tx(fb, 16384);
            tma_load_2d(dst, ea < 16 ? &P.tmX : &P.tmHO, ch * 64, rb * 128, fb);
          }
          TR(24 + ea);
          if (++ai == NA) { ai = 0; aph ^= 1; }
        }
      }
    } else {
      const int wg = warp - 10;
      cluster_wait();
      {
        const int rowg = rb * 128 + j * 16 + wg * 8;
        const uint32_t xs = sbase + OFF_KV + 32768 + wg * 8192;
        if (lane == 0) {
          mbar_wait(bars + 8 * (BAR_FULLB + 1), 0, t0);
          mbar_expect_tx(bars + 8 * (BAR_GATE + wg), 8192);
          bulk_load(xs, P.x + (size_t)rowg * DM, 8192, bars + 8 * (BAR_GATE + wg));
        }
        const uint4* gw = (const uint4*)P.gate_w;
        const uint4 w0 = __ldg(gw + lane), w1 = __ldg(gw + 32 + lane);
        const uint32_t wa[8] = {w0.x, w0.y, w0.z, w0.w, w1.x, w1.y, w1.z, w1.w};
        mbar_wait(bars + 8 * (BAR_GATE + wg), 0, t0);
        float zz = 0.f;
#pragma unroll 1
        for (int i = 0; i < 8; i++) {
          const uint4 x0 = lds128(xs + i * 1024 + lane * 16), x1 = lds128(xs + i * 1024 + 512 + lane * 16);
          const uint32_t xa[8] = {x0.x, x0.y, x0.z, x0.w, x1.x, x1.y, x1.z, x1.w};
          float z = 0.f;
#pragma unroll
          for (int e = 0; e < 8; e++) {
            z = fmaf(__uint_as_float(xa[e] << 16), __uint_as_float(wa[e] << 16), z);
            z = fmaf(__uint_as_float(xa[e] & 0xffff0000u), __uint_as_float(wa[e] & 0xffff0000u), z);
          }
#pragma unroll
          for (int o = 16; o > 0; o >>= 1) z += __shfl_xor_sync(0xffffffffu, z, o);
          if (lane == i) zz = z;
        }
        if (lane < 8) asm volatile("st.shared.f32 [%0], %1;" ::"r"(sbase + OFF_GST + wg * 32 + lane * 4), "f"(1.f / (1.f + __expf(-zz))) : "memory");
        fence_async_smem();
        __syncwarp();
        if (lane == 0) {
          bulk_store(&g_gate[rowg], sbase + OFF_GST + wg * 32, 32);
          bulk_commit(); bulk_wait_all();
          flag_add(&g_flag_g[rb * FS]);
          if (wg == 0) TR(10);
        }
      }
      if (lane == 0) {
        const uint32_t stg = bars + 8 * (BAR_STG + wg);
        mbar_wait(stg, 0, t0);
        for (int hh = 0; hh < 4; hh++)
          bulk_store(g_kv + ((size_t)(4 * j + hh) * SEQ + rb * 128 + wg * 64) * 64, sbase + OFF_KV + hh * 8192 + wg * 4096, 4096);
        bulk_commit(); bulk_wait_all();
        flag_add(&g_flag_kv[(rb * 8 + j) * FS]);
        if (wg == 0) TR(21);
        if (!typeB) {
          mbar_wait(bars + 8 * (BAR_STE + wg), 0, t0);
          tma_store_2d(&P.tmHOs, (24 + (j >> 1)) * 64, rb * 128 + wg * 64, sbase + OFF_KV + 32768 + wg * 8192);
          bulk_commit(); bulk_wait_all();
          flag_add(&g_flag_e[(rb * 8 + j) * FS]);
          if (wg == 1) flag_wait(&g_flag_e[(rb * 8 + j) * FS], ep1 * 2, t0);
        }
        const int nblk = rb >= 2 ? 3 : rb + 1;
        const uint32_t kvbytes = nblk * 8192;
        const uint8_t* kvsrc = g_kv + ((size_t)(4 * j) * SEQ + (rb + 1 - nblk) * 128) * 64;
        const uint32_t kvdst = sbase + OFF_KV + wg * KVBUF + (3 - nblk) * 8192;
        {
          const unsigned* f0 = &g_flag_kv[(rb * 8 + j) * FS];
          const unsigned* f1 = rb >= 1 ? f0 - 8 * FS : f0;
          const unsigned* f2 = rb >= 2 ? f0 - 16 * FS : f0;
          unsigned v0, v1, v2;
          do { v0 = ld_relaxed(f0); v1 = ld_relaxed(f1); v2 = ld_relaxed(f2); }
          while (((int)(v0 - ep1 * 2) < 0 || (int)(v1 - ep1 * 2) < 0 || (int)(v2 - ep1 * 2) < 0) && clk32() - t0 < TIMEOUT);
        }
        if (wg == 0) TR(11);
        fence_async_global();
        mbar_expect_tx(bars + 8 * (BAR_KVFULL + wg), kvbytes);
        bulk_load(kvdst, kvsrc + (size_t)wg * SEQ * 64, kvbytes, bars + 8 * (BAR_KVFULL + wg));
        for (int ev = 1; ev < 7; ev++) {
          mbar_wait(stg, ev & 1, t0);
          if (ev == 1) {
            for (int i = 0; i < 3; i++)
              tma_store_2d(&P.tmHOs, (3 * j + i) * 64, rb * 128 + wg * 64, sbase + OFF_A + ((16 + i) % NA) * SLOT + wg * 8192);
            bulk_commit(); bulk_wait_all();
            flag_add(&g_flag_h[(rb * 8 + j) * FS]);
            for (int i = 0; i < 3; i++) mbar_arrive(bars + 8 * (BAR_EMPTYA + (16 + i) % NA));
            if (wg == 0) TR(22);
            if (wg == 0) {
              const unsigned old = atomicAdd(&g_done, 1u);
              if (old == gridDim.x - 1) { g_done = 0; *(volatile unsigned*)&g_epoch = ep1; }
            }
          } else if (ev == 6) {
            bulk_store(g_part + (size_t)(rb * 8 + (j ^ 1)) * 16384 + wg * 8192, sbase + OFF_KV + wg * 8192, 8192);
            bulk_commit(); bulk_wait_all();
            flag_add(&g_flag_p[(rb * 8 + (j ^ 1)) * FS]);
            if (wg == 0) TR(23);
            if (wg == 1) {
              mbar_wait(bars + 8 * (BAR_KVEMPTY + 1), 1, t0);
              flag_wait(&g_flag_p[(rb * 8 + j) * FS], ep1 * 2, t0);
              fence_async_global();
              mbar_expect_tx(bars + 8 * BAR_PIN, 16384);
              bulk_load(sbase + OFF_KV + KVBUF, g_part + (size_t)(rb * 8 + j) * 16384, 16384, bars + 8 * BAR_PIN);
            }
          } else {
            const int hh = ev - 2;
            tma_store_2d(&P.tmOs, DFF + hh * 128 + j * 16, rb * 128 + wg * 64, sbase + OFF_A + (15 % NA) * SLOT + wg * 8192 + hh * 2048);
            bulk_commit();
            if (hh == wg) {
              mbar_wait(bars + 8 * (BAR_KVEMPTY + wg), 0, t0);
              mbar_expect_tx(bars + 8 * (BAR_KVFULL + wg), kvbytes);
              bulk_load(kvdst, kvsrc + (size_t)(wg + 2) * SEQ * 64, kvbytes, bars + 8 * (BAR_KVFULL + wg));
            }
            bulk_wait_all();
            flag_add(&g_flag_o[(rb * 8 + hh * 2 + (j >> 2)) * FS]);
            if (hh == 3) mbar_arrive(bars + 8 * (BAR_EMPTYA + 15 % NA));
            if (wg == 0) TR(12 + hh);
          }
        }
      }
    }
  }
}

typedef CUresult (*EncodeFn)(CUtensorMap*, CUtensorMapDataType, cuuint32_t, void*, const cuuint64_t*, const cuuint64_t*, const cuuint32_t*,
                             const cuuint32_t*, CUtensorMapInterleave, CUtensorMapSwizzle, CUtensorMapL2promotion, CUtensorMapFloatOOBfill);

void make_map(EncodeFn enc, CUtensorMap* m, const void* ptr, int rank, const cuuint64_t* dims, const cuuint64_t* strides, const cuuint32_t* box,
              CUtensorMapSwizzle sw = CU_TENSOR_MAP_SWIZZLE_128B) {
  cuuint32_t es[4] = {1, 1, 1, 1};
  enc(m, CU_TENSOR_MAP_DATA_TYPE_BFLOAT16, rank, const_cast<void*>(ptr), dims, strides, box, es, CU_TENSOR_MAP_INTERLEAVE_NONE, sw,
      CU_TENSOR_MAP_L2_PROMOTION_L2_256B, CU_TENSOR_MAP_FLOAT_OOB_FILL_NONE);
}

}

extern "C" void kernel_launch(void* const* d_in, const int* in_sizes, int n_in, void* d_out, int out_size) {
  (void)in_sizes; (void)n_in; (void)out_size;
  static EncodeFn enc = nullptr;
  static void* ho_ptr = nullptr;
  if (!enc) {
    void* fn = nullptr; cudaDriverEntryPointQueryResult st;
    cudaGetDriverEntryPoint("cuTensorMapEncodeTiled", &fn, cudaEnableDefault, &st);
    enc = (EncodeFn)fn;
    cudaGetSymbolAddress(&ho_ptr, g_ho);
    cudaFuncSetAttribute(fused_kernel, cudaFuncAttributeMaxDynamicSharedMemorySize, SMEM_BYTES);
  }
  const __nv_bfloat16* x = (const __nv_bfloat16*)d_in[0];
  const __nv_bfloat16* wqkv = (const __nv_bfloat16*)d_in[1];
  const __nv_bfloat16* wo = (const __nv_bfloat16*)d_in[2];
  const __nv_bfloat16* w1 = (const __nv_bfloat16*)d_in[4];
  const __nv_bfloat16* w2 = (const __nv_bfloat16*)d_in[5];
  const __nv_bfloat16* gate_w = (const __nv_bfloat16*)d_in[6];
  Params P;
  { cuuint64_t d[2] = {DM, SEQ}, s[1] = {DM * 2}; cuuint32_t b[2] = {64, 128}; make_map(enc, &P.tmX, x, 2, d, s, b); }
  { cuuint64_t d[3] = {512, 512, 3}, s[2] = {1536 * 2, 512 * 2}; cuuint32_t b[3] = {64, 16, 3}; make_map(enc, &P.tmWqkv, wqkv, 3, d, s, b); }
  { cuuint64_t d[3] = {64, 512, 28}, s[2] = {DFF * 2, 128}; cuuint32_t b[3] = {64, 16, 1}; make_map(enc, &P.tmW1a, w1, 3, d, s, b);
    b[2] = 3; make_map(enc, &P.tmW1b, w1, 3, d, s, b); }
  { cuuint64_t d[3] = {64, DFF, 8}, s[2] = {DM * 2, 128}; cuuint32_t b[3] = {64, 32, 2}; make_map(enc, &P.tmW2, w2, 3, d, s, b); }
  { cuuint64_t d[4] = {DM, 16, 4, 8}, s[3] = {DM * 2, 16 * DM * 2, 64 * DM * 2}; cuuint32_t b[4] = {64, 16, 1, 4}; make_map(enc, &P.tmWo, wo, 4, d, s, b); }
  { cuuint64_t d[2] = {KHO, SEQ}, s[1] = {KHO * 2}; cuuint32_t b[2] = {64, 128}; make_map(enc, &P.tmHO, ho_ptr, 2, d, s, b);
    b[1] = 64; make_map(enc, &P.tmHOs, ho_ptr, 2, d, s, b);
    b[0] = 16; make_map(enc, &P.tmOs, ho_ptr, 2, d, s, b, CU_TENSOR_MAP_SWIZZLE_NONE); }
  P.x = x; P.gate_w = gate_w; P.w1 = w1; P.w2 = w2; P.wo = wo; P.out = (__nv_bfloat16*)d_out;
  fused_kernel<<<128, 384, SMEM_BYTES>>>(P);
}
```

```cpp
#include <cuda_runtime.h>
#include <cuda_bf16.h>
#include <cuda.h>
#include <stdint.h>

#define DEVI __device__ __forceinline__

namespace {

constexpr int SEQ = 2048, DM = 512, DFF = 1792, KHO = 2304;
constexpr int NA = 5, NB = 6, SLOT = 16384, KVBUF = 24576;
constexpr int OFF_A = 0, OFF_B = NA * SLOT, OFF_KV = OFF_B + NB * SLOT, OFF_BAR = OFF_KV + 2 * KVBUF;
constexpr int OFF_GST = OFF_BAR + 512;
constexpr int SMEM_BYTES = OFF_BAR + 1024 + 1024;
constexpr uint32_t TIMEOUT = 1u << 28;
#define WAIT_HINT_NS 20000u
#define PFAT 8
constexpr int FS = 8;

constexpr int BAR_FULLA = 0, BAR_EMPTYA = BAR_FULLA + NA, BAR_FULLB = BAR_EMPTYA + NA, BAR_EMPTYB = BAR_FULLB + NB,
              BAR_KVFULL = BAR_EMPTYB + NB, BAR_KVEMPTY = BAR_KVFULL + 2, BAR_STG = BAR_KVEMPTY + 2, BAR_PIN = BAR_STG + 2, BAR_GATE = BAR_PIN + 1, BAR_STE = BAR_GATE + 2;

__device__ __align__(1024) uint8_t g_kv[32 * SEQ * 64];
__device__ __align__(1024) __nv_bfloat16 g_ho[SEQ * KHO];
__device__ __align__(1024) uint8_t g_part[128 * 16384];
__device__ __align__(128) float g_gate[SEQ];
__device__ unsigned g_flag_kv[128 * FS], g_flag_h[128 * FS], g_flag_o[128 * FS], g_flag_g[16 * FS], g_flag_p[128 * FS], g_flag_e[128 * FS];
__device__ unsigned g_epoch, g_done;
#define TR(i) do {} while (0)

struct Params {
  CUtensorMap tmX, tmWqkv, tmW1a, tmW1b, tmW2, tmWo, tmHO, tmHOs, tmOs;
  const __nv_bfloat16* x;
  const __nv_bfloat16* gate_w;
  const __nv_bfloat16* w1;
  const __nv_bfloat16* w2;
  const __nv_bfloat16* wo;
  __nv_bfloat16* out;
};

DEVI uint32_t smem_u32(const void* p) { return (uint32_t)__cvta_generic_to_shared(p); }
DEVI uint32_t clk32() { uint32_t c; asm volatile("mov.u32 %0, %%clock;" : "=r"(c)); return c; }
DEVI void mbar_init(uint32_t bar, uint32_t cnt) { asm volatile("mbarrier.init.shared::cta.b64 [%0], %1;" ::"r"(bar), "r"(cnt)); }
DEVI void mbar_expect_tx(uint32_t bar, uint32_t bytes) { asm volatile("mbarrier.arrive.expect_tx.shared::cta.b64 _, [%0], %1;" ::"r"(bar), "r"(bytes) : "memory"); }
DEVI void mbar_arrive(uint32_t bar) { asm volatile("mbarrier.arrive.shared::cta.b64 _, [%0];" ::"r"(bar) : "memory"); }
DEVI void mbar_arrive_n(uint32_t bar, uint32_t n) { asm volatile("mbarrier.arrive.shared::cta.b64 _, [%0], %1;" ::"r"(bar), "r"(n) : "memory"); }
DEVI void mbar_arrive_cluster(uint32_t bar, uint32_t cta) {
  asm volatile("{ .reg .b32 ra; mapa.shared::cluster.u32 ra, %0, %1; mbarrier.arrive.shared::cluster.b64 _, [ra]; }" ::"r"(bar), "r"(cta) : "memory");
}
DEVI void mbar_wait(uint32_t bar, uint32_t parity, uint32_t t0) {
  asm volatile("{ .reg .pred p; .reg .u32 c;\n"
               "mbarrier.try_wait.parity.shared::cta.b64 p, [%0], %1;\n"
               "@p bra DONE_%=;\n"
               "WAIT_%=:\n"
               "mbarrier.try_wait.parity.shared::cta.b64 p, [%0], %1, %4;\n"
               "@p bra DONE_%=;\n"
               "mov.u32 c, %%clock; sub.u32 c, c, %2; setp.lt.u32 p, c, %3;\n"
               "@p bra WAIT_%=;\n"
               "DONE_%=: }" ::"r"(bar), "r"(parity), "r"(t0), "n"(TIMEOUT), "r"(WAIT_HINT_NS) : "memory");
}
DEVI unsigned ld_relaxed(const unsigned* p) { unsigned v; asm volatile("ld.relaxed.gpu.global.u32 %0, [%1];" : "=r"(v) : "l"(p) : "memory"); return v; }
DEVI float ld_relaxed_f(const float* p) { float v; asm volatile("ld.relaxed.gpu.global.f32 %0, [%1];" : "=f"(v) : "l"(p) : "memory"); return v; }
DEVI void flag_wait(const unsigned* p, unsigned target, uint32_t t0) {
  while ((int)(ld_relaxed(p) - target) < 0) { if (clk32() - t0 > TIMEOUT) break; }
}
DEVI void flag_add(unsigned* p) { asm volatile("red.relaxed.gpu.global.add.u32 [%0], 1;" ::"l"(p) : "memory"); }
DEVI void fence_async_smem() { asm volatile("fence.proxy.async.shared::cta;" ::: "memory"); }
DEVI void fence_async_global() { asm volatile("fence.proxy.async.global;" ::: "memory"); }
DEVI void tma_load_2d(uint32_t dst, const CUtensorMap* m, int c0, int c1, uint32_t bar) {
  asm volatile("cp.async.bulk.tensor.2d.shared::cluster.global.mbarrier::complete_tx::bytes [%0], [%1, {%3, %4}], [%2];" ::"r"(dst), "l"(m), "r"(bar), "r"(c0), "r"(c1) : "memory");
}
DEVI void tma_load_3d(uint32_t dst, const CUtensorMap* m, int c0, int c1, int c2, uint32_t bar) {
  asm volatile("cp.async.bulk.tensor.3d.shared::cluster.global.mbarrier::complete_tx::bytes [%0], [%1, {%3, %4, %5}], [%2];"
               ::"r"(dst), "l"(m), "r"(bar), "r"(c0), "r"(c1), "r"(c2) : "memory");
}
DEVI void tma_load_3d_mc(uint32_t dst, const CUtensorMap* m, int c0, int c1, int c2, uint32_t bar) {
  asm volatile("cp.async.bulk.tensor.3d.shared::cluster.global.mbarrier::complete_tx::bytes.multicast::cluster [%0], [%1, {%3, %4, %5}], [%2], %6;"
               ::"r"(dst), "l"(m), "r"(bar), "r"(c0), "r"(c1), "r"(c2), "h"((uint16_t)3) : "memory");
}
DEVI void tma_load_4d_mc(uint32_t dst, const CUtensorMap* m, int c0, int c1, int c2, int c3, uint32_t bar) {
  asm volatile("cp.async.bulk.tensor.4d.shared::cluster.global.mbarrier::complete_tx::bytes.multicast::cluster [%0], [%1, {%3, %4, %5, %6}], [%2], %7;"
               ::"r"(dst), "l"(m), "r"(bar), "r"(c0), "r"(c1), "r"(c2), "r"(c3), "h"((uint16_t)3) : "memory");
}
DEVI void tma_store_2d(const CUtensorMap* m, int c0, int c1, uint32_t src) {
  asm volatile("cp.async.bulk.tensor.2d.global.shared::cta.bulk_group [%0, {%1, %2}], [%3];" ::"l"(m), "r"(c0), "r"(c1), "r"(src) : "memory");
}
DEVI void bulk_store(void* dst, uint32_t src, uint32_t bytes) {
  asm volatile("cp.async.bulk.global.shared::cta.bulk_group [%0], [%1], %2;" ::"l"(dst), "r"(src), "r"(bytes) : "memory");
}
DEVI void bulk_load(uint32_t dst, const void* src, uint32_t bytes, uint32_t bar) {
  asm volatile("cp.async.bulk.shared::cluster.global.mbarrier::complete_tx::bytes [%0], [%1], %2, [%3];" ::"r"(dst), "l"(src), "r"(bytes), "r"(bar) : "memory");
}
DEVI void bulk_commit() { asm volatile("cp.async.bulk.commit_group;" ::: "memory"); }
DEVI void bulk_wait_all() { asm volatile("cp.async.bulk.wait_group 0;" ::: "memory"); }
DEVI void l2_prefetch(const void* p, uint32_t bytes) { asm volatile("cp.async.bulk.prefetch.L2.global [%0], %1;" ::"l"(p), "r"(bytes) : "memory"); }
DEVI void cluster_arrive() { asm volatile("barrier.cluster.arrive.relaxed.aligned;" ::: "memory"); }
DEVI void cluster_wait() { asm volatile("barrier.cluster.wait.aligned;" ::: "memory"); }
template <int ID> DEVI void named_bar(int n) { asm volatile("bar.sync %0, %1;" ::"n"(ID), "r"(n) : "memory"); }
DEVI void wg_bar(int wg) { if (wg == 0) named_bar<1>(128); else named_bar<2>(128); }
DEVI void wgmma_fence() { asm volatile("wgmma.fence.sync.aligned;" ::: "memory"); }
DEVI void wgmma_commit() { asm volatile("wgmma.commit_group.sync.aligned;" ::: "memory"); }
template <int N> DEVI void wgmma_wait() { asm volatile("wgmma.wait_group.sync.aligned %0;" ::"n"(N) : "memory"); }
template <uint32_t LBO> DEVI uint64_t desc_sw128(uint32_t a16) {
  return ((uint64_t)(0x40000000u | (1024 >> 4)) << 32) | (a16 + ((LBO >> 4) << 16));
}
DEVI uint64_t desc_sw64(uint32_t a16) {
  return ((uint64_t)(0x80000000u | (512 >> 4)) << 32) | (a16 + ((512 >> 4) << 16));
}
DEVI uint32_t pack_bf16(float lo, float hi) { uint32_t r; asm("cvt.rn.bf16x2.f32 %0, %1, %2;" : "=r"(r) : "f"(hi), "f"(lo)); return r; }
DEVI void stsm_x4(uint32_t addr, uint32_t r0, uint32_t r1, uint32_t r2, uint32_t r3) {
  asm volatile("stmatrix.sync.aligned.m8n8.x4.shared.b16 [%0], {%1, %2, %3, %4};" ::"r"(addr), "r"(r0), "r"(r1), "r"(r2), "r"(r3) : "memory");
}
DEVI void sts128(uint32_t addr, uint32_t r0, uint32_t r1, uint32_t r2, uint32_t r3) {
  asm volatile("st.shared.v4.b32 [%0], {%1, %2, %3, %4};" ::"r"(addr), "r"(r0), "r"(r1), "r"(r2), "r"(r3) : "memory");
}
DEVI uint4 lds128(uint32_t addr) {
  uint4 v; asm volatile("ld.shared.v4.b32 {%0, %1, %2, %3}, [%4];" : "=r"(v.x), "=r"(v.y), "=r"(v.z), "=r"(v.w) : "r"(addr) : "memory"); return v;
}
DEVI float ex2(float x) { float y; asm("ex2.approx.ftz.f32 %0, %1;" : "=f"(y) : "f"(x)); return y; }

DEVI void wgmma_ss_n64(float (&d)[32], uint64_t da, uint64_t db) {
  asm volatile("wgmma.mma_async.sync.aligned.m64n64k16.f32.bf16.bf16 {%0, %1, %2, %3, %4, %5, %6, %7, %8, %9, %10, %11, %12, %13, %14, %15, %16, %17, %18, %19, %20, %21, %22, %23, %24, %25, %26, %27, %28, %29, %30, %31}, %32, %33, 1, 1, 1, 0, 1;"
    : "+f"(d[0]), "+f"(d[1]), "+f"(d[2]), "+f"(d[3]), "+f"(d[4]), "+f"(d[5]), "+f"(d[6]), "+f"(d[7]), "+f"(d[8]), "+f"(d[9]), "+f"(d[10]), "+f"(d[11]), "+f"(d[12]), "+f"(d[13]), "+f"(d[14]), "+f"(d[15]), "+f"(d[16]), "+f"(d[17]), "+f"(d[18]), "+f"(d[19]), "+f"(d[20]), "+f"(d[21]), "+f"(d[22]), "+f"(d[23]), "+f"(d[24]), "+f"(d[25]), "+f"(d[26]), "+f"(d[27]), "+f"(d[28]), "+f"(d[29]), "+f"(d[30]), "+f"(d[31])
    : "l"(da), "l"(db));
}
DEVI void wgmma_ss_n128(float (&d)[64], uint64_t da, uint64_t db) {
  asm volatile("wgmma.mma_async.sync.aligned.m64n128k16.f32.bf16.bf16 {%0, %1, %2, %3, %4, %5, %6, %7, %8, %9, %10, %11, %12, %13, %14, %15, %16, %17, %18, %19, %20, %21, %22, %23, %24, %25, %26, %27, %28, %29, %30, %31, %32, %33, %34, %35, %36, %37, %38, %39, %40, %41, %42, %43, %44, %45, %46, %47, %48, %49, %50, %51, %52, %53, %54, %55, %56, %57, %58, %59, %60, %61, %62, %63}, %64, %65, 1, 1, 1, 0, 1;"
    : "+f"(d[0]), "+f"(d[1]), "+f"(d[2]), "+f"(d[3]), "+f"(d[4]), "+f"(d[5]), "+f"(d[6]), "+f"(d[7]), "+f"(d[8]), "+f"(d[9]), "+f"(d[10]), "+f"(d[11]), "+f"(d[12]), "+f"(d[13]), "+f"(d[14]), "+f"(d[15]), "+f"(d[16]), "+f"(d[17]), "+f"(d[18]), "+f"(d[19]), "+f"(d[20]), "+f"(d[21]), "+f"(d[22]), "+f"(d[23]), "+f"(d[24]), "+f"(d[25]), "+f"(d[26]), "+f"(d[27]), "+f"(d[28]), "+f"(d[29]), "+f"(d[30]), "+f"(d[31]), "+f"(d[32]), "+f"(d[33]), "+f"(d[34]), "+f"(d[35]), "+f"(d[36]), "+f"(d[37]), "+f"(d[38]), "+f"(d[39]), "+f"(d[40]), "+f"(d[41]), "+f"(d[42]), "+f"(d[43]), "+f"(d[44]), "+f"(d[45]), "+f"(d[46]), "+f"(d[47]), "+f"(d[48]), "+f"(d[49]), "+f"(d[50]), "+f"(d[51]), "+f"(d[52]), "+f"(d[53]), "+f"(d[54]), "+f"(d[55]), "+f"(d[56]), "+f"(d[57]), "+f"(d[58]), "+f"(d[59]), "+f"(d[60]), "+f"(d[61]), "+f"(d[62]), "+f"(d[63])
    : "l"(da), "l"(db));
}
DEVI void wgmma_ss_n192(float (&d)[96], uint64_t da, uint64_t db) {
  asm volatile("wgmma.mma_async.sync.aligned.m64n192k16.f32.bf16.bf16 {%0, %1, %2, %3, %4, %5, %6, %7, %8, %9, %10, %11, %12, %13, %14, %15, %16, %17, %18, %19, %20, %21, %22, %23, %24, %25, %26, %27, %28, %29, %30, %31, %32, %33, %34, %35, %36, %37, %38, %39, %40, %41, %42, %43, %44, %45, %46, %47, %48, %49, %50, %51, %52, %53, %54, %55, %56, %57, %58, %59, %60, %61, %62, %63, %64, %65, %66, %67, %68, %69, %70, %71, %72, %73, %74, %75, %76, %77, %78, %79, %80, %81, %82, %83, %84, %85, %86, %87, %88, %89, %90, %91, %92, %93, %94, %95}, %96, %97, 1, 1, 1, 0, 1;"
    : "+f"(d[0]), "+f"(d[1]), "+f"(d[2]), "+f"(d[3]), "+f"(d[4]), "+f"(d[5]), "+f"(d[6]), "+f"(d[7]), "+f"(d[8]), "+f"(d[9]), "+f"(d[10]), "+f"(d[11]), "+f"(d[12]), "+f"(d[13]), "+f"(d[14]), "+f"(d[15]), "+f"(d[16]), "+f"(d[17]), "+f"(d[18]), "+f"(d[19]), "+f"(d[20]), "+f"(d[21]), "+f"(d[22]), "+f"(d[23]), "+f"(d[24]), "+f"(d[25]), "+f"(d[26]), "+f"(d[27]), "+f"(d[28]), "+f"(d[29]), "+f"(d[30]), "+f"(d[31]), "+f"(d[32]), "+f"(d[33]), "+f"(d[34]), "+f"(d[35]), "+f"(d[36]), "+f"(d[37]), "+f"(d[38]), "+f"(d[39]), "+f"(d[40]), "+f"(d[41]), "+f"(d[42]), "+f"(d[43]), "+f"(d[44]), "+f"(d[45]), "+f"(d[46]), "+f"(d[47]), "+f"(d[48]), "+f"(d[49]), "+f"(d[50]), "+f"(d[51]), "+f"(d[52]), "+f"(d[53]), "+f"(d[54]), "+f"(d[55]), "+f"(d[56]), "+f"(d[57]), "+f"(d[58]), "+f"(d[59]), "+f"(d[60]), "+f"(d[61]), "+f"(d[62]), "+f"(d[63]), "+f"(d[64]), "+f"(d[65]), "+f"(d[66]), "+f"(d[67]), "+f"(d[68]), "+f"(d[69]), "+f"(d[70]), "+f"(d[71]), "+f"(d[72]), "+f"(d[73]), "+f"(d[74]), "+f"(d[75]), "+f"(d[76]), "+f"(d[77]), "+f"(d[78]), "+f"(d[79]), "+f"(d[80]), "+f"(d[81]), "+f"(d[82]), "+f"(d[83]), "+f"(d[84]), "+f"(d[85]), "+f"(d[86]), "+f"(d[87]), "+f"(d[88]), "+f"(d[89]), "+f"(d[90]), "+f"(d[91]), "+f"(d[92]), "+f"(d[93]), "+f"(d[94]), "+f"(d[95])
    : "l"(da), "l"(db));
}
DEVI void wgmma_ss_n256(float (&d)[128], uint64_t da, uint64_t db) {
  asm volatile("wgmma.mma_async.sync.aligned.m64n256k16.f32.bf16.bf16 {%0, %1, %2, %3, %4, %5, %6, %7, %8, %9, %10, %11, %12, %13, %14, %15, %16, %17, %18, %19, %20, %21, %22, %23, %24, %25, %26, %27, %28, %29, %30, %31, %32, %33, %34, %35, %36, %37, %38, %39, %40, %41, %42, %43, %44, %45, %46, %47, %48, %49, %50, %51, %52, %53, %54, %55, %56, %57, %58, %59, %60, %61, %62, %63, %64, %65, %66, %67, %68, %69, %70, %71, %72, %73, %74, %75, %76, %77, %78, %79, %80, %81, %82, %83, %84, %85, %86, %87, %88, %89, %90, %91, %92, %93, %94, %95, %96, %97, %98, %99, %100, %101, %102, %103, %104, %105, %106, %107, %108, %109, %110, %111, %112, %113, %114, %115, %116, %117, %118, %119, %120, %121, %122, %123, %124, %125, %126, %127}, %128, %129, 1, 1, 1, 0, 1;"
    : "+f"(d[0]), "+f"(d[1]), "+f"(d[2]), "+f"(d[3]), "+f"(d[4]), "+f"(d[5]), "+f"(d[6]), "+f"(d[7]), "+f"(d[8]), "+f"(d[9]), "+f"(d[10]), "+f"(d[11]), "+f"(d[12]), "+f"(d[13]), "+f"(d[14]), "+f"(d[15]), "+f"(d[16]), "+f"(d[17]), "+f"(d[18]), "+f"(d[19]), "+f"(d[20]), "+f"(d[21]), "+f"(d[22]), "+f"(d[23]), "+f"(d[24]), "+f"(d[25]), "+f"(d[26]), "+f"(d[27]), "+f"(d[28]), "+f"(d[29]), "+f"(d[30]), "+f"(d[31]), "+f"(d[32]), "+f"(d[33]), "+f"(d[34]), "+f"(d[35]), "+f"(d[36]), "+f"(d[37]), "+f"(d[38]), "+f"(d[39]), "+f"(d[40]), "+f"(d[41]), "+f"(d[42]), "+f"(d[43]), "+f"(d[44]), "+f"(d[45]), "+f"(d[46]), "+f"(d[47]), "+f"(d[48]), "+f"(d[49]), "+f"(d[50]), "+f"(d[51]), "+f"(d[52]), "+f"(d[53]), "+f"(d[54]), "+f"(d[55]), "+f"(d[56]), "+f"(d[57]), "+f"(d[58]), "+f"(d[59]), "+f"(d[60]), "+f"(d[61]), "+f"(d[62]), "+f"(d[63]), "+f"(d[64]), "+f"(d[65]), "+f"(d[66]), "+f"(d[67]), "+f"(d[68]), "+f"(d[69]), "+f"(d[70]), "+f"(d[71]), "+f"(d[72]), "+f"(d[73]), "+f"(d[74]), "+f"(d[75]), "+f"(d[76]), "+f"(d[77]), "+f"(d[78]), "+f"(d[79]), "+f"(d[80]), "+f"(d[81]), "+f"(d[82]), "+f"(d[83]), "+f"(d[84]), "+f"(d[85]), "+f"(d[86]), "+f"(d[87]), "+f"(d[88]), "+f"(d[89]), "+f"(d[90]), "+f"(d[91]), "+f"(d[92]), "+f"(d[93]), "+f"(d[94]), "+f"(d[95]), "+f"(d[96]), "+f"(d[97]), "+f"(d[98]), "+f"(d[99]), "+f"(d[100]), "+f"(d[101]), "+f"(d[102]), "+f"(d[103]), "+f"(d[104]), "+f"(d[105]), "+f"(d[106]), "+f"(d[107]), "+f"(d[108]), "+f"(d[109]), "+f"(d[110]), "+f"(d[111]), "+f"(d[112]), "+f"(d[113]), "+f"(d[114]), "+f"(d[115]), "+f"(d[116]), "+f"(d[117]), "+f"(d[118]), "+f"(d[119]), "+f"(d[120]), "+f"(d[121]), "+f"(d[122]), "+f"(d[123]), "+f"(d[124]), "+f"(d[125]), "+f"(d[126]), "+f"(d[127])
    : "l"(da), "l"(db));
}
DEVI void wgmma_qk64(float (&d)[32], uint32_t a0, uint32_t a1, uint32_t a2, uint32_t a3, uint64_t db) {
  asm volatile("wgmma.mma_async.sync.aligned.m64n64k16.f32.bf16.bf16 {%0, %1, %2, %3, %4, %5, %6, %7, %8, %9, %10, %11, %12, %13, %14, %15, %16, %17, %18, %19, %20, %21, %22, %23, %24, %25, %26, %27, %28, %29, %30, %31}, {%32, %33, %34, %35}, %36, 0, 1, 1, 0;"
    : "=f"(d[0]), "=f"(d[1]), "=f"(d[2]), "=f"(d[3]), "=f"(d[4]), "=f"(d[5]), "=f"(d[6]), "=f"(d[7]), "=f"(d[8]), "=f"(d[9]), "=f"(d[10]), "=f"(d[11]), "=f"(d[12]), "=f"(d[13]), "=f"(d[14]), "=f"(d[15]), "=f"(d[16]), "=f"(d[17]), "=f"(d[18]), "=f"(d[19]), "=f"(d[20]), "=f"(d[21]), "=f"(d[22]), "=f"(d[23]), "=f"(d[24]), "=f"(d[25]), "=f"(d[26]), "=f"(d[27]), "=f"(d[28]), "=f"(d[29]), "=f"(d[30]), "=f"(d[31])
    : "r"(a0), "r"(a1), "r"(a2), "r"(a3), "l"(db));
}
DEVI void wgmma_qk128(float (&d)[64], uint32_t a0, uint32_t a1, uint32_t a2, uint32_t a3, uint64_t db) {
  asm volatile("wgmma.mma_async.sync.aligned.m64n128k16.f32.bf16.bf16 {%0, %1, %2, %3, %4, %5, %6, %7, %8, %9, %10, %11, %12, %13, %14, %15, %16, %17, %18, %19, %20, %21, %22, %23, %24, %25, %26, %27, %28, %29, %30, %31, %32, %33, %34, %35, %36, %37, %38, %39, %40, %41, %42, %43, %44, %45, %46, %47, %48, %49, %50, %51, %52, %53, %54, %55, %56, %57, %58, %59, %60, %61, %62, %63}, {%64, %65, %66, %67}, %68, 0, 1, 1, 0;"
    : "=f"(d[0]), "=f"(d[1]), "=f"(d[2]), "=f"(d[3]), "=f"(d[4]), "=f"(d[5]), "=f"(d[6]), "=f"(d[7]), "=f"(d[8]), "=f"(d[9]), "=f"(d[10]), "=f"(d[11]), "=f"(d[12]), "=f"(d[13]), "=f"(d[14]), "=f"(d[15]), "=f"(d[16]), "=f"(d[17]), "=f"(d[18]), "=f"(d[19]), "=f"(d[20]), "=f"(d[21]), "=f"(d[22]), "=f"(d[23]), "=f"(d[24]), "=f"(d[25]), "=f"(d[26]), "=f"(d[27]), "=f"(d[28]), "=f"(d[29]), "=f"(d[30]), "=f"(d[31]), "=f"(d[32]), "=f"(d[33]), "=f"(d[34]), "=f"(d[35]), "=f"(d[36]), "=f"(d[37]), "=f"(d[38]), "=f"(d[39]), "=f"(d[40]), "=f"(d[41]), "=f"(d[42]), "=f"(d[43]), "=f"(d[44]), "=f"(d[45]), "=f"(d[46]), "=f"(d[47]), "=f"(d[48]), "=f"(d[49]), "=f"(d[50]), "=f"(d[51]), "=f"(d[52]), "=f"(d[53]), "=f"(d[54]), "=f"(d[55]), "=f"(d[56]), "=f"(d[57]), "=f"(d[58]), "=f"(d[59]), "=f"(d[60]), "=f"(d[61]), "=f"(d[62]), "=f"(d[63])
    : "r"(a0), "r"(a1), "r"(a2), "r"(a3), "l"(db));
}
DEVI void wgmma_pv(float (&d)[8], uint32_t a0, uint32_t a1, uint32_t a2, uint32_t a3, uint64_t db) {
  asm volatile("wgmma.mma_async.sync.aligned.m64n16k16.f32.bf16.bf16 {%0, %1, %2, %3, %4, %5, %6, %7}, {%8, %9, %10, %11}, %12, 1, 1, 1, 1;"
    : "+f"(d[0]), "+f"(d[1]), "+f"(d[2]), "+f"(d[3]), "+f"(d[4]), "+f"(d[5]), "+f"(d[6]), "+f"(d[7])
    : "r"(a0), "r"(a1), "r"(a2), "r"(a3), "l"(db));
}
DEVI void wgmma_pv0(float (&d)[8], uint32_t a0, uint32_t a1, uint32_t a2, uint32_t a3, uint64_t db) {
  asm volatile("wgmma.mma_async.sync.aligned.m64n16k16.f32.bf16.bf16 {%0, %1, %2, %3, %4, %5, %6, %7}, {%8, %9, %10, %11}, %12, 0, 1, 1, 1;"
    : "=f"(d[0]), "=f"(d[1]), "=f"(d[2]), "=f"(d[3]), "=f"(d[4]), "=f"(d[5]), "=f"(d[6]), "=f"(d[7])
    : "r"(a0), "r"(a1), "r"(a2), "r"(a3), "l"(db));
}

template <int N> DEVI void wgmma_ss(float (&d)[N / 2], uint64_t da, uint64_t db) {
  if constexpr (N == 64) wgmma_ss_n64(d, da, db);
  else if constexpr (N == 128) wgmma_ss_n128(d, da, db);
  else if constexpr (N == 192) wgmma_ss_n192(d, da, db);
  else wgmma_ss_n256(d, da, db);
}

DEVI int oh_chunk(int j, int i, int& need) {
  if (j & 1) {
    if (i >= 3 && i < 7) { need = 16 + 2 * (i - 3); return 24 + (i - 3); }
    if (i >= 7) i -= 4;
  }
  const int g = i / 3, o = (j + 2 * g) & 7;
  need = o;
  return 3 * o + (i - 3 * g);
}

struct Ctx {
  uint32_t sbase, bars, peer, t0, a16, b16;
  int wg, lane;
  int ai, bi; uint32_t aph, bph;
  int brem;
  int pa, pb;
};

DEVI void release_prev(Ctx& c) {
  if (c.pb >= 0) {
    if (c.lane == 0) mbar_arrive(c.bars + 8 * (BAR_EMPTYB + c.pb));
    if (c.lane == 1) mbar_arrive_cluster(c.bars + 8 * (BAR_EMPTYB + c.pb), c.peer);
  }
  if (c.pa >= 0 && c.lane == 2) mbar_arrive(c.bars + 8 * (BAR_EMPTYA + c.pa));
}

DEVI void gemm_wait(Ctx& c) {
  asm volatile("{ .reg .pred p, q; .reg .u32 c;\n"
               "WAIT_%=:\n"
               "mbarrier.try_wait.parity.shared::cta.b64 p, [%0], %1;\n"
               "mbarrier.try_wait.parity.shared::cta.b64 q, [%2], %3;\n"
               "and.pred p, p, q;\n"
               "@p bra DONE_%=;\n"
               "mov.u32 c, %%clock; sub.u32 c, c, %4; setp.lt.u32 p, c, %5;\n"
               "@p bra WAIT_%=;\n"
               "DONE_%=: }" ::"r"(c.bars + 8 * (BAR_FULLA + c.ai)), "r"(c.aph), "r"(c.bars + 8 * (BAR_FULLB + c.bi)), "r"(c.bph), "r"(c.t0), "n"(TIMEOUT) : "memory");
}
template <int N>
DEVI void gemm_group(float (&acc)[N / 2], Ctx& c, int g, int& npa, int& npb) {
  const uint32_t a16 = c.a16 + c.ai * (SLOT >> 4);
  const uint32_t b16 = c.b16 + c.bi * (SLOT >> 4);
  bool adv;
  if constexpr (N >= 192) {
    const uint32_t a2 = a16 + (g & 1) * 4;
    wgmma_ss<N>(acc, desc_sw128<16>(a2), desc_sw128<2048>(b16));
    wgmma_ss<N>(acc, desc_sw128<16>(a2 + 2), desc_sw128<2048>(b16 + 512));
    adv = g & 1;
  } else {
#pragma unroll
    for (int s = 0; s < 4; s++) wgmma_ss<N>(acc, desc_sw128<16>(a16 + s * 2), desc_sw128<4096>(b16 + (s >> 1) * 512 + (s & 1) * 128));
    adv = true;
  }
  wgmma_commit();
  npb = c.brem > 0 ? c.bi : -1;
  c.brem--;
  if (++c.bi == NB) { c.bi = 0; c.bph ^= 1; }
  npa = -1;
  if (adv) { npa = c.ai; if (++c.ai == NA) { c.ai = 0; c.aph ^= 1; } }
}

template <int N>
DEVI void bare_groups(float (&acc)[N / 2], Ctx& c, int g0, int g1) {
  for (int g = g0; g < g1; g++) {
    int npa, npb;
    gemm_wait(c);
    wgmma_fence();
    gemm_group<N>(acc, c, g, npa, npb);
    wgmma_wait<1>();
    release_prev(c);
    c.pa = npa; c.pb = npb;
  }
}
DEVI void drain(Ctx& c) {
  wgmma_wait<0>();
  release_prev(c);
  c.pa = c.pb = -1;
}

constexpr float SC = 0.25f * 1.4426950408889634f;

#define ONCE _Pragma("unroll 1") for (unsigned once_ = 0; once_ < gridDim.y; once_++)

struct Attn {
  uint32_t q[4][4];
  uint32_t nm[4];
  float g0, g1;
  int cmin;
  int rowc;
};

template <int O0, int NS>
DEVI void kill32(float (&S)[NS]) {
#pragma unroll
  for (int i = 0; i < 32; i++) S[O0 + i] = __int_as_float(0xff800000);
}
DEVI void row_max(const float (&S)[64], float& x0, float& x1) {
#pragma unroll
  for (int n = 0; n < 16; n++) {
    x0 = fmaxf(x0, fmaxf(S[4 * n], S[4 * n + 1])); x1 = fmaxf(x1, fmaxf(S[4 * n + 2], S[4 * n + 3]));
  }
}
template <int K, bool PRE = false>
DEVI void exp8(const float (&S)[64], uint32_t (&P)[4], float n0, float n1, float (&l)[4]) {
  float e[8];
#pragma unroll
  for (int i = 0; i < 8; i++) e[i] = ex2(PRE ? S[8 * K + i] : fmaf(S[8 * K + i], SC, (i & 2) ? n1 : n0));
  l[0] += e[0]; l[1] += e[1]; l[2] += e[2]; l[3] += e[3];
  l[0] += e[4]; l[1] += e[5]; l[2] += e[6]; l[3] += e[7];
#pragma unroll
  for (int i = 0; i < 4; i++) P[i] = pack_bf16(e[2 * i], e[2 * i + 1]) | (__float_as_uint(l[i]) & blockIdx.y);
}
DEVI void merge_fl(float (&S)[64], const float (&F)[32], int rowc) {
#pragma unroll
  for (int n = 0; n < 8; n++) {
    if (n * 8 > rowc) S[32 + 4 * n] = F[4 * n];
    if (n * 8 + 1 > rowc) S[32 + 4 * n + 1] = F[4 * n + 1];
    if (n * 8 > rowc + 8) S[32 + 4 * n + 2] = F[4 * n + 2];
    if (n * 8 + 1 > rowc + 8) S[32 + 4 * n + 3] = F[4 * n + 3];
  }
}
DEVI bool wg_any(int wg, bool v) {
  uint32_t r;
  if (wg == 0) asm volatile("{ .reg .pred p, q; setp.ne.u32 p, %1, 0; bar.red.or.pred q, 1, 128, p; selp.u32 %0, 1, 0, q; }" : "=r"(r) : "r"((uint32_t)v) : "memory");
  else asm volatile("{ .reg .pred p, q; setp.ne.u32 p, %1, 0; bar.red.or.pred q, 2, 128, p; selp.u32 %0, 1, 0, q; }" : "=r"(r) : "r"((uint32_t)v) : "memory");
  return r != 0;
}

template <bool FIRST> DEVI void pv_step(float (&O)[8], const uint32_t (&P)[4], uint32_t v16) {
  wgmma_wait<0>();
  wgmma_fence();
  if (FIRST) wgmma_pv0(O, P[0], P[1], P[2], P[3], desc_sw64(v16)); else wgmma_pv(O, P[0], P[1], P[2], P[3], desc_sw64(v16));
  wgmma_commit();
}
template <int K> DEVI void pv_merged(float (&O)[8], const uint32_t (&P)[4], uint32_t (&PL)[4], uint32_t (&PF)[4], int rowc, uint32_t kb) {
#pragma unroll
  for (int i = 0; i < 4; i++) {
    const int col = (K - 4) * 16 + (i >> 1) * 8, r = rowc + (i & 1) * 8;
    const uint32_t m = (col > r ? 0xFFFFu : 0u) | (col + 1 > r ? 0xFFFF0000u : 0u);
    PF[i] = P[i] & m; PL[i] = P[i] & ~m;
  }
  wgmma_wait<0>();
  wgmma_fence();
  wgmma_pv(O, PL[0], PL[1], PL[2], PL[3], desc_sw64(kb + 3 * 256 + 2 + K * 64));
  wgmma_pv(O, PF[0], PF[1], PF[2], PF[3], desc_sw64(kb + 2 + (K - 4) * 64));
  wgmma_commit();
}
DEVI void qk_a(float (&S)[64], float (&F)[32], const uint32_t (&q)[4], uint32_t kb) {
  wgmma_fence();
  wgmma_qk128(S, q[0], q[1], q[2], q[3], desc_sw64(kb + 3 * 256));
  wgmma_qk64(F, q[0], q[1], q[2], q[3], desc_sw64(kb));
}
DEVI void fix_a(float (&S)[64], float (&F)[32], const Attn& at) {
  if (at.cmin > 0) { kill32<0>(F); if (at.cmin > 3) kill32<0>(S); }
  merge_fl(S, F, at.rowc);
}
DEVI void scale64(float (&S)[64], float n0, float n1) {
#pragma unroll
  for (int i = 0; i < 64; i++) S[i] = fmaf(S[i], SC, (i & 2) ? n1 : n0);
}
DEVI void fix_b(float (&S)[64], const Attn& at) {
  if (at.cmin > 1) { kill32<0>(S); if (at.cmin > 2) kill32<32>(S); }
}
DEVI void half_a(const float (&SA)[64], float (&SB)[64], float (&O)[8], float (&l)[4], const Attn& at, uint32_t kb, float n0, float n1) {
  uint32_t P[8][4], PL[4][4], PF[4][4];
  wgmma_fence();
  wgmma_qk128(SB, at.q[0][0], at.q[0][1], at.q[0][2], at.q[0][3], desc_sw64(kb + 256));
  wgmma_commit();
  const uint32_t v = kb + 3 * 256 + 2;
  exp8<0, true>(SA, P[0], n0, n1, l); exp8<1, true>(SA, P[1], n0, n1, l);
  pv_step<true>(O, P[0], v);         exp8<2, true>(SA, P[2], n0, n1, l);
  pv_step<false>(O, P[1], v + 64);   exp8<3, true>(SA, P[3], n0, n1, l);
  pv_step<false>(O, P[2], v + 128);  exp8<4, true>(SA, P[4], n0, n1, l);
  pv_step<false>(O, P[3], v + 192);  exp8<5, true>(SA, P[5], n0, n1, l);
  pv_merged<4>(O, P[4], PL[0], PF[0], at.rowc, kb); exp8<6, true>(SA, P[6], n0, n1, l);
  pv_merged<5>(O, P[5], PL[1], PF[1], at.rowc, kb); exp8<7, true>(SA, P[7], n0, n1, l);
  pv_merged<6>(O, P[6], PL[2], PF[2], at.rowc, kb);
  pv_merged<7>(O, P[7], PL[3], PF[3], at.rowc, kb);
  fix_b(SB, at);
}

DEVI void attention(const Ctx& c, Attn& at, int wi) {
  const uint32_t kvb = ((c.sbase & 0x3FFFF) + OFF_KV + c.wg * 4096) >> 4;
  float SA[64];
  float n0 = __uint_as_float(at.nm[0] << 16), n1 = __uint_as_float(at.nm[0] & 0xffff0000u);
  bool exact = false;
  mbar_wait(c.bars + 8 * BAR_KVFULL, 0, c.t0);
  {
    float F[32];
    qk_a(SA, F, at.q[0], kvb);
    wgmma_commit();
    wgmma_wait<0>();
    fix_a(SA, F, at);
    scale64(SA, n0, n1);
  }
  int h = 0;
#pragma unroll 1
  while (h < 4) {
    const uint32_t kb = kvb + (h & 1) * (KVBUF >> 4);
    const uint32_t kn = h == 3 ? kb : kvb + ((h & 1) ^ 1) * (KVBUF >> 4);
    float O[8], l[4] = {0.f, 0.f, 0.f, 0.f};
    float SN[64], F[32];
    {
      float SB[64];
      half_a(SA, SB, O, l, at, kb, n0, n1);
      uint32_t P[8][4];
      const uint32_t v = kb + 256 + 2;
      exp8<0>(SB, P[0], n0, n1, l); exp8<1>(SB, P[1], n0, n1, l);
      pv_step<false>(O, P[0], v);        exp8<2>(SB, P[2], n0, n1, l);
      pv_step<false>(O, P[1], v + 64);   exp8<3>(SB, P[3], n0, n1, l);
      pv_step<false>(O, P[2], v + 128);  exp8<4>(SB, P[4], n0, n1, l);
      if (h < 3) mbar_wait(c.bars + 8 * (BAR_KVFULL + ((h + 1) & 1)), (h + 1) >> 1, c.t0);
      wgmma_wait<0>();
      qk_a(SN, F, at.q[1], kn);
      wgmma_pv(O, P[3][0], P[3][1], P[3][2], P[3][3], desc_sw64(v + 192));
      wgmma_commit();
      ONCE { exp8<5>(SB, P[5], n0, n1, l); }
      pv_step<false>(O, P[4], v + 256);
      fix_a(SN, F, at);
      exp8<6>(SB, P[6], n0, n1, l);
      pv_step<false>(O, P[5], v + 320);
      scale64(SN, __uint_as_float(at.nm[1] << 16), __uint_as_float(at.nm[1] & 0xffff0000u));
      exp8<7>(SB, P[7], n0, n1, l);
      wgmma_wait<0>();
      wgmma_fence();
      wgmma_pv(O, P[6][0], P[6][1], P[6][2], P[6][3], desc_sw64(v + 384));
      wgmma_pv(O, P[7][0], P[7][1], P[7][2], P[7][3], desc_sw64(v + 448));
      wgmma_commit();
    }
    float l0 = l[0] + l[1], l1 = l[2] + l[3];
    l0 += __shfl_xor_sync(0xffffffffu, l0, 1); l1 += __shfl_xor_sync(0xffffffffu, l1, 1);
    l0 += __shfl_xor_sync(0xffffffffu, l0, 2); l1 += __shfl_xor_sync(0xffffffffu, l1, 2);
    const bool bad = !exact && !(l0 > 1e-6f && l0 < 1e18f && l1 > 1e-6f && l1 < 1e18f);
    const bool redo = wg_any(c.wg, bad);
    wgmma_wait<0>();
    if (redo) {
      float x0 = __int_as_float(0xff800000), x1 = x0;
      {
        float T[64];
        wgmma_fence();
        wgmma_qk128(T, at.q[0][0], at.q[0][1], at.q[0][2], at.q[0][3], desc_sw64(kb + 256));
        wgmma_commit();
        wgmma_wait<0>();
        fix_b(T, at);
        row_max(T, x0, x1);
      }
      float T[64], G[32];
      qk_a(T, G, at.q[0], kb);
      wgmma_commit();
      wgmma_wait<0>();
      fix_a(T, G, at);
      row_max(T, x0, x1);
      x0 = fmaxf(x0, __shfl_xor_sync(0xffffffffu, x0, 1)); x1 = fmaxf(x1, __shfl_xor_sync(0xffffffffu, x1, 1));
      x0 = fmaxf(x0, __shfl_xor_sync(0xffffffffu, x0, 2)); x1 = fmaxf(x1, __shfl_xor_sync(0xffffffffu, x1, 2));
      n0 = -x0 * SC; n1 = -x1 * SC;
      scale64(T, n0, n1);
#pragma unroll
      for (int i = 0; i < 64; i++) SA[i] = T[i];
      exact = true;
    } else {
      if (c.lane == 0) mbar_arrive(c.bars + 8 * (BAR_KVEMPTY + (h & 1)));
      const float c0 = __fdividef(at.g0, l0), c1 = __fdividef(at.g1, l1);
      const uint32_t ost = c.sbase + OFF_A + (15 % NA) * SLOT + c.wg * 8192 + h * 2048;
      const int mi = c.lane >> 3;
      const int srow = wi * 16 + (c.lane & 7) + 8 * (mi & 1);
      stsm_x4(ost + srow * 32 + (mi >> 1) * 16, pack_bf16(O[0] * c0, O[1] * c0), pack_bf16(O[2] * c1, O[3] * c1),
              pack_bf16(O[4] * c0, O[5] * c0), pack_bf16(O[6] * c1, O[7] * c1));
      fence_async_smem();
      __syncwarp();
      if (c.lane == 0) mbar_arrive(c.bars + 8 * (BAR_STG + c.wg));
      n0 = __uint_as_float(at.nm[1] << 16); n1 = __uint_as_float(at.nm[1] & 0xffff0000u);
#pragma unroll
      for (int i = 0; i < 64; i++) SA[i] = SN[i];
#pragma unroll
      for (int i = 0; i < 4; i++) { at.q[0][i] = at.q[1][i]; at.q[1][i] = at.q[2][i]; at.q[2][i] = at.q[3][i]; }
      at.nm[1] = at.nm[2]; at.nm[2] = at.nm[3];
      exact = false;
      h++;
    }
  }
}

template <int CH, int NACC>
DEVI void store_h_chunk(const float (&acc)[NACC], uint32_t base  , int lane, float s0, float s1) {
  const int mi = lane >> 3;
#pragma unroll
  for (int tp = 0; tp < 4; tp++) {
    const int t = CH * 8 + tp * 2;
    const uint32_t r0 = pack_bf16(fmaxf(acc[4 * t + 0], 0.f) * s0, fmaxf(acc[4 * t + 1], 0.f) * s0);
    const uint32_t r1 = pack_bf16(fmaxf(acc[4 * t + 2], 0.f) * s1, fmaxf(acc[4 * t + 3], 0.f) * s1);
    const uint32_t r2 = pack_bf16(fmaxf(acc[4 * t + 4], 0.f) * s0, fmaxf(acc[4 * t + 5], 0.f) * s0);
    const uint32_t r3 = pack_bf16(fmaxf(acc[4 * t + 6], 0.f) * s1, fmaxf(acc[4 * t + 7], 0.f) * s1);
    stsm_x4(base + (((tp * 2 + (mi >> 1)) ^ (lane & 7)) << 4), r0, r1, r2, r3);
  }
}

DEVI void get_gate(Attn& at, const Ctx& c, const unsigned* gflag, unsigned gtgt, const float* gp) {
  if (c.lane == 0) flag_wait(gflag, gtgt, c.t0);
  __syncwarp();
  at.g0 = ld_relaxed_f(gp); at.g1 = ld_relaxed_f(gp + 8);
}

template <int N>
DEVI void phase_q(Ctx& c, Attn& at, int warp, const unsigned* gflag, unsigned gtgt, const float* gp) {
  float acc[N / 2];
#pragma unroll
  for (int i = 0; i < N / 2; i++) acc[i] = 0.f;
  bare_groups<N>(acc, c, 0, 16);
  drain(c);
  const int lane = c.lane, mi = lane >> 3;
  const int row = warp * 16 + (lane & 7) + 8 * (mi & 1);
  const int sw = (row >> 1) & 3;
#pragma unroll
  for (int hh = 0; hh < 4; hh++) {
    const uint32_t base = c.sbase + OFF_KV + hh * 8192 + row * 64;
#pragma unroll
    for (int kv = 0; kv < 2; kv++) {
      const int t = 8 + kv * 8 + 2 * hh;
      stsm_x4(base + (((kv * 2 + (mi >> 1)) ^ sw) << 4),
              pack_bf16(acc[4 * t + 0], acc[4 * t + 1]), pack_bf16(acc[4 * t + 2], acc[4 * t + 3]),
              pack_bf16(acc[4 * t + 4], acc[4 * t + 5]), pack_bf16(acc[4 * t + 6], acc[4 * t + 7]));
    }
  }
  fence_async_smem();
  __syncwarp();
  if (lane == 0) mbar_arrive(c.bars + 8 * (BAR_STG + c.wg));
  if constexpr (N == 256) {
    get_gate(at, c, gflag, gtgt, gp);
    store_h_chunk<3>(acc, c.sbase + OFF_KV + 32768 + row * 128, lane, 1.f - at.g0, 1.f - at.g1);
    fence_async_smem();
    __syncwarp();
    if (lane == 0) mbar_arrive(c.bars + 8 * (BAR_STE + c.wg));
  }
#pragma unroll
  for (int hh = 0; hh < 4; hh++) {
#pragma unroll
    for (int i = 0; i < 4; i++) at.q[hh][i] = pack_bf16(acc[8 * hh + 2 * i], acc[8 * hh + 2 * i + 1]);
    const float* q = &acc[8 * hh];
    const float* k = &acc[32 + 8 * hh];
    float d0 = q[0] * k[0] + q[1] * k[1] + q[4] * k[4] + q[5] * k[5], d1 = q[2] * k[2] + q[3] * k[3] + q[6] * k[6] + q[7] * k[7];
    d0 += __shfl_xor_sync(0xffffffffu, d0, 1); d1 += __shfl_xor_sync(0xffffffffu, d1, 1);
    d0 += __shfl_xor_sync(0xffffffffu, d0, 2); d1 += __shfl_xor_sync(0xffffffffu, d1, 2);
    at.nm[hh] = pack_bf16(-d0 * SC, -d1 * SC);
  }
}

DEVI void first_loads(const Params& P, uint32_t sbase, int e, int j, int rb) {
  const uint32_t bars = sbase + OFF_BAR, fb = bars + 8 * (BAR_FULLB + e), fa = bars + 8 * (BAR_FULLA + e);
  mbar_expect_tx(fa, 16384);
  mbar_expect_tx(fb, (j & 1) ? 12288 : 16384);
  if (e == 0) tma_load_2d(sbase + OFF_A, &P.tmX, 0, rb * 128, fa);
#pragma unroll
  for (int r = 0; r < 2; r++) {
    tma_load_3d(sbase + OFF_B + e * SLOT + r * 8192, &P.tmWqkv, 64 * j, e * 32 + r * 16, 0, fb);
    if (!(j & 1)) tma_load_3d(sbase + OFF_B + e * SLOT + r * 8192 + 6144, &P.tmW1a, 0, e * 32 + r * 16, 24 + (j >> 1), fb);
  }
  if (e == 1) tma_load_2d(sbase + OFF_A + SLOT, &P.tmX, 64, rb * 128, fa);
}

__global__ void __cluster_dims__(2, 1, 1) __launch_bounds__(384, 1) fused_kernel(const __grid_constant__ Params P) {
  extern __shared__ uint8_t smem_raw[];
  const uint32_t sbase = (smem_u32(smem_raw) + 1023u) & ~1023u;
  const uint32_t bars = sbase + OFF_BAR;
  const int tid = threadIdx.x, warp = tid >> 5, lane = tid & 31;
  const uint32_t rank = blockIdx.x & 1, peer = rank ^ 1;
  const int j = (blockIdx.x >> 1) & 7, rb = ((blockIdx.x >> 4) << 1) | rank;
  const uint32_t t0 = clk32();

  const int typeB = j & 1;
  if (tid == 256) {
    for (int s = 0; s < NA; s++) mbar_init(bars + 8 * (BAR_FULLA + s), 1);
    for (int s = 0; s < NB; s++) mbar_init(bars + 8 * (BAR_FULLB + s), 1);
    fence_async_smem();
    first_loads(P, sbase, 0, j, rb);
  } else if (tid < 6) {
    asm volatile("prefetch.tensormap [%0];" ::"l"(&P.tmW1b + tid) : "memory");
  } else if (tid == 288) {
    for (int s = 0; s < NA; s++) mbar_init(bars + 8 * (BAR_EMPTYA + s), 10);
    for (int s = 0; s < NB; s++) mbar_init(bars + 8 * (BAR_EMPTYB + s), 16);
  } else if (tid == 320) {
    for (int s = 0; s < 2; s++) { mbar_init(bars + 8 * (BAR_KVFULL + s), 1); mbar_init(bars + 8 * (BAR_KVEMPTY + s), 8); mbar_init(bars + 8 * (BAR_STG + s), 4); mbar_init(bars + 8 * (BAR_STE + s), 4); }
    mbar_init(bars + 8 * BAR_PIN, 1); mbar_init(bars + 8 * BAR_GATE, 1); mbar_init(bars + 8 * (BAR_GATE + 1), 1);
  }
  if (tid >= 256 && lane == 0) asm volatile("fence.mbarrier_init.release.cluster;" ::: "memory");
  const unsigned ep1 = ld_relaxed(&g_epoch) + 1;
  __syncwarp();
  cluster_arrive();
  if (tid == 256) first_loads(P, sbase, 1, j, rb);

  const int on = 12 + 4 * typeB;

  if (warp < 8) {
    asm volatile("setmaxnreg.inc.sync.aligned.u32 232;");
    cluster_wait();
    const int wg = __shfl_sync(0xffffffffu, warp >> 2, 0), wi = warp & 3;
    Ctx c{sbase, bars, peer, t0, ((sbase & 0x3FFFF) + OFF_A + wg * 8192) >> 4, ((sbase & 0x3FFFF) + OFF_B) >> 4, wg, lane, 0, 0, 0u, 0u, 32 + on + 4 - NB, -1, -1};
    Attn at;
    at.cmin = 4 - 2 * rb - wg;
    at.rowc = wi * 16 + (lane >> 2) - (lane & 3) * 2;
    const int row0 = rb * 128 + warp * 16 + (lane >> 2);
    if (tid == 0) TR(0);
    if (typeB) phase_q<192>(c, at, warp, &g_flag_g[rb * FS], ep1 * 16, &g_gate[row0]);
    else phase_q<256>(c, at, warp, &g_flag_g[rb * FS], ep1 * 16, &g_gate[row0]);
    if (tid == 0) TR(2);
    {
      float acc[96];
#pragma unroll
      for (int i = 0; i < 96; i++) acc[i] = 0.f;
      bare_groups<192>(acc, c, 0, 8);
      if (typeB) get_gate(at, c, &g_flag_g[rb * FS], ep1 * 16, &g_gate[row0]);
      bare_groups<192>(acc, c, 8, 16);
      drain(c);
      if (tid == 0) TR(1);
      const uint32_t rowoff = (warp * 16 + (lane & 7) + 8 * ((lane >> 3) & 1)) * 128;
      const float s0 = 1.f - at.g0, s1 = 1.f - at.g1;
      constexpr int e0 = 16 % NA, e1 = 17 % NA, e2 = 18 % NA;
      mbar_wait(bars + 8 * (BAR_FULLA + e0), (16 / NA) & 1, t0);
      store_h_chunk<0>(acc, sbase + OFF_A + e0 * SLOT + rowoff, lane, s0, s1);
      mbar_wait(bars + 8 * (BAR_FULLA + e1), (17 / NA) & 1, t0);
      store_h_chunk<1>(acc, sbase + OFF_A + e1 * SLOT + rowoff, lane, s0, s1);
      mbar_wait(bars + 8 * (BAR_FULLA + e2), (18 / NA) & 1, t0);
      store_h_chunk<2>(acc, sbase + OFF_A + e2 * SLOT + rowoff, lane, s0, s1);
    }
    fence_async_smem();
    wg_bar(wg);
    if (lane == 0) mbar_arrive(bars + 8 * (BAR_STG + wg));
    if (tid == 0) TR(4);
    attention(c, at, wi);
    if (tid == 0) TR(3);
    float own[32];
    {
      float acc[64];
#pragma unroll
      for (int i = 0; i < 64; i++) acc[i] = 0.f;
      bare_groups<128>(acc, c, 0, on);
      drain(c);
      if (tid == 0) TR(5);
      mbar_wait(bars + 8 * (BAR_KVEMPTY + 0), 1, t0);
      const uint32_t pst = sbase + OFF_KV + wg * 8192 + (tid & 127) * 16;
#pragma unroll
      for (int i = 0; i < 4; i++) {
        uint32_t r[4];
#pragma unroll
        for (int k = 0; k < 4; k++) {
          const int idx = 8 * i + 2 * k;
          const float lo = typeB ? acc[idx] : acc[32 + idx], hi = typeB ? acc[idx + 1] : acc[32 + idx + 1];
          r[k] = pack_bf16(lo, hi);
        }
        sts128(pst + i * 2048, r[0], r[1], r[2], r[3]);
      }
#pragma unroll
      for (int i = 0; i < 32; i++) own[i] = typeB ? acc[32 + i] : acc[i];
      fence_async_smem();
      __syncwarp();
      if (lane == 0) mbar_arrive(bars + 8 * (BAR_STG + wg));
    }
    for (int g = 0; g < 8; g++) {
      const uint32_t a16 = c.a16 + c.ai * (SLOT >> 4);
      const uint32_t b16 = c.b16 + c.bi * (SLOT >> 4) + (g & 1) * 512;
      mbar_wait(bars + 8 * (BAR_FULLB + c.bi), c.bph, t0);
      mbar_wait(bars + 8 * (BAR_FULLA + c.ai), c.aph, t0);
      wgmma_fence();
#pragma unroll
      for (int s = 0; s < 4; s++) wgmma_ss<64>(own, desc_sw128<16>(a16 + s * 2), desc_sw128<2048>(b16 + s * 128));
      wgmma_commit();
      wgmma_wait<1>();
      release_prev(c);
      c.pa = c.ai; c.pb = -1;
      if (++c.ai == NA) { c.ai = 0; c.aph ^= 1; }
      if (g & 1) { if (++c.bi == NB) { c.bi = 0; c.bph ^= 1; } }
    }
    wgmma_wait<0>();
    if (tid == 0) TR(6);
    mbar_wait(bars + 8 * BAR_PIN, 0, t0);
    if (tid == 0) TR(7);
    {
      const uint32_t pin = sbase + OFF_KV + KVBUF + wg * 8192 + (tid & 127) * 16;
      __nv_bfloat16* o = P.out + (size_t)row0 * DM + j * 64 + (lane & 3) * 2;
#pragma unroll
      for (int i = 0; i < 4; i++) {
        const uint4 v = lds128(pin + i * 2048);
        const uint32_t r[4] = {v.x, v.y, v.z, v.w};
#pragma unroll
        for (int k = 0; k < 4; k++) {
          const int idx = 8 * i + 2 * k;
          const float lo = own[idx] + __uint_as_float(r[k] << 16), hi = own[idx + 1] + __uint_as_float(r[k] & 0xffff0000u);
          *(uint32_t*)(o + (k & 1) * 8 * DM + (2 * i + (k >> 1)) * 8) = pack_bf16(lo, hi);
        }
      }
    }
    if (tid == 0) TR(8);
  } else {
    asm volatile("setmaxnreg.dec.sync.aligned.u32 40;");
    if (warp == 8) {
      __syncwarp();
      cluster_wait();
      if (lane == 0) {
        int bi = 2; uint32_t bph = 1;
        const int nb = 32 + on + 4;
        for (int eb = 2; eb < nb; eb++) {
          if (eb == 4 || eb == 6) {
            for (int ea = eb - 2 - (eb == 6 ? 1 : 0); ea < (eb == 4 ? 3 : NA); ea++) {
              mbar_expect_tx(bars + 8 * (BAR_FULLA + ea), 16384);
              tma_load_2d(sbase + OFF_A + ea * SLOT, &P.tmX, ea * 64, rb * 128, bars + 8 * (BAR_FULLA + ea));
            }
          }
          const uint32_t fb = bars + 8 * (BAR_FULLB + bi), dst = sbase + OFF_B + bi * SLOT + rank * 8192;
          mbar_wait(bars + 8 * (BAR_EMPTYB + bi), bph, t0);
          if (eb < 16) {
            mbar_expect_tx(fb, typeB ? 12288 : 16384);
            tma_load_3d_mc(dst, &P.tmWqkv, 64 * j, eb * 32 + rank * 16, 0, fb);
            if (!typeB) tma_load_3d_mc(dst + 6144, &P.tmW1a, 0, eb * 32 + rank * 16, 24 + (j >> 1), fb);
          }
          else if (eb < 32) { mbar_expect_tx(fb, 12288); tma_load_3d_mc(dst, &P.tmW1b, 0, (eb - 16) * 32 + rank * 16, 3 * j, fb); }
          else if (eb < 32 + on) { int ow; const int ch = oh_chunk(j, eb - 32, ow); mbar_expect_tx(fb, 16384); tma_load_3d_mc(dst, &P.tmW2, 0, ch * 64 + rank * 32, (j >> 1) * 2, fb); }
          else { mbar_expect_tx(fb, 16384); tma_load_4d_mc(dst, &P.tmWo, 64 * j, 0, eb - 32 - on, rank * 4, fb); }
          if (++bi == NB) { bi = 0; bph ^= 1; }
          if (eb == PFAT) {
            const int b = blockIdx.x;
            l2_prefetch((const uint8_t*)P.w1 + b * 14336, 14336);
            l2_prefetch((const uint8_t*)P.w2 + b * 14336, 14336);
            l2_prefetch((const uint8_t*)P.wo + b * 4096, 4096);
          }
        }
      }
    } else if (warp == 9) {
      cluster_wait();
      if (lane == 0) {
        for (int ea = 0; ea < NA; ea++) mbar_arrive_n(bars + 8 * (BAR_EMPTYA + ea), 2);
        int ai = 0; uint32_t aph = 0;
        const int na = 16 + on + 8;
        unsigned ready = 0;
        for (int ea = NA; ea < na; ea++) {
          const uint32_t fb = bars + 8 * (BAR_FULLA + ai), dst = sbase + OFF_A + ai * SLOT;
          int ch = ea & 7, need = -1;
          if (ea >= 16 + on) { need = 8 + ea - 16 - on; ch = 20 + need; }
          else if (ea >= 19) ch = oh_chunk(j, ea - 16, need);
          if (need >= 0 && !((ready >> need) & 1)) {
            const unsigned* fp = need < 8 ? &g_flag_h[rb * 8 * FS] : need < 16 ? &g_flag_o[rb * 8 * FS] : &g_flag_e[rb * 8 * FS];
            const unsigned tgt = (need & 8) ? ep1 * 8 : ep1 * 2;
            do {
              unsigned v[8];
#pragma unroll
              for (int i = 0; i < 8; i++) v[i] = ld_relaxed(fp + i * FS);
#pragma unroll
              for (int i = 0; i < 8; i++) if ((int)(v[i] - tgt) >= 0) ready |= 1u << (i + (need & 24));
            } while (!((ready >> need) & 1) && clk32() - t0 < TIMEOUT);
            fence_async_global();
          }
          mbar_wait(bars + 8 * (BAR_EMPTYA + ai), aph, t0);
          if (ea >= 16 && ea < 19) mbar_arrive(fb);
          else {
            if (ea != 15) mbar_arrive_n(bars + 8 * (BAR_EMPTYA + ai), 2);
            mbar_expect_tx(fb, 16384);
            tma_load_2d(dst, ea < 16 ? &P.tmX : &P.tmHO, ch * 64, rb * 128, fb);
          }
          TR(24 + ea);
          if (++ai == NA) { ai = 0; aph ^= 1; }
        }
      }
    } else {
      const int wg = warp - 10;
      cluster_wait();
      {
        const int rowg = rb * 128 + j * 16 + wg * 8;
        const uint32_t xs = sbase + OFF_KV + 32768 + wg * 8192;
        if (lane == 0) {
          mbar_wait(bars + 8 * (BAR_FULLB + 1), 0, t0);
          mbar_expect_tx(bars + 8 * (BAR_GATE + wg), 8192);
          bulk_load(xs, P.x + (size_t)rowg * DM, 8192, bars + 8 * (BAR_GATE + wg));
        }
        const uint4* gw = (const uint4*)P.gate_w;
        const uint4 w0 = __ldg(gw + lane), w1 = __ldg(gw + 32 + lane);
        const uint32_t wa[8] = {w0.x, w0.y, w0.z, w0.w, w1.x, w1.y, w1.z, w1.w};
        mbar_wait(bars + 8 * (BAR_GATE + wg), 0, t0);
        float zz = 0.f;
#pragma unroll 1
        for (int i = 0; i < 8; i++) {
          const uint4 x0 = lds128(xs + i * 1024 + lane * 16), x1 = lds128(xs + i * 1024 + 512 + lane * 16);
          const uint32_t xa[8] = {x0.x, x0.y, x0.z, x0.w, x1.x, x1.y, x1.z, x1.w};
          float z = 0.f;
#pragma unroll
          for (int e = 0; e < 8; e++) {
            z = fmaf(__uint_as_float(xa[e] << 16), __uint_as_float(wa[e] << 16), z);
            z = fmaf(__uint_as_float(xa[e] & 0xffff0000u), __uint_as_float(wa[e] & 0xffff0000u), z);
          }
#pragma unroll
          for (int o = 16; o > 0; o >>= 1) z += __shfl_xor_sync(0xffffffffu, z, o);
          if (lane == i) zz = z;
        }
        if (lane < 8) asm volatile("st.shared.f32 [%0], %1;" ::"r"(sbase + OFF_GST + wg * 32 + lane * 4), "f"(1.f / (1.f + __expf(-zz))) : "memory");
        fence_async_smem();
        __syncwarp();
        if (lane == 0) {
          bulk_store(&g_gate[rowg], sbase + OFF_GST + wg * 32, 32);
          bulk_commit(); bulk_wait_all();
          flag_add(&g_flag_g[rb * FS]);
          if (wg == 0) TR(10);
        }
      }
      if (lane == 0) {
        const uint32_t stg = bars + 8 * (BAR_STG + wg);
        mbar_wait(stg, 0, t0);
        for (int hh = 0; hh < 4; hh++)
          bulk_store(g_kv + ((size_t)(4 * j + hh) * SEQ + rb * 128 + wg * 64) * 64, sbase + OFF_KV + hh * 8192 + wg * 4096, 4096);
        bulk_commit(); bulk_wait_all();
        flag_add(&g_flag_kv[(rb * 8 + j) * FS]);
        if (wg == 0) TR(21);
        if (!typeB) {
          mbar_wait(bars + 8 * (BAR_STE + wg), 0, t0);
          tma_store_2d(&P.tmHOs, (24 + (j >> 1)) * 64, rb * 128 + wg * 64, sbase + OFF_KV + 32768 + wg * 8192);
          bulk_commit(); bulk_wait_all();
          flag_add(&g_flag_e[(rb * 8 + j) * FS]);
          if (wg == 1) flag_wait(&g_flag_e[(rb * 8 + j) * FS], ep1 * 2, t0);
        }
        const int nblk = rb >= 2 ? 3 : rb + 1;
        const uint32_t kvbytes = nblk * 8192;
        const uint8_t* kvsrc = g_kv + ((size_t)(4 * j) * SEQ + (rb + 1 - nblk) * 128) * 64;
        const uint32_t kvdst = sbase + OFF_KV + wg * KVBUF + (3 - nblk) * 8192;
        {
          const unsigned* f0 = &g_flag_kv[(rb * 8 + j) * FS];
          const unsigned* f1 = rb >= 1 ? f0 - 8 * FS : f0;
          const unsigned* f2 = rb >= 2 ? f0 - 16 * FS : f0;
          unsigned v0, v1, v2;
          do { v0 = ld_relaxed(f0); v1 = ld_relaxed(f1); v2 = ld_relaxed(f2); }
          while (((int)(v0 - ep1 * 2) < 0 || (int)(v1 - ep1 * 2) < 0 || (int)(v2 - ep1 * 2) < 0) && clk32() - t0 < TIMEOUT);
        }
        if (wg == 0) TR(11);
        fence_async_global();
        mbar_expect_tx(bars + 8 * (BAR_KVFULL + wg), kvbytes);
        bulk_load(kvdst, kvsrc + (size_t)wg * SEQ * 64, kvbytes, bars + 8 * (BAR_KVFULL + wg));
        for (int ev = 1; ev < 7; ev++) {
          mbar_wait(stg, ev & 1, t0);
          if (ev == 1) {
            for (int i = 0; i < 3; i++)
              tma_store_2d(&P.tmHOs, (3 * j + i) * 64, rb * 128 + wg * 64, sbase + OFF_A + ((16 + i) % NA) * SLOT + wg * 8192);
            bulk_commit(); bulk_wait_all();
            flag_add(&g_flag_h[(rb * 8 + j) * FS]);
            for (int i = 0; i < 3; i++) mbar_arrive(bars + 8 * (BAR_EMPTYA + (16 + i) % NA));
            if (wg == 0) TR(22);
            if (wg == 0) {
              const unsigned old = atomicAdd(&g_done, 1u);
              if (old == gridDim.x - 1) { g_done = 0; *(volatile unsigned*)&g_epoch = ep1; }
            }
          } else if (ev == 6) {
            bulk_store(g_part + (size_t)(rb * 8 + (j ^ 1)) * 16384 + wg * 8192, sbase + OFF_KV + wg * 8192, 8192);
            bulk_commit(); bulk_wait_all();
            flag_add(&g_flag_p[(rb * 8 + (j ^ 1)) * FS]);
            if (wg == 0) TR(23);
            if (wg == 1) {
              mbar_wait(bars + 8 * (BAR_KVEMPTY + 1), 1, t0);
              flag_wait(&g_flag_p[(rb * 8 + j) * FS], ep1 * 2, t0);
              fence_async_global();
              mbar_expect_tx(bars + 8 * BAR_PIN, 16384);
              bulk_load(sbase + OFF_KV + KVBUF, g_part + (size_t)(rb * 8 + j) * 16384, 16384, bars + 8 * BAR_PIN);
            }
          } else {
            const int hh = ev - 2;
            tma_store_2d(&P.tmOs, DFF + hh * 128 + j * 16, rb * 128 + wg * 64, sbase + OFF_A + (15 % NA) * SLOT + wg * 8192 + hh * 2048);
            bulk_commit();
            if (hh == wg) {
              mbar_wait(bars + 8 * (BAR_KVEMPTY + wg), 0, t0);
              mbar_expect_tx(bars + 8 * (BAR_KVFULL + wg), kvbytes);
              bulk_load(kvdst, kvsrc + (size_t)(wg + 2) * SEQ * 64, kvbytes, bars + 8 * (BAR_KVFULL + wg));
            }
            bulk_wait_all();
            flag_add(&g_flag_o[(rb * 8 + hh * 2 + (j >> 2)) * FS]);
            if (hh == 3) mbar_arrive(bars + 8 * (BAR_EMPTYA + 15 % NA));
            if (wg == 0) TR(12 + hh);
          }
        }
      }
    }
  }
}

typedef CUresult (*EncodeFn)(CUtensorMap*, CUtensorMapDataType, cuuint32_t, void*, const cuuint64_t*, const cuuint64_t*, const cuuint32_t*,
                             const cuuint32_t*, CUtensorMapInterleave, CUtensorMapSwizzle, CUtensorMapL2promotion, CUtensorMapFloatOOBfill);

void make_map(EncodeFn enc, CUtensorMap* m, const void* ptr, int rank, const cuuint64_t* dims, const cuuint64_t* strides, const cuuint32_t* box,
              CUtensorMapSwizzle sw = CU_TENSOR_MAP_SWIZZLE_128B) {
  cuuint32_t es[4] = {1, 1, 1, 1};
  enc(m, CU_TENSOR_MAP_DATA_TYPE_BFLOAT16, rank, const_cast<void*>(ptr), dims, strides, box, es, CU_TENSOR_MAP_INTERLEAVE_NONE, sw,
      CU_TENSOR_MAP_L2_PROMOTION_L2_256B, CU_TENSOR_MAP_FLOAT_OOB_FILL_NONE);
}

}

extern "C" void kernel_launch(void* const* d_in, const int* in_sizes, int n_in, void* d_out, int out_size) {
  (void)in_sizes; (void)n_in; (void)out_size;
  static EncodeFn enc = nullptr;
  static void* ho_ptr = nullptr;
  if (!enc) {
    void* fn = nullptr; cudaDriverEntryPointQueryResult st;
    cudaGetDriverEntryPoint("cuTensorMapEncodeTiled", &fn, cudaEnableDefault, &st);
    enc = (EncodeFn)fn;
    cudaGetSymbolAddress(&ho_ptr, g_ho);
    cudaFuncSetAttribute(fused_kernel, cudaFuncAttributeMaxDynamicSharedMemorySize, SMEM_BYTES);
  }
  const __nv_bfloat16* x = (const __nv_bfloat16*)d_in[0];
  const __nv_bfloat16* wqkv = (const __nv_bfloat16*)d_in[1];
  const __nv_bfloat16* wo = (const __nv_bfloat16*)d_in[2];
  const __nv_bfloat16* w1 = (const __nv_bfloat16*)d_in[4];
  const __nv_bfloat16* w2 = (const __nv_bfloat16*)d_in[5];
  const __nv_bfloat16* gate_w = (const __nv_bfloat16*)d_in[6];
  Params P;
  { cuuint64_t d[2] = {DM, SEQ}, s[1] = {DM * 2}; cuuint32_t b[2] = {64, 128}; make_map(enc, &P.tmX, x, 2, d, s, b); }
  { cuuint64_t d[3] = {512, 512, 3}, s[2] = {1536 * 2, 512 * 2}; cuuint32_t b[3] = {64, 16, 3}; make_map(enc, &P.tmWqkv, wqkv, 3, d, s, b); }
  { cuuint64_t d[3] = {64, 512, 28}, s[2] = {DFF * 2, 128}; cuuint32_t b[3] = {64, 16, 1}; make_map(enc, &P.tmW1a, w1, 3, d, s, b);
    b[2] = 3; make_map(enc, &P.tmW1b, w1, 3, d, s, b); }
  { cuuint64_t d[3] = {64, DFF, 8}, s[2] = {DM * 2, 128}; cuuint32_t b[3] = {64, 32, 2}; make_map(enc, &P.tmW2, w2, 3, d, s, b); }
  { cuuint64_t d[4] = {DM, 16, 4, 8}, s[3] = {DM * 2, 16 * DM * 2, 64 * DM * 2}; cuuint32_t b[4] = {64, 16, 1, 4}; make_map(enc, &P.tmWo, wo, 4, d, s, b); }
  { cuuint64_t d[2] = {KHO, SEQ}, s[1] = {KHO * 2}; cuuint32_t b[2] = {64, 128}; make_map(enc, &P.tmHO, ho_ptr, 2, d, s, b);
    b[1] = 64; make_map(enc, &P.tmHOs, ho_ptr, 2, d, s, b);
    b[0] = 16; make_map(enc, &P.tmOs, ho_ptr, 2, d, s, b, CU_TENSOR_MAP_SWIZZLE_NONE); }
  P.x = x; P.gate_w = gate_w; P.w1 = w1; P.w2 = w2; P.wo = wo; P.out = (__nv_bfloat16*)d_out;
  fused_kernel<<<128, 384, SMEM_BYTES>>>(P);
}
```

```cpp
#include <cuda_runtime.h>
#include <cuda_bf16.h>
#include <cuda.h>
#include <stdint.h>

#define DEVI __device__ __forceinline__

namespace {

constexpr int SEQ = 2048, DM = 512, DFF = 1792, KHO = 2304;
constexpr int NA = 5, NB = 6, SLOT = 16384, KVBUF = 24576;
constexpr int OFF_A = 0, OFF_B = NA * SLOT, OFF_KV = OFF_B + NB * SLOT, OFF_BAR = OFF_KV + 2 * KVBUF;
constexpr int OFF_GST = OFF_BAR + 512;
constexpr int SMEM_BYTES = OFF_BAR + 1024 + 1024;
constexpr uint32_t TIMEOUT = 1u << 28;
#define WAIT_HINT_NS 20000u
#define PFAT 8
constexpr int FS = 8;

constexpr int BAR_FULLA = 0, BAR_EMPTYA = BAR_FULLA + NA, BAR_FULLB = BAR_EMPTYA + NA, BAR_EMPTYB = BAR_FULLB + NB,
              BAR_KVFULL = BAR_EMPTYB + NB, BAR_KVEMPTY = BAR_KVFULL + 2, BAR_STG = BAR_KVEMPTY + 2, BAR_PIN = BAR_STG + 2, BAR_GATE = BAR_PIN + 1, BAR_STE = BAR_GATE + 2;

__device__ __align__(1024) uint8_t g_kv[32 * SEQ * 64];
__device__ __align__(1024) __nv_bfloat16 g_ho[SEQ * KHO];
__device__ __align__(1024) uint8_t g_part[128 * 16384];
__device__ __align__(128) float g_gate[SEQ];
__device__ unsigned g_flag_kv[128 * FS], g_flag_h[128 * FS], g_flag_o[128 * FS], g_flag_g[16 * FS], g_flag_p[128 * FS], g_flag_e[128 * FS];
__device__ unsigned g_epoch, g_done;
#define TR(i) do {} while (0)

struct Params {
  CUtensorMap tmX, tmWqkv, tmW1a, tmW1b, tmW2, tmWo, tmHO, tmHOs, tmOs;
  const __nv_bfloat16* x;
  const __nv_bfloat16* gate_w;
  const __nv_bfloat16* w1;
  const __nv_bfloat16* w2;
  const __nv_bfloat16* wo;
  __nv_bfloat16* out;
};

DEVI uint32_t smem_u32(const void* p) { return (uint32_t)__cvta_generic_to_shared(p); }
DEVI uint32_t clk32() { uint32_t c; asm volatile("mov.u32 %0, %%clock;" : "=r"(c)); return c; }
DEVI void mbar_init(uint32_t bar, uint32_t cnt) { asm volatile("mbarrier.init.shared::cta.b64 [%0], %1;" ::"r"(bar), "r"(cnt)); }
DEVI void mbar_expect_tx(uint32_t bar, uint32_t bytes) { asm volatile("mbarrier.arrive.expect_tx.shared::cta.b64 _, [%0], %1;" ::"r"(bar), "r"(bytes) : "memory"); }
DEVI void mbar_arrive(uint32_t bar) { asm volatile("mbarrier.arrive.shared::cta.b64 _, [%0];" ::"r"(bar) : "memory"); }
DEVI void mbar_arrive_n(uint32_t bar, uint32_t n) { asm volatile("mbarrier.arrive.shared::cta.b64 _, [%0], %1;" ::"r"(bar), "r"(n) : "memory"); }
DEVI void mbar_arrive_cluster(uint32_t bar, uint32_t cta) {
  asm volatile("{ .reg .b32 ra; mapa.shared::cluster.u32 ra, %0, %1; mbarrier.arrive.shared::cluster.b64 _, [ra]; }" ::"r"(bar), "r"(cta) : "memory");
}
DEVI void mbar_wait(uint32_t bar, uint32_t parity, uint32_t t0) {
  asm volatile("{ .reg .pred p; .reg .u32 c;\n"
               "mbarrier.try_wait.parity.shared::cta.b64 p, [%0], %1;\n"
               "@p bra DONE_%=;\n"
               "WAIT_%=:\n"
               "mbarrier.try_wait.parity.shared::cta.b64 p, [%0], %1, %4;\n"
               "@p bra DONE_%=;\n"
               "mov.u32 c, %%clock; sub.u32 c, c, %2; setp.lt.u32 p, c, %3;\n"
               "@p bra WAIT_%=;\n"
               "DONE_%=: }" ::"r"(bar), "r"(parity), "r"(t0), "n"(TIMEOUT), "r"(WAIT_HINT_NS) : "memory");
}
DEVI unsigned ld_relaxed(const unsigned* p) { unsigned v; asm volatile("ld.relaxed.gpu.global.u32 %0, [%1];" : "=r"(v) : "l"(p) : "memory"); return v; }
DEVI float ld_relaxed_f(const float* p) { float v; asm volatile("ld.relaxed.gpu.global.f32 %0, [%1];" : "=f"(v) : "l"(p) : "memory"); return v; }
DEVI void flag_wait(const unsigned* p, unsigned target, uint32_t t0) {
  while ((int)(ld_relaxed(p) - target) < 0) { if (clk32() - t0 > TIMEOUT) break; }
}
DEVI void flag_add(unsigned* p) { asm volatile("red.relaxed.gpu.global.add.u32 [%0], 1;" ::"l"(p) : "memory"); }
DEVI void fence_async_smem() { asm volatile("fence.proxy.async.shared::cta;" ::: "memory"); }
DEVI void fence_async_global() { asm volatile("fence.proxy.async.global;" ::: "memory"); }
DEVI void tma_load_2d(uint32_t dst, const CUtensorMap* m, int c0, int c1, uint32_t bar) {
  asm volatile("cp.async.bulk.tensor.2d.shared::cluster.global.mbarrier::complete_tx::bytes [%0], [%1, {%3, %4}], [%2];" ::"r"(dst), "l"(m), "r"(bar), "r"(c0), "r"(c1) : "memory");
}
DEVI void tma_load_3d(uint32_t dst, const CUtensorMap* m, int c0, int c1, int c2, uint32_t bar) {
  asm volatile("cp.async.bulk.tensor.3d.shared::cluster.global.mbarrier::complete_tx::bytes [%0], [%1, {%3, %4, %5}], [%2];"
               ::"r"(dst), "l"(m), "r"(bar), "r"(c0), "r"(c1), "r"(c2) : "memory");
}
DEVI void tma_load_3d_mc(uint32_t dst, const CUtensorMap* m, int c0, int c1, int c2, uint32_t bar) {
  asm volatile("cp.async.bulk.tensor.3d.shared::cluster.global.mbarrier::complete_tx::bytes.multicast::cluster [%0], [%1, {%3, %4, %5}], [%2], %6;"
               ::"r"(dst), "l"(m), "r"(bar), "r"(c0), "r"(c1), "r"(c2), "h"((uint16_t)3) : "memory");
}
DEVI void tma_load_4d_mc(uint32_t dst, const CUtensorMap* m, int c0, int c1, int c2, int c3, uint32_t bar) {
  asm volatile("cp.async.bulk.tensor.4d.shared::cluster.global.mbarrier::complete_tx::bytes.multicast::cluster [%0], [%1, {%3, %4, %5, %6}], [%2], %7;"
               ::"r"(dst), "l"(m), "r"(bar), "r"(c0), "r"(c1), "r"(c2), "r"(c3), "h"((uint16_t)3) : "memory");
}
DEVI void tma_store_2d(const CUtensorMap* m, int c0, int c1, uint32_t src) {
  asm volatile("cp.async.bulk.tensor.2d.global.shared::cta.bulk_group [%0, {%1, %2}], [%3];" ::"l"(m), "r"(c0), "r"(c1), "r"(src) : "memory");
}
DEVI void bulk_store(void* dst, uint32_t src, uint32_t bytes) {
  asm volatile("cp.async.bulk.global.shared::cta.bulk_group [%0], [%1], %2;" ::"l"(dst), "r"(src), "r"(bytes) : "memory");
}
DEVI void bulk_load(uint32_t dst, const void* src, uint32_t bytes, uint32_t bar) {
  asm volatile("cp.async.bulk.shared::cluster.global.mbarrier::complete_tx::bytes [%0], [%1], %2, [%3];" ::"r"(dst), "l"(src), "r"(bytes), "r"(bar) : "memory");
}
DEVI void bulk_commit() { asm volatile("cp.async.bulk.commit_group;" ::: "memory"); }
DEVI void bulk_wait_all() { asm volatile("cp.async.bulk.wait_group 0;" ::: "memory"); }
DEVI void l2_prefetch(const void* p, uint32_t bytes) { asm volatile("cp.async.bulk.prefetch.L2.global [%0], %1;" ::"l"(p), "r"(bytes) : "memory"); }
DEVI void cluster_arrive() { asm volatile("barrier.cluster.arrive.relaxed.aligned;" ::: "memory"); }
DEVI void cluster_wait() { asm volatile("barrier.cluster.wait.aligned;" ::: "memory"); }
template <int ID> DEVI void named_bar(int n) { asm volatile("bar.sync %0, %1;" ::"n"(ID), "r"(n) : "memory"); }
DEVI void wg_bar(int wg) { if (wg == 0) named_bar<1>(128); else named_bar<2>(128); }
DEVI void wgmma_fence() { asm volatile("wgmma.fence.sync.aligned;" ::: "memory"); }
DEVI void wgmma_commit() { asm volatile("wgmma.commit_group.sync.aligned;" ::: "memory"); }
template <int N> DEVI void wgmma_wait() { asm volatile("wgmma.wait_group.sync.aligned %0;" ::"n"(N) : "memory"); }
template <uint32_t LBO> DEVI uint64_t desc_sw128(uint32_t a16) {
  return ((uint64_t)(0x40000000u | (1024 >> 4)) << 32) | (a16 + ((LBO >> 4) << 16));
}
DEVI uint64_t desc_sw64(uint32_t a16) {
  return ((uint64_t)(0x80000000u | (512 >> 4)) << 32) | (a16 + ((512 >> 4) << 16));
}
DEVI uint32_t pack_bf16(float lo, float hi) { uint32_t r; asm("cvt.rn.bf16x2.f32 %0, %1, %2;" : "=r"(r) : "f"(hi), "f"(lo)); return r; }
DEVI void stsm_x4(uint32_t addr, uint32_t r0, uint32_t r1, uint32_t r2, uint32_t r3) {
  asm volatile("stmatrix.sync.aligned.m8n8.x4.shared.b16 [%0], {%1, %2, %3, %4};" ::"r"(addr), "r"(r0), "r"(r1), "r"(r2), "r"(r3) : "memory");
}
DEVI void sts128(uint32_t addr, uint32_t r0, uint32_t r1, uint32_t r2, uint32_t r3) {
  asm volatile("st.shared.v4.b32 [%0], {%1, %2, %3, %4};" ::"r"(addr), "r"(r0), "r"(r1), "r"(r2), "r"(r3) : "memory");
}
DEVI uint4 lds128(uint32_t addr) {
  uint4 v; asm volatile("ld.shared.v4.b32 {%0, %1, %2, %3}, [%4];" : "=r"(v.x), "=r"(v.y), "=r"(v.z), "=r"(v.w) : "r"(addr) : "memory"); return v;
}
DEVI float ex2(float x) { float y; asm("ex2.approx.ftz.f32 %0, %1;" : "=f"(y) : "f"(x)); return y; }

DEVI void wgmma_ss_n64(float (&d)[32], uint64_t da, uint64_t db) {
  asm volatile("wgmma.mma_async.sync.aligned.m64n64k16.f32.bf16.bf16 {%0, %1, %2, %3, %4, %5, %6, %7, %8, %9, %10, %11, %12, %13, %14, %15, %16, %17, %18, %19, %20, %21, %22, %23, %24, %25, %26, %27, %28, %29, %30, %31}, %32, %33, 1, 1, 1, 0, 1;"
    : "+f"(d[0]), "+f"(d[1]), "+f"(d[2]), "+f"(d[3]), "+f"(d[4]), "+f"(d[5]), "+f"(d[6]), "+f"(d[7]), "+f"(d[8]), "+f"(d[9]), "+f"(d[10]), "+f"(d[11]), "+f"(d[12]), "+f"(d[13]), "+f"(d[14]), "+f"(d[15]), "+f"(d[16]), "+f"(d[17]), "+f"(d[18]), "+f"(d[19]), "+f"(d[20]), "+f"(d[21]), "+f"(d[22]), "+f"(d[23]), "+f"(d[24]), "+f"(d[25]), "+f"(d[26]), "+f"(d[27]), "+f"(d[28]), "+f"(d[29]), "+f"(d[30]), "+f"(d[31])
    : "l"(da), "l"(db));
}
DEVI void wgmma_ss_n128(float (&d)[64], uint64_t da, uint64_t db) {
  asm volatile("wgmma.mma_async.sync.aligned.m64n128k16.f32.bf16.bf16 {%0, %1, %2, %3, %4, %5, %6, %7, %8, %9, %10, %11, %12, %13, %14, %15, %16, %17, %18, %19, %20, %21, %22, %23, %24, %25, %26, %27, %28, %29, %30, %31, %32, %33, %34, %35, %36, %37, %38, %39, %40, %41, %42, %43, %44, %45, %46, %47, %48, %49, %50, %51, %52, %53, %54, %55, %56, %57, %58, %59, %60, %61, %62, %63}, %64, %65, 1, 1, 1, 0, 1;"
    : "+f"(d[0]), "+f"(d[1]), "+f"(d[2]), "+f"(d[3]), "+f"(d[4]), "+f"(d[5]), "+f"(d[6]), "+f"(d[7]), "+f"(d[8]), "+f"(d[9]), "+f"(d[10]), "+f"(d[11]), "+f"(d[12]), "+f"(d[13]), "+f"(d[14]), "+f"(d[15]), "+f"(d[16]), "+f"(d[17]), "+f"(d[18]), "+f"(d[19]), "+f"(d[20]), "+f"(d[21]), "+f"(d[22]), "+f"(d[23]), "+f"(d[24]), "+f"(d[25]), "+f"(d[26]), "+f"(d[27]), "+f"(d[28]), "+f"(d[29]), "+f"(d[30]), "+f"(d[31]), "+f"(d[32]), "+f"(d[33]), "+f"(d[34]), "+f"(d[35]), "+f"(d[36]), "+f"(d[37]), "+f"(d[38]), "+f"(d[39]), "+f"(d[40]), "+f"(d[41]), "+f"(d[42]), "+f"(d[43]), "+f"(d[44]), "+f"(d[45]), "+f"(d[46]), "+f"(d[47]), "+f"(d[48]), "+f"(d[49]), "+f"(d[50]), "+f"(d[51]), "+f"(d[52]), "+f"(d[53]), "+f"(d[54]), "+f"(d[55]), "+f"(d[56]), "+f"(d[57]), "+f"(d[58]), "+f"(d[59]), "+f"(d[60]), "+f"(d[61]), "+f"(d[62]), "+f"(d[63])
    : "l"(da), "l"(db));
}
DEVI void wgmma_ss_n192(float (&d)[96], uint64_t da, uint64_t db) {
  asm volatile("wgmma.mma_async.sync.aligned.m64n192k16.f32.bf16.bf16 {%0, %1, %2, %3, %4, %5, %6, %7, %8, %9, %10, %11, %12, %13, %14, %15, %16, %17, %18, %19, %20, %21, %22, %23, %24, %25, %26, %27, %28, %29, %30, %31, %32, %33, %34, %35, %36, %37, %38, %39, %40, %41, %42, %43, %44, %45, %46, %47, %48, %49, %50, %51, %52, %53, %54, %55, %56, %57, %58, %59, %60, %61, %62, %63, %64, %65, %66, %67, %68, %69, %70, %71, %72, %73, %74, %75, %76, %77, %78, %79, %80, %81, %82, %83, %84, %85, %86, %87, %88, %89, %90, %91, %92, %93, %94, %95}, %96, %97, 1, 1, 1, 0, 1;"
    : "+f"(d[0]), "+f"(d[1]), "+f"(d[2]), "+f"(d[3]), "+f"(d[4]), "+f"(d[5]), "+f"(d[6]), "+f"(d[7]), "+f"(d[8]), "+f"(d[9]), "+f"(d[10]), "+f"(d[11]), "+f"(d[12]), "+f"(d[13]), "+f"(d[14]), "+f"(d[15]), "+f"(d[16]), "+f"(d[17]), "+f"(d[18]), "+f"(d[19]), "+f"(d[20]), "+f"(d[21]), "+f"(d[22]), "+f"(d[23]), "+f"(d[24]), "+f"(d[25]), "+f"(d[26]), "+f"(d[27]), "+f"(d[28]), "+f"(d[29]), "+f"(d[30]), "+f"(d[31]), "+f"(d[32]), "+f"(d[33]), "+f"(d[34]), "+f"(d[35]), "+f"(d[36]), "+f"(d[37]), "+f"(d[38]), "+f"(d[39]), "+f"(d[40]), "+f"(d[41]), "+f"(d[42]), "+f"(d[43]), "+f"(d[44]), "+f"(d[45]), "+f"(d[46]), "+f"(d[47]), "+f"(d[48]), "+f"(d[49]), "+f"(d[50]), "+f"(d[51]), "+f"(d[52]), "+f"(d[53]), "+f"(d[54]), "+f"(d[55]), "+f"(d[56]), "+f"(d[57]), "+f"(d[58]), "+f"(d[59]), "+f"(d[60]), "+f"(d[61]), "+f"(d[62]), "+f"(d[63]), "+f"(d[64]), "+f"(d[65]), "+f"(d[66]), "+f"(d[67]), "+f"(d[68]), "+f"(d[69]), "+f"(d[70]), "+f"(d[71]), "+f"(d[72]), "+f"(d[73]), "+f"(d[74]), "+f"(d[75]), "+f"(d[76]), "+f"(d[77]), "+f"(d[78]), "+f"(d[79]), "+f"(d[80]), "+f"(d[81]), "+f"(d[82]), "+f"(d[83]), "+f"(d[84]), "+f"(d[85]), "+f"(d[86]), "+f"(d[87]), "+f"(d[88]), "+f"(d[89]), "+f"(d[90]), "+f"(d[91]), "+f"(d[92]), "+f"(d[93]), "+f"(d[94]), "+f"(d[95])
    : "l"(da), "l"(db));
}
DEVI void wgmma_ss_n256(float (&d)[128], uint64_t da, uint64_t db) {
  asm volatile("wgmma.mma_async.sync.aligned.m64n256k16.f32.bf16.bf16 {%0, %1, %2, %3, %4, %5, %6, %7, %8, %9, %10, %11, %12, %13, %14, %15, %16, %17, %18, %19, %20, %21, %22, %23, %24, %25, %26, %27, %28, %29, %30, %31, %32, %33, %34, %35, %36, %37, %38, %39, %40, %41, %42, %43, %44, %45, %46, %47, %48, %49, %50, %51, %52, %53, %54, %55, %56, %57, %58, %59, %60, %61, %62, %63, %64, %65, %66, %67, %68, %69, %70, %71, %72, %73, %74, %75, %76, %77, %78, %79, %80, %81, %82, %83, %84, %85, %86, %87, %88, %89, %90, %91, %92, %93, %94, %95, %96, %97, %98, %99, %100, %101, %102, %103, %104, %105, %106, %107, %108, %109, %110, %111, %112, %113, %114, %115, %116, %117, %118, %119, %120, %121, %122, %123, %124, %125, %126, %127}, %128, %129, 1, 1, 1, 0, 1;"
    : "+f"(d[0]), "+f"(d[1]), "+f"(d[2]), "+f"(d[3]), "+f"(d[4]), "+f"(d[5]), "+f"(d[6]), "+f"(d[7]), "+f"(d[8]), "+f"(d[9]), "+f"(d[10]), "+f"(d[11]), "+f"(d[12]), "+f"(d[13]), "+f"(d[14]), "+f"(d[15]), "+f"(d[16]), "+f"(d[17]), "+f"(d[18]), "+f"(d[19]), "+f"(d[20]), "+f"(d[21]), "+f"(d[22]), "+f"(d[23]), "+f"(d[24]), "+f"(d[25]), "+f"(d[26]), "+f"(d[27]), "+f"(d[28]), "+f"(d[29]), "+f"(d[30]), "+f"(d[31]), "+f"(d[32]), "+f"(d[33]), "+f"(d[34]), "+f"(d[35]), "+f"(d[36]), "+f"(d[37]), "+f"(d[38]), "+f"(d[39]), "+f"(d[40]), "+f"(d[41]), "+f"(d[42]), "+f"(d[43]), "+f"(d[44]), "+f"(d[45]), "+f"(d[46]), "+f"(d[47]), "+f"(d[48]), "+f"(d[49]), "+f"(d[50]), "+f"(d[51]), "+f"(d[52]), "+f"(d[53]), "+f"(d[54]), "+f"(d[55]), "+f"(d[56]), "+f"(d[57]), "+f"(d[58]), "+f"(d[59]), "+f"(d[60]), "+f"(d[61]), "+f"(d[62]), "+f"(d[63]), "+f"(d[64]), "+f"(d[65]), "+f"(d[66]), "+f"(d[67]), "+f"(d[68]), "+f"(d[69]), "+f"(d[70]), "+f"(d[71]), "+f"(d[72]), "+f"(d[73]), "+f"(d[74]), "+f"(d[75]), "+f"(d[76]), "+f"(d[77]), "+f"(d[78]), "+f"(d[79]), "+f"(d[80]), "+f"(d[81]), "+f"(d[82]), "+f"(d[83]), "+f"(d[84]), "+f"(d[85]), "+f"(d[86]), "+f"(d[87]), "+f"(d[88]), "+f"(d[89]), "+f"(d[90]), "+f"(d[91]), "+f"(d[92]), "+f"(d[93]), "+f"(d[94]), "+f"(d[95]), "+f"(d[96]), "+f"(d[97]), "+f"(d[98]), "+f"(d[99]), "+f"(d[100]), "+f"(d[101]), "+f"(d[102]), "+f"(d[103]), "+f"(d[104]), "+f"(d[105]), "+f"(d[106]), "+f"(d[107]), "+f"(d[108]), "+f"(d[109]), "+f"(d[110]), "+f"(d[111]), "+f"(d[112]), "+f"(d[113]), "+f"(d[114]), "+f"(d[115]), "+f"(d[116]), "+f"(d[117]), "+f"(d[118]), "+f"(d[119]), "+f"(d[120]), "+f"(d[121]), "+f"(d[122]), "+f"(d[123]), "+f"(d[124]), "+f"(d[125]), "+f"(d[126]), "+f"(d[127])
    : "l"(da), "l"(db));
}
DEVI void wgmma_qk64(float (&d)[32], uint32_t a0, uint32_t a1, uint32_t a2, uint32_t a3, uint64_t db) {
  asm volatile("wgmma.mma_async.sync.aligned.m64n64k16.f32.bf16.bf16 {%0, %1, %2, %3, %4, %5, %6, %7, %8, %9, %10, %11, %12, %13, %14, %15, %16, %17, %18, %19, %20, %21, %22, %23, %24, %25, %26, %27, %28, %29, %30, %31}, {%32, %33, %34, %35}, %36, 0, 1, 1, 0;"
    : "=f"(d[0]), "=f"(d[1]), "=f"(d[2]), "=f"(d[3]), "=f"(d[4]), "=f"(d[5]), "=f"(d[6]), "=f"(d[7]), "=f"(d[8]), "=f"(d[9]), "=f"(d[10]), "=f"(d[11]), "=f"(d[12]), "=f"(d[13]), "=f"(d[14]), "=f"(d[15]), "=f"(d[16]), "=f"(d[17]), "=f"(d[18]), "=f"(d[19]), "=f"(d[20]), "=f"(d[21]), "=f"(d[22]), "=f"(d[23]), "=f"(d[24]), "=f"(d[25]), "=f"(d[26]), "=f"(d[27]), "=f"(d[28]), "=f"(d[29]), "=f"(d[30]), "=f"(d[31])
    : "r"(a0), "r"(a1), "r"(a2), "r"(a3), "l"(db));
}
DEVI void wgmma_qk128(float (&d)[64], uint32_t a0, uint32_t a1, uint32_t a2, uint32_t a3, uint64_t db) {
  asm volatile("wgmma.mma_async.sync.aligned.m64n128k16.f32.bf16.bf16 {%0, %1, %2, %3, %4, %5, %6, %7, %8, %9, %10, %11, %12, %13, %14, %15, %16, %17, %18, %19, %20, %21, %22, %23, %24, %25, %26, %27, %28, %29, %30, %31, %32, %33, %34, %35, %36, %37, %38, %39, %40, %41, %42, %43, %44, %45, %46, %47, %48, %49, %50, %51, %52, %53, %54, %55, %56, %57, %58, %59, %60, %61, %62, %63}, {%64, %65, %66, %67}, %68, 0, 1, 1, 0;"
    : "=f"(d[0]), "=f"(d[1]), "=f"(d[2]), "=f"(d[3]), "=f"(d[4]), "=f"(d[5]), "=f"(d[6]), "=f"(d[7]), "=f"(d[8]), "=f"(d[9]), "=f"(d[10]), "=f"(d[11]), "=f"(d[12]), "=f"(d[13]), "=f"(d[14]), "=f"(d[15]), "=f"(d[16]), "=f"(d[17]), "=f"(d[18]), "=f"(d[19]), "=f"(d[20]), "=f"(d[21]), "=f"(d[22]), "=f"(d[23]), "=f"(d[24]), "=f"(d[25]), "=f"(d[26]), "=f"(d[27]), "=f"(d[28]), "=f"(d[29]), "=f"(d[30]), "=f"(d[31]), "=f"(d[32]), "=f"(d[33]), "=f"(d[34]), "=f"(d[35]), "=f"(d[36]), "=f"(d[37]), "=f"(d[38]), "=f"(d[39]), "=f"(d[40]), "=f"(d[41]), "=f"(d[42]), "=f"(d[43]), "=f"(d[44]), "=f"(d[45]), "=f"(d[46]), "=f"(d[47]), "=f"(d[48]), "=f"(d[49]), "=f"(d[50]), "=f"(d[51]), "=f"(d[52]), "=f"(d[53]), "=f"(d[54]), "=f"(d[55]), "=f"(d[56]), "=f"(d[57]), "=f"(d[58]), "=f"(d[59]), "=f"(d[60]), "=f"(d[61]), "=f"(d[62]), "=f"(d[63])
    : "r"(a0), "r"(a1), "r"(a2), "r"(a3), "l"(db));
}
DEVI void wgmma_pv(float (&d)[8], uint32_t a0, uint32_t a1, uint32_t a2, uint32_t a3, uint64_t db) {
  asm volatile("wgmma.mma_async.sync.aligned.m64n16k16.f32.bf16.bf16 {%0, %1, %2, %3, %4, %5, %6, %7}, {%8, %9, %10, %11}, %12, 1, 1, 1, 1;"
    : "+f"(d[0]), "+f"(d[1]), "+f"(d[2]), "+f"(d[3]), "+f"(d[4]), "+f"(d[5]), "+f"(d[6]), "+f"(d[7])
    : "r"(a0), "r"(a1), "r"(a2), "r"(a3), "l"(db));
}
DEVI void wgmma_pv0(float (&d)[8], uint32_t a0, uint32_t a1, uint32_t a2, uint32_t a3, uint64_t db) {
  asm volatile("wgmma.mma_async.sync.aligned.m64n16k16.f32.bf16.bf16 {%0, %1, %2, %3, %4, %5, %6, %7}, {%8, %9, %10, %11}, %12, 0, 1, 1, 1;"
    : "=f"(d[0]), "=f"(d[1]), "=f"(d[2]), "=f"(d[3]), "=f"(d[4]), "=f"(d[5]), "=f"(d[6]), "=f"(d[7])
    : "r"(a0), "r"(a1), "r"(a2), "r"(a3), "l"(db));
}

template <int N> DEVI void wgmma_ss(float (&d)[N / 2], uint64_t da, uint64_t db) {
  if constexpr (N == 64) wgmma_ss_n64(d, da, db);
  else if constexpr (N == 128) wgmma_ss_n128(d, da, db);
  else if constexpr (N == 192) wgmma_ss_n192(d, da, db);
  else wgmma_ss_n256(d, da, db);
}

DEVI int oh_chunk(int j, int i, int& need) {
  if (j & 1) {
    if (i >= 3 && i < 7) { need = 16 + 2 * (i - 3); return 24 + (i - 3); }
    if (i >= 7) i -= 4;
  }
  const int g = i / 3, o = (j + 2 * g) & 7;
  need = o;
  return 3 * o + (i - 3 * g);
}

struct Ctx {
  uint32_t sbase, bars, peer, t0, a16, b16;
  int wg, lane;
  int ai, bi; uint32_t aph, bph;
  int brem;
  int pa, pb;
};

DEVI void release_prev(Ctx& c) {
  if (c.pb >= 0) {
    if (c.lane == 0) mbar_arrive(c.bars + 8 * (BAR_EMPTYB + c.pb));
    if (c.lane == 1) mbar_arrive_cluster(c.bars + 8 * (BAR_EMPTYB + c.pb), c.peer);
  }
  if (c.pa >= 0 && c.lane == 2) mbar_arrive(c.bars + 8 * (BAR_EMPTYA + c.pa));
}

DEVI void gemm_wait(Ctx& c) {
  asm volatile("{ .reg .pred p, q; .reg .u32 c;\n"
               "WAIT_%=:\n"
               "mbarrier.try_wait.parity.shared::cta.b64 p, [%0], %1;\n"
               "mbarrier.try_wait.parity.shared::cta.b64 q, [%2], %3;\n"
               "and.pred p, p, q;\n"
               "@p bra DONE_%=;\n"
               "mov.u32 c, %%clock; sub.u32 c, c, %4; setp.lt.u32 p, c, %5;\n"
               "@p bra WAIT_%=;\n"
               "DONE_%=: }" ::"r"(c.bars + 8 * (BAR_FULLA + c.ai)), "r"(c.aph), "r"(c.bars + 8 * (BAR_FULLB + c.bi)), "r"(c.bph), "r"(c.t0), "n"(TIMEOUT) : "memory");
}
template <int N>
DEVI void gemm_group(float (&acc)[N / 2], Ctx& c, int g, int& npa, int& npb) {
  const uint32_t a16 = c.a16 + c.ai * (SLOT >> 4);
  const uint32_t b16 = c.b16 + c.bi * (SLOT >> 4);
  bool adv;
  if constexpr (N >= 192) {
    const uint32_t a2 = a16 + (g & 1) * 4;
    wgmma_ss<N>(acc, desc_sw128<16>(a2), desc_sw128<2048>(b16));
    wgmma_ss<N>(acc, desc_sw128<16>(a2 + 2), desc_sw128<2048>(b16 + 512));
    adv = g & 1;
  } else {
#pragma unroll
    for (int s = 0; s < 4; s++) wgmma_ss<N>(acc, desc_sw128<16>(a16 + s * 2), desc_sw128<4096>(b16 + (s >> 1) * 512 + (s & 1) * 128));
    adv = true;
  }
  wgmma_commit();
  npb = c.brem > 0 ? c.bi : -1;
  c.brem--;
  if (++c.bi == NB) { c.bi = 0; c.bph ^= 1; }
  npa = -1;
  if (adv) { npa = c.ai; if (++c.ai == NA) { c.ai = 0; c.aph ^= 1; } }
}

template <int N>
DEVI void bare_groups(float (&acc)[N / 2], Ctx& c, int g0, int g1) {
  for (int g = g0; g < g1; g++) {
    int npa, npb;
    gemm_wait(c);
    wgmma_fence();
    gemm_group<N>(acc, c, g, npa, npb);
    wgmma_wait<1>();
    release_prev(c);
    c.pa = npa; c.pb = npb;
  }
}
DEVI void drain(Ctx& c) {
  wgmma_wait<0>();
  release_prev(c);
  c.pa = c.pb = -1;
}

constexpr float SC = 0.25f * 1.4426950408889634f;

#define ONCE _Pragma("unroll 1") for (unsigned once_ = 0; once_ < gridDim.y; once_++)

struct Attn {
  uint32_t q[4][4];
  uint32_t nm[4];
  float g0, g1;
  int cmin;
  int rowc;
};

template <int O0, int NS>
DEVI void kill32(float (&S)[NS]) {
#pragma unroll
  for (int i = 0; i < 32; i++) S[O0 + i] = __int_as_float(0xff800000);
}
DEVI void row_max(const float (&S)[64], float& x0, float& x1) {
#pragma unroll
  for (int n = 0; n < 16; n++) {
    x0 = fmaxf(x0, fmaxf(S[4 * n], S[4 * n + 1])); x1 = fmaxf(x1, fmaxf(S[4 * n + 2], S[4 * n + 3]));
  }
}
template <int K, bool PRE = false>
DEVI void exp8(const float (&S)[64], uint32_t (&P)[4], float n0, float n1, float (&l)[4]) {
  float e[8];
#pragma unroll
  for (int i = 0; i < 8; i++) e[i] = ex2(PRE ? S[8 * K + i] : fmaf(S[8 * K + i], SC, (i & 2) ? n1 : n0));
  l[0] += e[0]; l[1] += e[1]; l[2] += e[2]; l[3] += e[3];
  l[0] += e[4]; l[1] += e[5]; l[2] += e[6]; l[3] += e[7];
#pragma unroll
  for (int i = 0; i < 4; i++) P[i] = pack_bf16(e[2 * i], e[2 * i + 1]) | (__float_as_uint(l[i]) & blockIdx.y);
}
DEVI void merge_fl(float (&S)[64], const float (&F)[32], int rowc) {
#pragma unroll
  for (int n = 0; n < 8; n++) {
    if (n * 8 > rowc) S[32 + 4 * n] = F[4 * n];
    if (n * 8 + 1 > rowc) S[32 + 4 * n + 1] = F[4 * n + 1];
    if (n * 8 > rowc + 8) S[32 + 4 * n + 2] = F[4 * n + 2];
    if (n * 8 + 1 > rowc + 8) S[32 + 4 * n + 3] = F[4 * n + 3];
  }
}
DEVI bool wg_any(int wg, bool v) {
  uint32_t r;
  if (wg == 0) asm volatile("{ .reg .pred p, q; setp.ne.u32 p, %1, 0; bar.red.or.pred q, 1, 128, p; selp.u32 %0, 1, 0, q; }" : "=r"(r) : "r"((uint32_t)v) : "memory");
  else asm volatile("{ .reg .pred p, q; setp.ne.u32 p, %1, 0; bar.red.or.pred q, 2, 128, p; selp.u32 %0, 1, 0, q; }" : "=r"(r) : "r"((uint32_t)v) : "memory");
  return r != 0;
}

template <bool FIRST> DEVI void pv_step(float (&O)[8], const uint32_t (&P)[4], uint32_t v16) {
  wgmma_wait<0>();
  wgmma_fence();
  if (FIRST) wgmma_pv0(O, P[0], P[1], P[2], P[3], desc_sw64(v16)); else wgmma_pv(O, P[0], P[1], P[2], P[3], desc_sw64(v16));
  wgmma_commit();
}
template <int K> DEVI void pv_merged(float (&O)[8], const uint32_t (&P)[4], uint32_t (&PL)[4], uint32_t (&PF)[4], int rowc, uint32_t kb) {
#pragma unroll
  for (int i = 0; i < 4; i++) {
    const int col = (K - 4) * 16 + (i >> 1) * 8, r = rowc + (i & 1) * 8;
    const uint32_t m = (col > r ? 0xFFFFu : 0u) | (col + 1 > r ? 0xFFFF0000u : 0u);
    PF[i] = P[i] & m; PL[i] = P[i] & ~m;
  }
  wgmma_wait<0>();
  wgmma_fence();
  wgmma_pv(O, PL[0], PL[1], PL[2], PL[3], desc_sw64(kb + 3 * 256 + 2 + K * 64));
  wgmma_pv(O, PF[0], PF[1], PF[2], PF[3], desc_sw64(kb + 2 + (K - 4) * 64));
  wgmma_commit();
}
DEVI void qk_a(float (&S)[64], float (&F)[32], const uint32_t (&q)[4], uint32_t kb) {
  wgmma_fence();
  wgmma_qk128(S, q[0], q[1], q[2], q[3], desc_sw64(kb + 3 * 256));
  wgmma_qk64(F, q[0], q[1], q[2], q[3], desc_sw64(kb));
}
DEVI void fix_a(float (&S)[64], float (&F)[32], const Attn& at) {
  if (at.cmin > 0) { kill32<0>(F); if (at.cmin > 3) kill32<0>(S); }
  merge_fl(S, F, at.rowc);
}
DEVI void scale64(float (&S)[64], float n0, float n1) {
#pragma unroll
  for (int i = 0; i < 64; i++) S[i] = fmaf(S[i], SC, (i & 2) ? n1 : n0);
}
DEVI void fix_b(float (&S)[64], const Attn& at) {
  if (at.cmin > 1) { kill32<0>(S); if (at.cmin > 2) kill32<32>(S); }
}
DEVI void half_a(const float (&SA)[64], float (&SB)[64], float (&O)[8], float (&l)[4], const Attn& at, uint32_t kb, float n0, float n1) {
  uint32_t P[8][4], PL[4][4], PF[4][4];
  wgmma_fence();
  wgmma_qk128(SB, at.q[0][0], at.q[0][1], at.q[0][2], at.q[0][3], desc_sw64(kb + 256));
  wgmma_commit();
  const uint32_t v = kb + 3 * 256 + 2;
  exp8<0, true>(SA, P[0], n0, n1, l); exp8<1, true>(SA, P[1], n0, n1, l);
  pv_step<true>(O, P[0], v);         exp8<2, true>(SA, P[2], n0, n1, l);
  pv_step<false>(O, P[1], v + 64);   exp8<3, true>(SA, P[3], n0, n1, l);
  pv_step<false>(O, P[2], v + 128);  exp8<4, true>(SA, P[4], n0, n1, l);
  pv_step<false>(O, P[3], v + 192);  exp8<5, true>(SA, P[5], n0, n1, l);
  pv_merged<4>(O, P[4], PL[0], PF[0], at.rowc, kb); exp8<6, true>(SA, P[6], n0, n1, l);
  pv_merged<5>(O, P[5], PL[1], PF[1], at.rowc, kb); exp8<7, true>(SA, P[7], n0, n1, l);
  pv_merged<6>(O, P[6], PL[2], PF[2], at.rowc, kb);
  pv_merged<7>(O, P[7], PL[3], PF[3], at.rowc, kb);
  fix_b(SB, at);
}

DEVI void attention(const Ctx& c, Attn& at, int wi) {
  const uint32_t kvb = ((c.sbase & 0x3FFFF) + OFF_KV + c.wg * 4096) >> 4;
  float SA[64];
  float n0 = __uint_as_float(at.nm[0] << 16), n1 = __uint_as_float(at.nm[0] & 0xffff0000u);
  bool exact = false;
  mbar_wait(c.bars + 8 * BAR_KVFULL, 0, c.t0);
  {
    float F[32];
    qk_a(SA, F, at.q[0], kvb);
    wgmma_commit();
    wgmma_wait<0>();
    fix_a(SA, F, at);
    scale64(SA, n0, n1);
  }
  int h = 0;
#pragma unroll 1
  while (h < 4) {
    const uint32_t kb = kvb + (h & 1) * (KVBUF >> 4);
    const uint32_t kn = h == 3 ? kb : kvb + ((h & 1) ^ 1) * (KVBUF >> 4);
    float O[8], l[4] = {0.f, 0.f, 0.f, 0.f};
    float SN[64], F[32];
    {
      float SB[64];
      half_a(SA, SB, O, l, at, kb, n0, n1);
      uint32_t P[8][4];
      const uint32_t v = kb + 256 + 2;
      exp8<0>(SB, P[0], n0, n1, l); exp8<1>(SB, P[1], n0, n1, l);
      pv_step<false>(O, P[0], v);        exp8<2>(SB, P[2], n0, n1, l);
      pv_step<false>(O, P[1], v + 64);   exp8<3>(SB, P[3], n0, n1, l);
      pv_step<false>(O, P[2], v + 128);  exp8<4>(SB, P[4], n0, n1, l);
      if (h < 3) mbar_wait(c.bars + 8 * (BAR_KVFULL + ((h + 1) & 1)), (h + 1) >> 1, c.t0);
      wgmma_wait<0>();
      qk_a(SN, F, at.q[1], kn);
      wgmma_pv(O, P[3][0], P[3][1], P[3][2], P[3][3], desc_sw64(v + 192));
      wgmma_commit();
      ONCE { exp8<5>(SB, P[5], n0, n1, l); }
      pv_step<false>(O, P[4], v + 256);
      fix_a(SN, F, at);
      exp8<6>(SB, P[6], n0, n1, l);
      pv_step<false>(O, P[5], v + 320);
      scale64(SN, __uint_as_float(at.nm[1] << 16), __uint_as_float(at.nm[1] & 0xffff0000u));
      exp8<7>(SB, P[7], n0, n1, l);
      wgmma_wait<0>();
      wgmma_fence();
      wgmma_pv(O, P[6][0], P[6][1], P[6][2], P[6][3], desc_sw64(v + 384));
      wgmma_pv(O, P[7][0], P[7][1], P[7][2], P[7][3], desc_sw64(v + 448));
      wgmma_commit();
    }
    float l0 = l[0] + l[1], l1 = l[2] + l[3];
    l0 += __shfl_xor_sync(0xffffffffu, l0, 1); l1 += __shfl_xor_sync(0xffffffffu, l1, 1);
    l0 += __shfl_xor_sync(0xffffffffu, l0, 2); l1 += __shfl_xor_sync(0xffffffffu, l1, 2);
    const bool bad = !exact && !(l0 > 1e-6f && l0 < 1e18f && l1 > 1e-6f && l1 < 1e18f);
    const bool redo = wg_any(c.wg, bad);
    wgmma_wait<0>();
    if (redo) {
      float x0 = __int_as_float(0xff800000), x1 = x0;
      {
        float T[64];
        wgmma_fence();
        wgmma_qk128(T, at.q[0][0], at.q[0][1], at.q[0][2], at.q[0][3], desc_sw64(kb + 256));
        wgmma_commit();
        wgmma_wait<0>();
        fix_b(T, at);
        row_max(T, x0, x1);
      }
      float T[64], G[32];
      qk_a(T, G, at.q[0], kb);
      wgmma_commit();
      wgmma_wait<0>();
      fix_a(T, G, at);
      row_max(T, x0, x1);
      x0 = fmaxf(x0, __shfl_xor_sync(0xffffffffu, x0, 1)); x1 = fmaxf(x1, __shfl_xor_sync(0xffffffffu, x1, 1));
      x0 = fmaxf(x0, __shfl_xor_sync(0xffffffffu, x0, 2)); x1 = fmaxf(x1, __shfl_xor_sync(0xffffffffu, x1, 2));
      n0 = -x0 * SC; n1 = -x1 * SC;
      scale64(T, n0, n1);
#pragma unroll
      for (int i = 0; i < 64; i++) SA[i] = T[i];
      exact = true;
    } else {
      if (c.lane == 0) mbar_arrive(c.bars + 8 * (BAR_KVEMPTY + (h & 1)));
      const float c0 = __fdividef(at.g0, l0), c1 = __fdividef(at.g1, l1);
      const uint32_t ost = c.sbase + OFF_A + (15 % NA) * SLOT + c.wg * 8192 + h * 2048;
      const int mi = c.lane >> 3;
      const int srow = wi * 16 + (c.lane & 7) + 8 * (mi & 1);
      stsm_x4(ost + srow * 32 + (mi >> 1) * 16, pack_bf16(O[0] * c0, O[1] * c0), pack_bf16(O[2] * c1, O[3] * c1),
              pack_bf16(O[4] * c0, O[5] * c0), pack_bf16(O[6] * c1, O[7] * c1));
      fence_async_smem();
      __syncwarp();
      if (c.lane == 0) mbar_arrive(c.bars + 8 * (BAR_STG + c.wg));
      n0 = __uint_as_float(at.nm[1] << 16); n1 = __uint_as_float(at.nm[1] & 0xffff0000u);
#pragma unroll
      for (int i = 0; i < 64; i++) SA[i] = SN[i];
#pragma unroll
      for (int i = 0; i < 4; i++) { at.q[0][i] = at.q[1][i]; at.q[1][i] = at.q[2][i]; at.q[2][i] = at.q[3][i]; }
      at.nm[1] = at.nm[2]; at.nm[2] = at.nm[3];
      exact = false;
      h++;
    }
  }
}

template <int CH, int NACC>
DEVI void store_h_chunk(const float (&acc)[NACC], uint32_t base  , int lane, float s0, float s1) {
  const int mi = lane >> 3;
#pragma unroll
  for (int tp = 0; tp < 4; tp++) {
    const int t = CH * 8 + tp * 2;
    const uint32_t r0 = pack_bf16(fmaxf(acc[4 * t + 0], 0.f) * s0, fmaxf(acc[4 * t + 1], 0.f) * s0);
    const uint32_t r1 = pack_bf16(fmaxf(acc[4 * t + 2], 0.f) * s1, fmaxf(acc[4 * t + 3], 0.f) * s1);
    const uint32_t r2 = pack_bf16(fmaxf(acc[4 * t + 4], 0.f) * s0, fmaxf(acc[4 * t + 5], 0.f) * s0);
    const uint32_t r3 = pack_bf16(fmaxf(acc[4 * t + 6], 0.f) * s1, fmaxf(acc[4 * t + 7], 0.f) * s1);
    stsm_x4(base + (((tp * 2 + (mi >> 1)) ^ (lane & 7)) << 4), r0, r1, r2, r3);
  }
}

DEVI void get_gate(Attn& at, const Ctx& c, const unsigned* gflag, unsigned gtgt, const float* gp) {
  if (c.lane == 0) flag_wait(gflag, gtgt, c.t0);
  __syncwarp();
  at.g0 = ld_relaxed_f(gp); at.g1 = ld_relaxed_f(gp + 8);
}

template <int N>
DEVI void phase_q(Ctx& c, Attn& at, int warp, const unsigned* gflag, unsigned gtgt, const float* gp) {
  float acc[N / 2];
#pragma unroll
  for (int i = 0; i < N / 2; i++) acc[i] = 0.f;
  bare_groups<N>(acc, c, 0, 14);
  if constexpr (N == 256) get_gate(at, c, gflag, gtgt, gp);
  bare_groups<N>(acc, c, 14, 16);
  drain(c);
  const int lane = c.lane, mi = lane >> 3;
  const int row = warp * 16 + (lane & 7) + 8 * (mi & 1);
  const int sw = (row >> 1) & 3;
#pragma unroll
  for (int hh = 0; hh < 4; hh++) {
    const uint32_t base = c.sbase + OFF_KV + hh * 8192 + row * 64;
#pragma unroll
    for (int kv = 0; kv < 2; kv++) {
      const int t = 8 + kv * 8 + 2 * hh;
      stsm_x4(base + (((kv * 2 + (mi >> 1)) ^ sw) << 4),
              pack_bf16(acc[4 * t + 0], acc[4 * t + 1]), pack_bf16(acc[4 * t + 2], acc[4 * t + 3]),
              pack_bf16(acc[4 * t + 4], acc[4 * t + 5]), pack_bf16(acc[4 * t + 6], acc[4 * t + 7]));
    }
  }
  fence_async_smem();
  __syncwarp();
  if (lane == 0) mbar_arrive(c.bars + 8 * (BAR_STG + c.wg));
  if constexpr (N == 256) {
    store_h_chunk<3>(acc, c.sbase + OFF_KV + 32768 + row * 128, lane, 1.f - at.g0, 1.f - at.g1);
    fence_async_smem();
    __syncwarp();
    if (lane == 0) mbar_arrive(c.bars + 8 * (BAR_STE + c.wg));
  }
#pragma unroll
  for (int hh = 0; hh < 4; hh++) {
#pragma unroll
    for (int i = 0; i < 4; i++) at.q[hh][i] = pack_bf16(acc[8 * hh + 2 * i], acc[8 * hh + 2 * i + 1]);
    const float* q = &acc[8 * hh];
    const float* k = &acc[32 + 8 * hh];
    float d0 = q[0] * k[0] + q[1] * k[1] + q[4] * k[4] + q[5] * k[5], d1 = q[2] * k[2] + q[3] * k[3] + q[6] * k[6] + q[7] * k[7];
    d0 += __shfl_xor_sync(0xffffffffu, d0, 1); d1 += __shfl_xor_sync(0xffffffffu, d1, 1);
    d0 += __shfl_xor_sync(0xffffffffu, d0, 2); d1 += __shfl_xor_sync(0xffffffffu, d1, 2);
    at.nm[hh] = pack_bf16(-d0 * SC, -d1 * SC);
  }
}

DEVI void first_loads(const Params& P, uint32_t sbase, int e, int j, int rb) {
  const uint32_t bars = sbase + OFF_BAR, fb = bars + 8 * (BAR_FULLB + e), fa = bars + 8 * (BAR_FULLA + e);
  mbar_expect_tx(fa, 16384);
  mbar_expect_tx(fb, (j & 1) ? 12288 : 16384);
  if (e == 0) tma_load_2d(sbase + OFF_A, &P.tmX, 0, rb * 128, fa);
#pragma unroll
  for (int r = 0; r < 2; r++) {
    tma_load_3d(sbase + OFF_B + e * SLOT + r * 8192, &P.tmWqkv, 64 * j, e * 32 + r * 16, 0, fb);
    if (!(j & 1)) tma_load_3d(sbase + OFF_B + e * SLOT + r * 8192 + 6144, &P.tmW1a, 0, e * 32 + r * 16, 24 + (j >> 1), fb);
  }
  if (e == 1) tma_load_2d(sbase + OFF_A + SLOT, &P.tmX, 64, rb * 128, fa);
}

__global__ void __cluster_dims__(2, 1, 1) __launch_bounds__(384, 1) fused_kernel(const __grid_constant__ Params P) {
  extern __shared__ uint8_t smem_raw[];
  const uint32_t sbase = (smem_u32(smem_raw) + 1023u) & ~1023u;
  const uint32_t bars = sbase + OFF_BAR;
  const int tid = threadIdx.x, warp = tid >> 5, lane = tid & 31;
  const uint32_t rank = blockIdx.x & 1, peer = rank ^ 1;
  const int j = (blockIdx.x >> 1) & 7, rb = ((blockIdx.x >> 4) << 1) | rank;
  const uint32_t t0 = clk32();

  const int typeB = j & 1;
  if (tid == 288) {
    for (int s = 0; s < NA; s++) mbar_init(bars + 8 * (BAR_FULLA + s), 1);
    for (int s = 0; s < NB; s++) mbar_init(bars + 8 * (BAR_FULLB + s), 1);
    fence_async_smem();
  } else if (tid < 9) {
    asm volatile("prefetch.tensormap [%0];" ::"l"(&P.tmX + tid) : "memory");
  } else if (tid == 256) {
    for (int s = 0; s < NA; s++) mbar_init(bars + 8 * (BAR_EMPTYA + s), 10);
    for (int s = 0; s < NB; s++) mbar_init(bars + 8 * (BAR_EMPTYB + s), 16);
  } else if (tid == 320) {
    for (int s = 0; s < 2; s++) { mbar_init(bars + 8 * (BAR_KVFULL + s), 1); mbar_init(bars + 8 * (BAR_KVEMPTY + s), 8); mbar_init(bars + 8 * (BAR_STG + s), 4); mbar_init(bars + 8 * (BAR_STE + s), 4); }
    mbar_init(bars + 8 * BAR_PIN, 1); mbar_init(bars + 8 * BAR_GATE, 1); mbar_init(bars + 8 * (BAR_GATE + 1), 1);
  }
  if (tid >= 256 && lane == 0) asm volatile("fence.mbarrier_init.release.cluster;" ::: "memory");
  const unsigned ep1 = ld_relaxed(&g_epoch) + 1;
  __syncwarp();
  cluster_arrive();
  if (tid == 288) { first_loads(P, sbase, 0, j, rb); first_loads(P, sbase, 1, j, rb); }
  __syncwarp();

  const int on = 12 + 4 * typeB;

  if (warp < 8) {
    asm volatile("setmaxnreg.inc.sync.aligned.u32 232;");
    cluster_wait();
    const int wg = __shfl_sync(0xffffffffu, warp >> 2, 0), wi = warp & 3;
    Ctx c{sbase, bars, peer, t0, ((sbase & 0x3FFFF) + OFF_A + wg * 8192) >> 4, ((sbase & 0x3FFFF) + OFF_B) >> 4, wg, lane, 0, 0, 0u, 0u, 32 + on + 4 - NB, -1, -1};
    Attn at;
    at.cmin = 4 - 2 * rb - wg;
    at.rowc = wi * 16 + (lane >> 2) - (lane & 3) * 2;
    const int row0 = rb * 128 + warp * 16 + (lane >> 2);
    if (tid == 0) TR(0);
    if (typeB) phase_q<192>(c, at, warp, &g_flag_g[rb * FS], ep1 * 16, &g_gate[row0]);
    else phase_q<256>(c, at, warp, &g_flag_g[rb * FS], ep1 * 16, &g_gate[row0]);
    if (tid == 0) TR(2);
    {
      float acc[96];
#pragma unroll
      for (int i = 0; i < 96; i++) acc[i] = 0.f;
      bare_groups<192>(acc, c, 0, 8);
      if (typeB) get_gate(at, c, &g_flag_g[rb * FS], ep1 * 16, &g_gate[row0]);
      bare_groups<192>(acc, c, 8, 16);
      drain(c);
      if (tid == 0) TR(1);
      const uint32_t rowoff = (warp * 16 + (lane & 7) + 8 * ((lane >> 3) & 1)) * 128;
      const float s0 = 1.f - at.g0, s1 = 1.f - at.g1;
      constexpr int e0 = 16 % NA, e1 = 17 % NA, e2 = 18 % NA;
      mbar_wait(bars + 8 * (BAR_FULLA + e0), (16 / NA) & 1, t0);
      store_h_chunk<0>(acc, sbase + OFF_A + e0 * SLOT + rowoff, lane, s0, s1);
      mbar_wait(bars + 8 * (BAR_FULLA + e1), (17 / NA) & 1, t0);
      store_h_chunk<1>(acc, sbase + OFF_A + e1 * SLOT + rowoff, lane, s0, s1);
      mbar_wait(bars + 8 * (BAR_FULLA + e2), (18 / NA) & 1, t0);
      store_h_chunk<2>(acc, sbase + OFF_A + e2 * SLOT + rowoff, lane, s0, s1);
    }
    fence_async_smem();
    wg_bar(wg);
    if (lane == 0) mbar_arrive(bars + 8 * (BAR_STG + wg));
    if (tid == 0) TR(4);
    attention(c, at, wi);
    if (tid == 0) TR(3);
    float own[32];
    {
      float acc[64];
#pragma unroll
      for (int i = 0; i < 64; i++) acc[i] = 0.f;
      bare_groups<128>(acc, c, 0, on);
      drain(c);
      if (tid == 0) TR(5);
      mbar_wait(bars + 8 * (BAR_KVEMPTY + 0), 1, t0);
      const uint32_t pst = sbase + OFF_KV + wg * 8192 + (tid & 127) * 16;
#pragma unroll
      for (int i = 0; i < 4; i++) {
        uint32_t r[4];
#pragma unroll
        for (int k = 0; k < 4; k++) {
          const int idx = 8 * i + 2 * k;
          const float lo = typeB ? acc[idx] : acc[32 + idx], hi = typeB ? acc[idx + 1] : acc[32 + idx + 1];
          r[k] = pack_bf16(lo, hi);
        }
        sts128(pst + i * 2048, r[0], r[1], r[2], r[3]);
      }
#pragma unroll
      for (int i = 0; i < 32; i++) own[i] = typeB ? acc[32 + i] : acc[i];
      fence_async_smem();
      __syncwarp();
      if (lane == 0) mbar_arrive(bars + 8 * (BAR_STG + wg));
    }
    for (int g = 0; g < 8; g++) {
      const uint32_t a16 = c.a16 + c.ai * (SLOT >> 4);
      const uint32_t b16 = c.b16 + c.bi * (SLOT >> 4) + (g & 1) * 512;
      mbar_wait(bars + 8 * (BAR_FULLB + c.bi), c.bph, t0);
      mbar_wait(bars + 8 * (BAR_FULLA + c.ai), c.aph, t0);
      wgmma_fence();
#pragma unroll
      for (int s = 0; s < 4; s++) wgmma_ss<64>(own, desc_sw128<16>(a16 + s * 2), desc_sw128<2048>(b16 + s * 128));
      wgmma_commit();
      wgmma_wait<1>();
      release_prev(c);
      c.pa = c.ai; c.pb = -1;
      if (++c.ai == NA) { c.ai = 0; c.aph ^= 1; }
      if (g & 1) { if (++c.bi == NB) { c.bi = 0; c.bph ^= 1; } }
    }
    wgmma_wait<0>();
    if (tid == 0) TR(6);
    mbar_wait(bars + 8 * BAR_PIN, 0, t0);
    if (tid == 0) TR(7);
    {
      const uint32_t pin = sbase + OFF_KV + KVBUF + wg * 8192 + (tid & 127) * 16;
      __nv_bfloat16* o = P.out + (size_t)row0 * DM + j * 64 + (lane & 3) * 2;
#pragma unroll
      for (int i = 0; i < 4; i++) {
        const uint4 v = lds128(pin + i * 2048);
        const uint32_t r[4] = {v.x, v.y, v.z, v.w};
#pragma unroll
        for (int k = 0; k < 4; k++) {
          const int idx = 8 * i + 2 * k;
          const float lo = own[idx] + __uint_as_float(r[k] << 16), hi = own[idx + 1] + __uint_as_float(r[k] & 0xffff0000u);
          *(uint32_t*)(o + (k & 1) * 8 * DM + (2 * i + (k >> 1)) * 8) = pack_bf16(lo, hi);
        }
      }
    }
    if (tid == 0) TR(8);
  } else {
    asm volatile("setmaxnreg.dec.sync.aligned.u32 40;");
    if (warp == 8) {
      __syncwarp();
      cluster_wait();
      if (lane == 0) {
        int bi = 2; uint32_t bph = 1;
        const int nb = 32 + on + 4;
        for (int eb = 2; eb < nb; eb++) {
          if (eb == 4 || eb == 6) {
            for (int ea = eb - 2 - (eb == 6 ? 1 : 0); ea < (eb == 4 ? 3 : NA); ea++) {
              mbar_expect_tx(bars + 8 * (BAR_FULLA + ea), 16384);
              tma_load_2d(sbase + OFF_A + ea * SLOT, &P.tmX, ea * 64, rb * 128, bars + 8 * (BAR_FULLA + ea));
            }
          }
          const uint32_t fb = bars + 8 * (BAR_FULLB + bi), dst = sbase + OFF_B + bi * SLOT + rank * 8192;
          mbar_wait(bars + 8 * (BAR_EMPTYB + bi), bph, t0);
          if (eb < 16) {
            mbar_expect_tx(fb, typeB ? 12288 : 16384);
            tma_load_3d_mc(dst, &P.tmWqkv, 64 * j, eb * 32 + rank * 16, 0, fb);
            if (!typeB) tma_load_3d_mc(dst + 6144, &P.tmW1a, 0, eb * 32 + rank * 16, 24 + (j >> 1), fb);
          }
          else if (eb < 32) { mbar_expect_tx(fb, 12288); tma_load_3d_mc(dst, &P.tmW1b, 0, (eb - 16) * 32 + rank * 16, 3 * j, fb); }
          else if (eb < 32 + on) { int ow; const int ch = oh_chunk(j, eb - 32, ow); mbar_expect_tx(fb, 16384); tma_load_3d_mc(dst, &P.tmW2, 0, ch * 64 + rank * 32, (j >> 1) * 2, fb); }
          else { mbar_expect_tx(fb, 16384); tma_load_4d_mc(dst, &P.tmWo, 64 * j, 0, eb - 32 - on, rank * 4, fb); }
          if (++bi == NB) { bi = 0; bph ^= 1; }
          if (eb == PFAT) {
            const int b = blockIdx.x;
            l2_prefetch((const uint8_t*)P.w1 + b * 14336, 14336);
            l2_prefetch((const uint8_t*)P.w2 + b * 14336, 14336);
            l2_prefetch((const uint8_t*)P.wo + b * 4096, 4096);
          }
        }
      }
    } else if (warp == 9) {
      cluster_wait();
      if (lane == 0) {
        for (int ea = 0; ea < NA; ea++) mbar_arrive_n(bars + 8 * (BAR_EMPTYA + ea), 2);
        int ai = 0; uint32_t aph = 0;
        const int na = 16 + on + 8;
        unsigned ready = 0;
        for (int ea = NA; ea < na; ea++) {
          const uint32_t fb = bars + 8 * (BAR_FULLA + ai), dst = sbase + OFF_A + ai * SLOT;
          int ch = ea & 7, need = -1;
          if (ea >= 16 + on) { need = 8 + ea - 16 - on; ch = 20 + need; }
          else if (ea >= 19) ch = oh_chunk(j, ea - 16, need);
          if (need >= 0 && !((ready >> need) & 1)) {
            const unsigned* fp = need < 8 ? &g_flag_h[rb * 8 * FS] : need < 16 ? &g_flag_o[rb * 8 * FS] : &g_flag_e[rb * 8 * FS];
            const unsigned tgt = (need & 8) ? ep1 * 8 : ep1 * 2;
            do {
              unsigned v[8];
#pragma unroll
              for (int i = 0; i < 8; i++) v[i] = ld_relaxed(fp + i * FS);
#pragma unroll
              for (int i = 0; i < 8; i++) if ((int)(v[i] - tgt) >= 0) ready |= 1u << (i + (need & 24));
            } while (!((ready >> need) & 1) && clk32() - t0 < TIMEOUT);
            fence_async_global();
          }
          mbar_wait(bars + 8 * (BAR_EMPTYA + ai), aph, t0);
          if (ea >= 16 && ea < 19) mbar_arrive(fb);
          else {
            if (ea != 15) mbar_arrive_n(bars + 8 * (BAR_EMPTYA + ai), 2);
            mbar_expect_tx(fb, 16384);
            tma_load_2d(dst, ea < 16 ? &P.tmX : &P.tmHO, ch * 64, rb * 128, fb);
          }
          TR(24 + ea);
          if (++ai == NA) { ai = 0; aph ^= 1; }
        }
      }
    } else {
      const int wg = warp - 10;
      cluster_wait();
      {
        const int rowg = rb * 128 + j * 16 + wg * 8;
        const uint32_t xs = sbase + OFF_KV + 32768 + wg * 8192;
        if (lane == 0) {
          mbar_wait(bars + 8 * (BAR_FULLB + 1), 0, t0);
          mbar_expect_tx(bars + 8 * (BAR_GATE + wg), 8192);
          bulk_load(xs, P.x + (size_t)rowg * DM, 8192, bars + 8 * (BAR_GATE + wg));
        }
        const uint4* gw = (const uint4*)P.gate_w;
        const uint4 w0 = __ldg(gw + lane), w1 = __ldg(gw + 32 + lane);
        const uint32_t wa[8] = {w0.x, w0.y, w0.z, w0.w, w1.x, w1.y, w1.z, w1.w};
        mbar_wait(bars + 8 * (BAR_GATE + wg), 0, t0);
        float zz = 0.f;
#pragma unroll 1
        for (int i = 0; i < 8; i++) {
          const uint4 x0 = lds128(xs + i * 1024 + lane * 16), x1 = lds128(xs + i * 1024 + 512 + lane * 16);
          const uint32_t xa[8] = {x0.x, x0.y, x0.z, x0.w, x1.x, x1.y, x1.z, x1.w};
          float z = 0.f;
#pragma unroll
          for (int e = 0; e < 8; e++) {
            z = fmaf(__uint_as_float(xa[e] << 16), __uint_as_float(wa[e] << 16), z);
            z = fmaf(__uint_as_float(xa[e] & 0xffff0000u), __uint_as_float(wa[e] & 0xffff0000u), z);
          }
#pragma unroll
          for (int o = 16; o > 0; o >>= 1) z += __shfl_xor_sync(0xffffffffu, z, o);
          if (lane == i) zz = z;
        }
        if (lane < 8) asm volatile("st.shared.f32 [%0], %1;" ::"r"(sbase + OFF_GST + wg * 32 + lane * 4), "f"(1.f / (1.f + __expf(-zz))) : "memory");
        fence_async_smem();
        __syncwarp();
        if (lane == 0) {
          bulk_store(&g_gate[rowg], sbase + OFF_GST + wg * 32, 32);
          bulk_commit(); bulk_wait_all();
          flag_add(&g_flag_g[rb * FS]);
          if (wg == 0) TR(10);
        }
      }
      if (lane == 0) {
        const uint32_t stg = bars + 8 * (BAR_STG + wg);
        mbar_wait(stg, 0, t0);
        for (int hh = 0; hh < 4; hh++)
          bulk_store(g_kv + ((size_t)(4 * j + hh) * SEQ + rb * 128 + wg * 64) * 64, sbase + OFF_KV + hh * 8192 + wg * 4096, 4096);
        bulk_commit(); bulk_wait_all();
        flag_add(&g_flag_kv[(rb * 8 + j) * FS]);
        if (wg == 0) TR(21);
        if (!typeB) {
          mbar_wait(bars + 8 * (BAR_STE + wg), 0, t0);
          tma_store_2d(&P.tmHOs, (24 + (j >> 1)) * 64, rb * 128 + wg * 64, sbase + OFF_KV + 32768 + wg * 8192);
          bulk_commit(); bulk_wait_all();
          flag_add(&g_flag_e[(rb * 8 + j) * FS]);
          if (wg == 1) flag_wait(&g_flag_e[(rb * 8 + j) * FS], ep1 * 2, t0);
        }
        const int nblk = rb >= 2 ? 3 : rb + 1;
        const uint32_t kvbytes = nblk * 8192;
        const uint8_t* kvsrc = g_kv + ((size_t)(4 * j) * SEQ + (rb + 1 - nblk) * 128) * 64;
        const uint32_t kvdst = sbase + OFF_KV + wg * KVBUF + (3 - nblk) * 8192;
        {
          const unsigned* f0 = &g_flag_kv[(rb * 8 + j) * FS];
          const unsigned* f1 = rb >= 1 ? f0 - 8 * FS : f0;
          const unsigned* f2 = rb >= 2 ? f0 - 16 * FS : f0;
          unsigned v0, v1, v2;
          do { v0 = ld_relaxed(f0); v1 = ld_relaxed(f1); v2 = ld_relaxed(f2); }
          while (((int)(v0 - ep1 * 2) < 0 || (int)(v1 - ep1 * 2) < 0 || (int)(v2 - ep1 * 2) < 0) && clk32() - t0 < TIMEOUT);
        }
        if (wg == 0) TR(11);
        fence_async_global();
        mbar_expect_tx(bars + 8 * (BAR_KVFULL + wg), kvbytes);
        bulk_load(kvdst, kvsrc + (size_t)wg * SEQ * 64, kvbytes, bars + 8 * (BAR_KVFULL + wg));
        for (int ev = 1; ev < 7; ev++) {
          mbar_wait(stg, ev & 1, t0);
          if (ev == 1) {
            for (int i = 0; i < 3; i++)
              tma_store_2d(&P.tmHOs, (3 * j + i) * 64, rb * 128 + wg * 64, sbase + OFF_A + ((16 + i) % NA) * SLOT + wg * 8192);
            bulk_commit(); bulk_wait_all();
            flag_add(&g_flag_h[(rb * 8 + j) * FS]);
            for (int i = 0; i < 3; i++) mbar_arrive(bars + 8 * (BAR_EMPTYA + (16 + i) % NA));
            if (wg == 0) TR(22);
            if (wg == 0) {
              const unsigned old = atomicAdd(&g_done, 1u);
              if (old == gridDim.x - 1) { g_done = 0; *(volatile unsigned*)&g_epoch = ep1; }
            }
          } else if (ev == 6) {
            bulk_store(g_part + (size_t)(rb * 8 + (j ^ 1)) * 16384 + wg * 8192, sbase + OFF_KV + wg * 8192, 8192);
            bulk_commit(); bulk_wait_all();
            flag_add(&g_flag_p[(rb * 8 + (j ^ 1)) * FS]);
            if (wg == 0) TR(23);
            if (wg == 1) {
              mbar_wait(bars + 8 * (BAR_KVEMPTY + 1), 1, t0);
              flag_wait(&g_flag_p[(rb * 8 + j) * FS], ep1 * 2, t0);
              fence_async_global();
              mbar_expect_tx(bars + 8 * BAR_PIN, 16384);
              bulk_load(sbase + OFF_KV + KVBUF, g_part + (size_t)(rb * 8 + j) * 16384, 16384, bars + 8 * BAR_PIN);
            }
          } else {
            const int hh = ev - 2;
            tma_store_2d(&P.tmOs, DFF + hh * 128 + j * 16, rb * 128 + wg * 64, sbase + OFF_A + (15 % NA) * SLOT + wg * 8192 + hh * 2048);
            bulk_commit();
            if (hh == wg) {
              mbar_wait(bars + 8 * (BAR_KVEMPTY + wg), 0, t0);
              mbar_expect_tx(bars + 8 * (BAR_KVFULL + wg), kvbytes);
              bulk_load(kvdst, kvsrc + (size_t)(wg + 2) * SEQ * 64, kvbytes, bars + 8 * (BAR_KVFULL + wg));
            }
            bulk_wait_all();
            flag_add(&g_flag_o[(rb * 8 + hh * 2 + (j >> 2)) * FS]);
            if (hh == 3) mbar_arrive(bars + 8 * (BAR_EMPTYA + 15 % NA));
            if (wg == 0) TR(12 + hh);
          }
        }
      }
    }
  }
}

typedef CUresult (*EncodeFn)(CUtensorMap*, CUtensorMapDataType, cuuint32_t, void*, const cuuint64_t*, const cuuint64_t*, const cuuint32_t*,
                             const cuuint32_t*, CUtensorMapInterleave, CUtensorMapSwizzle, CUtensorMapL2promotion, CUtensorMapFloatOOBfill);

void make_map(EncodeFn enc, CUtensorMap* m, const void* ptr, int rank, const cuuint64_t* dims, const cuuint64_t* strides, const cuuint32_t* box,
              CUtensorMapSwizzle sw = CU_TENSOR_MAP_SWIZZLE_128B) {
  cuuint32_t es[4] = {1, 1, 1, 1};
  enc(m, CU_TENSOR_MAP_DATA_TYPE_BFLOAT16, rank, const_cast<void*>(ptr), dims, strides, box, es, CU_TENSOR_MAP_INTERLEAVE_NONE, sw,
      CU_TENSOR_MAP_L2_PROMOTION_L2_256B, CU_TENSOR_MAP_FLOAT_OOB_FILL_NONE);
}

}

extern "C" void kernel_launch(void* const* d_in, const int* in_sizes, int n_in, void* d_out, int out_size) {
  (void)in_sizes; (void)n_in; (void)out_size;
  static EncodeFn enc = nullptr;
  static void* ho_ptr = nullptr;
  if (!enc) {
    void* fn = nullptr; cudaDriverEntryPointQueryResult st;
    cudaGetDriverEntryPoint("cuTensorMapEncodeTiled", &fn, cudaEnableDefault, &st);
    enc = (EncodeFn)fn;
    cudaGetSymbolAddress(&ho_ptr, g_ho);
    cudaFuncSetAttribute(fused_kernel, cudaFuncAttributeMaxDynamicSharedMemorySize, SMEM_BYTES);
  }
  const __nv_bfloat16* x = (const __nv_bfloat16*)d_in[0];
  const __nv_bfloat16* wqkv = (const __nv_bfloat16*)d_in[1];
  const __nv_bfloat16* wo = (const __nv_bfloat16*)d_in[2];
  const __nv_bfloat16* w1 = (const __nv_bfloat16*)d_in[4];
  const __nv_bfloat16* w2 = (const __nv_bfloat16*)d_in[5];
  const __nv_bfloat16* gate_w = (const __nv_bfloat16*)d_in[6];
  Params P;
  { cuuint64_t d[2] = {DM, SEQ}, s[1] = {DM * 2}; cuuint32_t b[2] = {64, 128}; make_map(enc, &P.tmX, x, 2, d, s, b); }
  { cuuint64_t d[3] = {512, 512, 3}, s[2] = {1536 * 2, 512 * 2}; cuuint32_t b[3] = {64, 16, 3}; make_map(enc, &P.tmWqkv, wqkv, 3, d, s, b); }
  { cuuint64_t d[3] = {64, 512, 28}, s[2] = {DFF * 2, 128}; cuuint32_t b[3] = {64, 16, 1}; make_map(enc, &P.tmW1a, w1, 3, d, s, b);
    b[2] = 3; make_map(enc, &P.tmW1b, w1, 3, d, s, b); }
  { cuuint64_t d[3] = {64, DFF, 8}, s[2] = {DM * 2, 128}; cuuint32_t b[3] = {64, 32, 2}; make_map(enc, &P.tmW2, w2, 3, d, s, b); }
  { cuuint64_t d[4] = {DM, 16, 4, 8}, s[3] = {DM * 2, 16 * DM * 2, 64 * DM * 2}; cuuint32_t b[4] = {64, 16, 1, 4}; make_map(enc, &P.tmWo, wo, 4, d, s, b); }
  { cuuint64_t d[2] = {KHO, SEQ}, s[1] = {KHO * 2}; cuuint32_t b[2] = {64, 128}; make_map(enc, &P.tmHO, ho_ptr, 2, d, s, b);
    b[1] = 64; make_map(enc, &P.tmHOs, ho_ptr, 2, d, s, b);
    b[0] = 16; make_map(enc, &P.tmOs, ho_ptr, 2, d, s, b, CU_TENSOR_MAP_SWIZZLE_NONE); }
  P.x = x; P.gate_w = gate_w; P.w1 = w1; P.w2 = w2; P.wo = wo; P.out = (__nv_bfloat16*)d_out;
  fused_kernel<<<128, 384, SMEM_BYTES>>>(P);
}
```

```cpp
#include <cuda_runtime.h>
#include <cuda_bf16.h>
#include <cuda.h>
#include <stdint.h>

#define DEVI __device__ __forceinline__

namespace {

constexpr int SEQ = 2048, DM = 512, DFF = 1792, KHO = 2304;
constexpr int NA = 5, NB = 6, SLOT = 16384, KVBUF = 24576;
constexpr int NA2 = 8;
constexpr int OFF_B = 0, OFF_A = NB * SLOT, OFF_KV = OFF_A + NA * SLOT, OFF_BAR = OFF_KV + 2 * KVBUF;
constexpr int OFF_GST = OFF_BAR + 512;
constexpr int SMEM_BYTES = OFF_BAR + 1024 + 1024;
constexpr uint32_t TIMEOUT = 1u << 28;
#define WAIT_HINT_NS 20000u
#define PFAT 8
constexpr int FS = 8;

constexpr int BAR_FULLA = 0, BAR_EMPTYA = BAR_FULLA + NA2, BAR_FULLB = BAR_EMPTYA + NA2, BAR_EMPTYB = BAR_FULLB + NB,
              BAR_KVFULL = BAR_EMPTYB + NB, BAR_KVEMPTY = BAR_KVFULL + 2, BAR_STG = BAR_KVEMPTY + 2, BAR_PIN = BAR_STG + 2, BAR_GATE = BAR_PIN + 1, BAR_STE = BAR_GATE + 2;

__device__ __align__(1024) uint8_t g_kv[32 * SEQ * 64];
__device__ __align__(1024) __nv_bfloat16 g_ho[SEQ * KHO];
__device__ __align__(1024) uint8_t g_part[128 * 16384];
__device__ __align__(128) float g_gate[SEQ];
__device__ unsigned g_flag_kv[128 * FS], g_flag_h[128 * FS], g_flag_o[128 * FS], g_flag_g[16 * FS], g_flag_p[128 * FS], g_flag_e[128 * FS];
__device__ unsigned g_epoch, g_done;
#define TR(i) do {} while (0)

struct Params {
  CUtensorMap tmX, tmWqkv, tmW1a, tmW1b, tmW2, tmWo, tmHO, tmHOs, tmOs, tmOut;
  const __nv_bfloat16* x;
  const __nv_bfloat16* gate_w;
  const __nv_bfloat16* w1;
  const __nv_bfloat16* w2;
  const __nv_bfloat16* wo;
  __nv_bfloat16* out;
};

DEVI uint32_t smem_u32(const void* p) { return (uint32_t)__cvta_generic_to_shared(p); }
DEVI uint32_t clk32() { uint32_t c; asm volatile("mov.u32 %0, %%clock;" : "=r"(c)); return c; }
DEVI void mbar_init(uint32_t bar, uint32_t cnt) { asm volatile("mbarrier.init.shared::cta.b64 [%0], %1;" ::"r"(bar), "r"(cnt)); }
DEVI void mbar_expect_tx(uint32_t bar, uint32_t bytes) { asm volatile("mbarrier.arrive.expect_tx.shared::cta.b64 _, [%0], %1;" ::"r"(bar), "r"(bytes) : "memory"); }
DEVI void mbar_arrive(uint32_t bar) { asm volatile("mbarrier.arrive.shared::cta.b64 _, [%0];" ::"r"(bar) : "memory"); }
DEVI void mbar_arrive_n(uint32_t bar, uint32_t n) { asm volatile("mbarrier.arrive.shared::cta.b64 _, [%0], %1;" ::"r"(bar), "r"(n) : "memory"); }
DEVI void mbar_arrive_cluster(uint32_t bar, uint32_t cta) {
  asm volatile("{ .reg .b32 ra; mapa.shared::cluster.u32 ra, %0, %1; mbarrier.arrive.shared::cluster.b64 _, [ra]; }" ::"r"(bar), "r"(cta) : "memory");
}
DEVI void mbar_wait(uint32_t bar, uint32_t parity, uint32_t t0) {
  asm volatile("{ .reg .pred p; .reg .u32 c;\n"
               "mbarrier.try_wait.parity.shared::cta.b64 p, [%0], %1;\n"
               "@p bra DONE_%=;\n"
               "WAIT_%=:\n"
               "mbarrier.try_wait.parity.shared::cta.b64 p, [%0], %1, %4;\n"
               "@p bra DONE_%=;\n"
               "mov.u32 c, %%clock; sub.u32 c, c, %2; setp.lt.u32 p, c, %3;\n"
               "@p bra WAIT_%=;\n"
               "DONE_%=: }" ::"r"(bar), "r"(parity), "r"(t0), "n"(TIMEOUT), "r"(WAIT_HINT_NS) : "memory");
}
DEVI unsigned ld_relaxed(const unsigned* p) { unsigned v; asm volatile("ld.relaxed.gpu.global.u32 %0, [%1];" : "=r"(v) : "l"(p) : "memory"); return v; }
DEVI float ld_relaxed_f(const float* p) { float v; asm volatile("ld.relaxed.gpu.global.f32 %0, [%1];" : "=f"(v) : "l"(p) : "memory"); return v; }
DEVI void flag_wait(const unsigned* p, unsigned target, uint32_t t0) {
  while ((int)(ld_relaxed(p) - target) < 0) { if (clk32() - t0 > TIMEOUT) break; }
}
DEVI void flag_add(unsigned* p) { asm volatile("red.relaxed.gpu.global.add.u32 [%0], 1;" ::"l"(p) : "memory"); }
DEVI void fence_async_smem() { asm volatile("fence.proxy.async.shared::cta;" ::: "memory"); }
DEVI void fence_async_global() { asm volatile("fence.proxy.async.global;" ::: "memory"); }
DEVI void tma_load_2d(uint32_t dst, const CUtensorMap* m, int c0, int c1, uint32_t bar) {
  asm volatile("cp.async.bulk.tensor.2d.shared::cluster.global.mbarrier::complete_tx::bytes [%0], [%1, {%3, %4}], [%2];" ::"r"(dst), "l"(m), "r"(bar), "r"(c0), "r"(c1) : "memory");
}
DEVI void tma_load_3d(uint32_t dst, const CUtensorMap* m, int c0, int c1, int c2, uint32_t bar) {
  asm volatile("cp.async.bulk.tensor.3d.shared::cluster.global.mbarrier::complete_tx::bytes [%0], [%1, {%3, %4, %5}], [%2];"
               ::"r"(dst), "l"(m), "r"(bar), "r"(c0), "r"(c1), "r"(c2) : "memory");
}
DEVI void tma_load_3d_mc(uint32_t dst, const CUtensorMap* m, int c0, int c1, int c2, uint32_t bar) {
  asm volatile("cp.async.bulk.tensor.3d.shared::cluster.global.mbarrier::complete_tx::bytes.multicast::cluster [%0], [%1, {%3, %4, %5}], [%2], %6;"
               ::"r"(dst), "l"(m), "r"(bar), "r"(c0), "r"(c1), "r"(c2), "h"((uint16_t)3) : "memory");
}
DEVI void tma_load_4d_mc(uint32_t dst, const CUtensorMap* m, int c0, int c1, int c2, int c3, uint32_t bar) {
  asm volatile("cp.async.bulk.tensor.4d.shared::cluster.global.mbarrier::complete_tx::bytes.multicast::cluster [%0], [%1, {%3, %4, %5, %6}], [%2], %7;"
               ::"r"(dst), "l"(m), "r"(bar), "r"(c0), "r"(c1), "r"(c2), "r"(c3), "h"((uint16_t)3) : "memory");
}
DEVI void tma_store_2d(const CUtensorMap* m, int c0, int c1, uint32_t src) {
  asm volatile("cp.async.bulk.tensor.2d.global.shared::cta.bulk_group [%0, {%1, %2}], [%3];" ::"l"(m), "r"(c0), "r"(c1), "r"(src) : "memory");
}
DEVI void bulk_store(void* dst, uint32_t src, uint32_t bytes) {
  asm volatile("cp.async.bulk.global.shared::cta.bulk_group [%0], [%1], %2;" ::"l"(dst), "r"(src), "r"(bytes) : "memory");
}
DEVI void bulk_load(uint32_t dst, const void* src, uint32_t bytes, uint32_t bar) {
  asm volatile("cp.async.bulk.shared::cluster.global.mbarrier::complete_tx::bytes [%0], [%1], %2, [%3];" ::"r"(dst), "l"(src), "r"(bytes), "r"(bar) : "memory");
}
DEVI void bulk_commit() { asm volatile("cp.async.bulk.commit_group;" ::: "memory"); }
DEVI void bulk_wait_all() { asm volatile("cp.async.bulk.wait_group 0;" ::: "memory"); }
DEVI void l2_prefetch(const void* p, uint32_t bytes) { asm volatile("cp.async.bulk.prefetch.L2.global [%0], %1;" ::"l"(p), "r"(bytes) : "memory"); }
DEVI void cluster_arrive() { asm volatile("barrier.cluster.arrive.relaxed.aligned;" ::: "memory"); }
DEVI void cluster_wait() { asm volatile("barrier.cluster.wait.aligned;" ::: "memory"); }
template <int ID> DEVI void named_bar(int n) { asm volatile("bar.sync %0, %1;" ::"n"(ID), "r"(n) : "memory"); }
DEVI void wg_bar(int wg) { if (wg == 0) named_bar<1>(128); else named_bar<2>(128); }
DEVI void wgmma_fence() { asm volatile("wgmma.fence.sync.aligned;" ::: "memory"); }
DEVI void wgmma_commit() { asm volatile("wgmma.commit_group.sync.aligned;" ::: "memory"); }
template <int N> DEVI void wgmma_wait() { asm volatile("wgmma.wait_group.sync.aligned %0;" ::"n"(N) : "memory"); }
template <uint32_t LBO> DEVI uint64_t desc_sw128(uint32_t a16) {
  return ((uint64_t)(0x40000000u | (1024 >> 4)) << 32) | (a16 + ((LBO >> 4) << 16));
}
DEVI uint64_t desc_sw64(uint32_t a16) {
  return ((uint64_t)(0x80000000u | (512 >> 4)) << 32) | (a16 + ((512 >> 4) << 16));
}
DEVI uint32_t pack_bf16(float lo, float hi) { uint32_t r; asm("cvt.rn.bf16x2.f32 %0, %1, %2;" : "=r"(r) : "f"(hi), "f"(lo)); return r; }
DEVI void stsm_x4(uint32_t addr, uint32_t r0, uint32_t r1, uint32_t r2, uint32_t r3) {
  asm volatile("stmatrix.sync.aligned.m8n8.x4.shared.b16 [%0], {%1, %2, %3, %4};" ::"r"(addr), "r"(r0), "r"(r1), "r"(r2), "r"(r3) : "memory");
}
DEVI void sts128(uint32_t addr, uint32_t r0, uint32_t r1, uint32_t r2, uint32_t r3) {
  asm volatile("st.shared.v4.b32 [%0], {%1, %2, %3, %4};" ::"r"(addr), "r"(r0), "r"(r1), "r"(r2), "r"(r3) : "memory");
}
DEVI uint4 lds128(uint32_t addr) {
  uint4 v; asm volatile("ld.shared.v4.b32 {%0, %1, %2, %3}, [%4];" : "=r"(v.x), "=r"(v.y), "=r"(v.z), "=r"(v.w) : "r"(addr) : "memory"); return v;
}
DEVI float ex2(float x) { float y; asm("ex2.approx.ftz.f32 %0, %1;" : "=f"(y) : "f"(x)); return y; }

DEVI void wgmma_ss_n64(float (&d)[32], uint64_t da, uint64_t db) {
  asm volatile("wgmma.mma_async.sync.aligned.m64n64k16.f32.bf16.bf16 {%0, %1, %2, %3, %4, %5, %6, %7, %8, %9, %10, %11, %12, %13, %14, %15, %16, %17, %18, %19, %20, %21, %22, %23, %24, %25, %26, %27, %28, %29, %30, %31}, %32, %33, 1, 1, 1, 0, 1;"
    : "+f"(d[0]), "+f"(d[1]), "+f"(d[2]), "+f"(d[3]), "+f"(d[4]), "+f"(d[5]), "+f"(d[6]), "+f"(d[7]), "+f"(d[8]), "+f"(d[9]), "+f"(d[10]), "+f"(d[11]), "+f"(d[12]), "+f"(d[13]), "+f"(d[14]), "+f"(d[15]), "+f"(d[16]), "+f"(d[17]), "+f"(d[18]), "+f"(d[19]), "+f"(d[20]), "+f"(d[21]), "+f"(d[22]), "+f"(d[23]), "+f"(d[24]), "+f"(d[25]), "+f"(d[26]), "+f"(d[27]), "+f"(d[28]), "+f"(d[29]), "+f"(d[30]), "+f"(d[31])
    : "l"(da), "l"(db));
}
DEVI void wgmma_ss_n128(float (&d)[64], uint64_t da, uint64_t db) {
  asm volatile("wgmma.mma_async.sync.aligned.m64n128k16.f32.bf16.bf16 {%0, %1, %2, %3, %4, %5, %6, %7, %8, %9, %10, %11, %12, %13, %14, %15, %16, %17, %18, %19, %20, %21, %22, %23, %24, %25, %26, %27, %28, %29, %30, %31, %32, %33, %34, %35, %36, %37, %38, %39, %40, %41, %42, %43, %44, %45, %46, %47, %48, %49, %50, %51, %52, %53, %54, %55, %56, %57, %58, %59, %60, %61, %62, %63}, %64, %65, 1, 1, 1, 0, 1;"
    : "+f"(d[0]), "+f"(d[1]), "+f"(d[2]), "+f"(d[3]), "+f"(d[4]), "+f"(d[5]), "+f"(d[6]), "+f"(d[7]), "+f"(d[8]), "+f"(d[9]), "+f"(d[10]), "+f"(d[11]), "+f"(d[12]), "+f"(d[13]), "+f"(d[14]), "+f"(d[15]), "+f"(d[16]), "+f"(d[17]), "+f"(d[18]), "+f"(d[19]), "+f"(d[20]), "+f"(d[21]), "+f"(d[22]), "+f"(d[23]), "+f"(d[24]), "+f"(d[25]), "+f"(d[26]), "+f"(d[27]), "+f"(d[28]), "+f"(d[29]), "+f"(d[30]), "+f"(d[31]), "+f"(d[32]), "+f"(d[33]), "+f"(d[34]), "+f"(d[35]), "+f"(d[36]), "+f"(d[37]), "+f"(d[38]), "+f"(d[39]), "+f"(d[40]), "+f"(d[41]), "+f"(d[42]), "+f"(d[43]), "+f"(d[44]), "+f"(d[45]), "+f"(d[46]), "+f"(d[47]), "+f"(d[48]), "+f"(d[49]), "+f"(d[50]), "+f"(d[51]), "+f"(d[52]), "+f"(d[53]), "+f"(d[54]), "+f"(d[55]), "+f"(d[56]), "+f"(d[57]), "+f"(d[58]), "+f"(d[59]), "+f"(d[60]), "+f"(d[61]), "+f"(d[62]), "+f"(d[63])
    : "l"(da), "l"(db));
}
DEVI void wgmma_ss_n192(float (&d)[96], uint64_t da, uint64_t db) {
  asm volatile("wgmma.mma_async.sync.aligned.m64n192k16.f32.bf16.bf16 {%0, %1, %2, %3, %4, %5, %6, %7, %8, %9, %10, %11, %12, %13, %14, %15, %16, %17, %18, %19, %20, %21, %22, %23, %24, %25, %26, %27, %28, %29, %30, %31, %32, %33, %34, %35, %36, %37, %38, %39, %40, %41, %42, %43, %44, %45, %46, %47, %48, %49, %50, %51, %52, %53, %54, %55, %56, %57, %58, %59, %60, %61, %62, %63, %64, %65, %66, %67, %68, %69, %70, %71, %72, %73, %74, %75, %76, %77, %78, %79, %80, %81, %82, %83, %84, %85, %86, %87, %88, %89, %90, %91, %92, %93, %94, %95}, %96, %97, 1, 1, 1, 0, 1;"
    : "+f"(d[0]), "+f"(d[1]), "+f"(d[2]), "+f"(d[3]), "+f"(d[4]), "+f"(d[5]), "+f"(d[6]), "+f"(d[7]), "+f"(d[8]), "+f"(d[9]), "+f"(d[10]), "+f"(d[11]), "+f"(d[12]), "+f"(d[13]), "+f"(d[14]), "+f"(d[15]), "+f"(d[16]), "+f"(d[17]), "+f"(d[18]), "+f"(d[19]), "+f"(d[20]), "+f"(d[21]), "+f"(d[22]), "+f"(d[23]), "+f"(d[24]), "+f"(d[25]), "+f"(d[26]), "+f"(d[27]), "+f"(d[28]), "+f"(d[29]), "+f"(d[30]), "+f"(d[31]), "+f"(d[32]), "+f"(d[33]), "+f"(d[34]), "+f"(d[35]), "+f"(d[36]), "+f"(d[37]), "+f"(d[38]), "+f"(d[39]), "+f"(d[40]), "+f"(d[41]), "+f"(d[42]), "+f"(d[43]), "+f"(d[44]), "+f"(d[45]), "+f"(d[46]), "+f"(d[47]), "+f"(d[48]), "+f"(d[49]), "+f"(d[50]), "+f"(d[51]), "+f"(d[52]), "+f"(d[53]), "+f"(d[54]), "+f"(d[55]), "+f"(d[56]), "+f"(d[57]), "+f"(d[58]), "+f"(d[59]), "+f"(d[60]), "+f"(d[61]), "+f"(d[62]), "+f"(d[63]), "+f"(d[64]), "+f"(d[65]), "+f"(d[66]), "+f"(d[67]), "+f"(d[68]), "+f"(d[69]), "+f"(d[70]), "+f"(d[71]), "+f"(d[72]), "+f"(d[73]), "+f"(d[74]), "+f"(d[75]), "+f"(d[76]), "+f"(d[77]), "+f"(d[78]), "+f"(d[79]), "+f"(d[80]), "+f"(d[81]), "+f"(d[82]), "+f"(d[83]), "+f"(d[84]), "+f"(d[85]), "+f"(d[86]), "+f"(d[87]), "+f"(d[88]), "+f"(d[89]), "+f"(d[90]), "+f"(d[91]), "+f"(d[92]), "+f"(d[93]), "+f"(d[94]), "+f"(d[95])
    : "l"(da), "l"(db));
}
DEVI void wgmma_ss_n256(float (&d)[128], uint64_t da, uint64_t db) {
  asm volatile("wgmma.mma_async.sync.aligned.m64n256k16.f32.bf16.bf16 {%0, %1, %2, %3, %4, %5, %6, %7, %8, %9, %10, %11, %12, %13, %14, %15, %16, %17, %18, %19, %20, %21, %22, %23, %24, %25, %26, %27, %28, %29, %30, %31, %32, %33, %34, %35, %36, %37, %38, %39, %40, %41, %42, %43, %44, %45, %46, %47, %48, %49, %50, %51, %52, %53, %54, %55, %56, %57, %58, %59, %60, %61, %62, %63, %64, %65, %66, %67, %68, %69, %70, %71, %72, %73, %74, %75, %76, %77, %78, %79, %80, %81, %82, %83, %84, %85, %86, %87, %88, %89, %90, %91, %92, %93, %94, %95, %96, %97, %98, %99, %100, %101, %102, %103, %104, %105, %106, %107, %108, %109, %110, %111, %112, %113, %114, %115, %116, %117, %118, %119, %120, %121, %122, %123, %124, %125, %126, %127}, %128, %129, 1, 1, 1, 0, 1;"
    : "+f"(d[0]), "+f"(d[1]), "+f"(d[2]), "+f"(d[3]), "+f"(d[4]), "+f"(d[5]), "+f"(d[6]), "+f"(d[7]), "+f"(d[8]), "+f"(d[9]), "+f"(d[10]), "+f"(d[11]), "+f"(d[12]), "+f"(d[13]), "+f"(d[14]), "+f"(d[15]), "+f"(d[16]), "+f"(d[17]), "+f"(d[18]), "+f"(d[19]), "+f"(d[20]), "+f"(d[21]), "+f"(d[22]), "+f"(d[23]), "+f"(d[24]), "+f"(d[25]), "+f"(d[26]), "+f"(d[27]), "+f"(d[28]), "+f"(d[29]), "+f"(d[30]), "+f"(d[31]), "+f"(d[32]), "+f"(d[33]), "+f"(d[34]), "+f"(d[35]), "+f"(d[36]), "+f"(d[37]), "+f"(d[38]), "+f"(d[39]), "+f"(d[40]), "+f"(d[41]), "+f"(d[42]), "+f"(d[43]), "+f"(d[44]), "+f"(d[45]), "+f"(d[46]), "+f"(d[47]), "+f"(d[48]), "+f"(d[49]), "+f"(d[50]), "+f"(d[51]), "+f"(d[52]), "+f"(d[53]), "+f"(d[54]), "+f"(d[55]), "+f"(d[56]), "+f"(d[57]), "+f"(d[58]), "+f"(d[59]), "+f"(d[60]), "+f"(d[61]), "+f"(d[62]), "+f"(d[63]), "+f"(d[64]), "+f"(d[65]), "+f"(d[66]), "+f"(d[67]), "+f"(d[68]), "+f"(d[69]), "+f"(d[70]), "+f"(d[71]), "+f"(d[72]), "+f"(d[73]), "+f"(d[74]), "+f"(d[75]), "+f"(d[76]), "+f"(d[77]), "+f"(d[78]), "+f"(d[79]), "+f"(d[80]), "+f"(d[81]), "+f"(d[82]), "+f"(d[83]), "+f"(d[84]), "+f"(d[85]), "+f"(d[86]), "+f"(d[87]), "+f"(d[88]), "+f"(d[89]), "+f"(d[90]), "+f"(d[91]), "+f"(d[92]), "+f"(d[93]), "+f"(d[94]), "+f"(d[95]), "+f"(d[96]), "+f"(d[97]), "+f"(d[98]), "+f"(d[99]), "+f"(d[100]), "+f"(d[101]), "+f"(d[102]), "+f"(d[103]), "+f"(d[104]), "+f"(d[105]), "+f"(d[106]), "+f"(d[107]), "+f"(d[108]), "+f"(d[109]), "+f"(d[110]), "+f"(d[111]), "+f"(d[112]), "+f"(d[113]), "+f"(d[114]), "+f"(d[115]), "+f"(d[116]), "+f"(d[117]), "+f"(d[118]), "+f"(d[119]), "+f"(d[120]), "+f"(d[121]), "+f"(d[122]), "+f"(d[123]), "+f"(d[124]), "+f"(d[125]), "+f"(d[126]), "+f"(d[127])
    : "l"(da), "l"(db));
}
DEVI void wgmma_qk64(float (&d)[32], uint32_t a0, uint32_t a1, uint32_t a2, uint32_t a3, uint64_t db) {
  asm volatile("wgmma.mma_async.sync.aligned.m64n64k16.f32.bf16.bf16 {%0, %1, %2, %3, %4, %5, %6, %7, %8, %9, %10, %11, %12, %13, %14, %15, %16, %17, %18, %19, %20, %21, %22, %23, %24, %25, %26, %27, %28, %29, %30, %31}, {%32, %33, %34, %35}, %36, 0, 1, 1, 0;"
    : "=f"(d[0]), "=f"(d[1]), "=f"(d[2]), "=f"(d[3]), "=f"(d[4]), "=f"(d[5]), "=f"(d[6]), "=f"(d[7]), "=f"(d[8]), "=f"(d[9]), "=f"(d[10]), "=f"(d[11]), "=f"(d[12]), "=f"(d[13]), "=f"(d[14]), "=f"(d[15]), "=f"(d[16]), "=f"(d[17]), "=f"(d[18]), "=f"(d[19]), "=f"(d[20]), "=f"(d[21]), "=f"(d[22]), "=f"(d[23]), "=f"(d[24]), "=f"(d[25]), "=f"(d[26]), "=f"(d[27]), "=f"(d[28]), "=f"(d[29]), "=f"(d[30]), "=f"(d[31])
    : "r"(a0), "r"(a1), "r"(a2), "r"(a3), "l"(db));
}
DEVI void wgmma_qk128(float (&d)[64], uint32_t a0, uint32_t a1, uint32_t a2, uint32_t a3, uint64_t db) {
  asm volatile("wgmma.mma_async.sync.aligned.m64n128k16.f32.bf16.bf16 {%0, %1, %2, %3, %4, %5, %6, %7, %8, %9, %10, %11, %12, %13, %14, %15, %16, %17, %18, %19, %20, %21, %22, %23, %24, %25, %26, %27, %28, %29, %30, %31, %32, %33, %34, %35, %36, %37, %38, %39, %40, %41, %42, %43, %44, %45, %46, %47, %48, %49, %50, %51, %52, %53, %54, %55, %56, %57, %58, %59, %60, %61, %62, %63}, {%64, %65, %66, %67}, %68, 0, 1, 1, 0;"
    : "=f"(d[0]), "=f"(d[1]), "=f"(d[2]), "=f"(d[3]), "=f"(d[4]), "=f"(d[5]), "=f"(d[6]), "=f"(d[7]), "=f"(d[8]), "=f"(d[9]), "=f"(d[10]), "=f"(d[11]), "=f"(d[12]), "=f"(d[13]), "=f"(d[14]), "=f"(d[15]), "=f"(d[16]), "=f"(d[17]), "=f"(d[18]), "=f"(d[19]), "=f"(d[20]), "=f"(d[21]), "=f"(d[22]), "=f"(d[23]), "=f"(d[24]), "=f"(d[25]), "=f"(d[26]), "=f"(d[27]), "=f"(d[28]), "=f"(d[29]), "=f"(d[30]), "=f"(d[31]), "=f"(d[32]), "=f"(d[33]), "=f"(d[34]), "=f"(d[35]), "=f"(d[36]), "=f"(d[37]), "=f"(d[38]), "=f"(d[39]), "=f"(d[40]), "=f"(d[41]), "=f"(d[42]), "=f"(d[43]), "=f"(d[44]), "=f"(d[45]), "=f"(d[46]), "=f"(d[47]), "=f"(d[48]), "=f"(d[49]), "=f"(d[50]), "=f"(d[51]), "=f"(d[52]), "=f"(d[53]), "=f"(d[54]), "=f"(d[55]), "=f"(d[56]), "=f"(d[57]), "=f"(d[58]), "=f"(d[59]), "=f"(d[60]), "=f"(d[61]), "=f"(d[62]), "=f"(d[63])
    : "r"(a0), "r"(a1), "r"(a2), "r"(a3), "l"(db));
}
DEVI void wgmma_pv(float (&d)[8], uint32_t a0, uint32_t a1, uint32_t a2, uint32_t a3, uint64_t db) {
  asm volatile("wgmma.mma_async.sync.aligned.m64n16k16.f32.bf16.bf16 {%0, %1, %2, %3, %4, %5, %6, %7}, {%8, %9, %10, %11}, %12, 1, 1, 1, 1;"
    : "+f"(d[0]), "+f"(d[1]), "+f"(d[2]), "+f"(d[3]), "+f"(d[4]), "+f"(d[5]), "+f"(d[6]), "+f"(d[7])
    : "r"(a0), "r"(a1), "r"(a2), "r"(a3), "l"(db));
}
DEVI void wgmma_pv0(float (&d)[8], uint32_t a0, uint32_t a1, uint32_t a2, uint32_t a3, uint64_t db) {
  asm volatile("wgmma.mma_async.sync.aligned.m64n16k16.f32.bf16.bf16 {%0, %1, %2, %3, %4, %5, %6, %7}, {%8, %9, %10, %11}, %12, 0, 1, 1, 1;"
    : "=f"(d[0]), "=f"(d[1]), "=f"(d[2]), "=f"(d[3]), "=f"(d[4]), "=f"(d[5]), "=f"(d[6]), "=f"(d[7])
    : "r"(a0), "r"(a1), "r"(a2), "r"(a3), "l"(db));
}

template <int N> DEVI void wgmma_ss(float (&d)[N / 2], uint64_t da, uint64_t db) {
  if constexpr (N == 64) wgmma_ss_n64(d, da, db);
  else if constexpr (N == 128) wgmma_ss_n128(d, da, db);
  else if constexpr (N == 192) wgmma_ss_n192(d, da, db);
  else wgmma_ss_n256(d, da, db);
}

DEVI int oh_chunk(int j, int i, int& need) {
  if (j & 1) {
    if (i >= 3 && i < 7) { need = 16 + 2 * (i - 3); return 24 + (i - 3); }
    if (i >= 7) i -= 4;
  }
  const int g = i / 3, o = (j + 2 * g) & 7;
  need = o;
  return 3 * o + (i - 3 * g);
}

struct Ctx {
  uint32_t sbase, bars, peer, t0, a16, b16;
  int wg, lane;
  int ai, bi; uint32_t aph, bph;
  int brem;
  int pa, pb;
};

DEVI void release_prev(Ctx& c) {
  if (c.pb >= 0) {
    if (c.lane == 0) mbar_arrive(c.bars + 8 * (BAR_EMPTYB + c.pb));
    if (c.lane == 1) mbar_arrive_cluster(c.bars + 8 * (BAR_EMPTYB + c.pb), c.peer);
  }
  if (c.pa >= 0 && c.lane == 2) mbar_arrive(c.bars + 8 * (BAR_EMPTYA + c.pa));
}

DEVI void gemm_wait(Ctx& c) {
  asm volatile("{ .reg .pred p, q; .reg .u32 c;\n"
               "WAIT_%=:\n"
               "mbarrier.try_wait.parity.shared::cta.b64 p, [%0], %1;\n"
               "mbarrier.try_wait.parity.shared::cta.b64 q, [%2], %3;\n"
               "and.pred p, p, q;\n"
               "@p bra DONE_%=;\n"
               "mov.u32 c, %%clock; sub.u32 c, c, %4; setp.lt.u32 p, c, %5;\n"
               "@p bra WAIT_%=;\n"
               "DONE_%=: }" ::"r"(c.bars + 8 * (BAR_FULLA + c.ai)), "r"((c.aph >> c.ai) & 1), "r"(c.bars + 8 * (BAR_FULLB + c.bi)), "r"(c.bph), "r"(c.t0), "n"(TIMEOUT) : "memory");
}
template <int N>
DEVI void gemm_group(float (&acc)[N / 2], Ctx& c, int g, int& npa, int& npb) {
  const uint32_t a16 = c.a16 + c.ai * (SLOT >> 4);
  const uint32_t b16 = c.b16 + c.bi * (SLOT >> 4);
  bool adv;
  if constexpr (N >= 192) {
    const uint32_t a2 = a16 + (g & 1) * 4;
    wgmma_ss<N>(acc, desc_sw128<16>(a2), desc_sw128<2048>(b16));
    wgmma_ss<N>(acc, desc_sw128<16>(a2 + 2), desc_sw128<2048>(b16 + 512));
    adv = g & 1;
  } else {
#pragma unroll
    for (int s = 0; s < 4; s++) wgmma_ss<N>(acc, desc_sw128<16>(a16 + s * 2), desc_sw128<4096>(b16 + (s >> 1) * 512 + (s & 1) * 128));
    adv = true;
  }
  wgmma_commit();
  npb = c.brem > 0 ? c.bi : -1;
  c.brem--;
  if (++c.bi == NB) { c.bi = 0; c.bph ^= 1; }
  npa = -1;
  if (adv) { npa = c.ai; c.aph ^= 1u << c.ai; if (++c.ai == (N >= 192 ? NA : NA2)) c.ai = 0; }
}

template <int N>
DEVI void bare_groups(float (&acc)[N / 2], Ctx& c, int g0, int g1) {
  for (int g = g0; g < g1; g++) {
    int npa, npb;
    gemm_wait(c);
    wgmma_fence();
    gemm_group<N>(acc, c, g, npa, npb);
    wgmma_wait<1>();
    release_prev(c);
    c.pa = npa; c.pb = npb;
  }
}
DEVI void drain(Ctx& c) {
  wgmma_wait<0>();
  release_prev(c);
  c.pa = c.pb = -1;
}

constexpr float SC = 0.25f * 1.4426950408889634f;

#define ONCE _Pragma("unroll 1") for (unsigned once_ = 0; once_ < gridDim.y; once_++)

struct Attn {
  uint32_t q[4][4];
  uint32_t nm[4];
  float g0, g1;
  int cmin;
  int rowc;
};

template <int O0, int NS>
DEVI void kill32(float (&S)[NS]) {
#pragma unroll
  for (int i = 0; i < 32; i++) S[O0 + i] = __int_as_float(0xff800000);
}
DEVI void row_max(const float (&S)[64], float& x0, float& x1) {
#pragma unroll
  for (int n = 0; n < 16; n++) {
    x0 = fmaxf(x0, fmaxf(S[4 * n], S[4 * n + 1])); x1 = fmaxf(x1, fmaxf(S[4 * n + 2], S[4 * n + 3]));
  }
}
template <int K, bool PRE = false>
DEVI void exp8(const float (&S)[64], uint32_t (&P)[4], float n0, float n1, float (&l)[4]) {
  float e[8];
#pragma unroll
  for (int i = 0; i < 8; i++) e[i] = ex2(PRE ? S[8 * K + i] : fmaf(S[8 * K + i], SC, (i & 2) ? n1 : n0));
  l[0] += e[0]; l[1] += e[1]; l[2] += e[2]; l[3] += e[3];
  l[0] += e[4]; l[1] += e[5]; l[2] += e[6]; l[3] += e[7];
#pragma unroll
  for (int i = 0; i < 4; i++) P[i] = pack_bf16(e[2 * i], e[2 * i + 1]) | (__float_as_uint(l[i]) & blockIdx.y);
}
DEVI void merge_fl(float (&S)[64], const float (&F)[32], int rowc) {
#pragma unroll
  for (int n = 0; n < 8; n++) {
    if (n * 8 > rowc) S[32 + 4 * n] = F[4 * n];
    if (n * 8 + 1 > rowc) S[32 + 4 * n + 1] = F[4 * n + 1];
    if (n * 8 > rowc + 8) S[32 + 4 * n + 2] = F[4 * n + 2];
    if (n * 8 + 1 > rowc + 8) S[32 + 4 * n + 3] = F[4 * n + 3];
  }
}
DEVI bool wg_any(int wg, bool v) {
  uint32_t r;
  if (wg == 0) asm volatile("{ .reg .pred p, q; setp.ne.u32 p, %1, 0; bar.red.or.pred q, 1, 128, p; selp.u32 %0, 1, 0, q; }" : "=r"(r) : "r"((uint32_t)v) : "memory");
  else asm volatile("{ .reg .pred p, q; setp.ne.u32 p, %1, 0; bar.red.or.pred q, 2, 128, p; selp.u32 %0, 1, 0, q; }" : "=r"(r) : "r"((uint32_t)v) : "memory");
  return r != 0;
}

template <bool FIRST> DEVI void pv_step(float (&O)[8], const uint32_t (&P)[4], uint32_t v16) {
  wgmma_wait<0>();
  wgmma_fence();
  if (FIRST) wgmma_pv0(O, P[0], P[1], P[2], P[3], desc_sw64(v16)); else wgmma_pv(O, P[0], P[1], P[2], P[3], desc_sw64(v16));
  wgmma_commit();
}
template <int K> DEVI void pv_merged(float (&O)[8], const uint32_t (&P)[4], uint32_t (&PL)[4], uint32_t (&PF)[4], int rowc, uint32_t kb) {
#pragma unroll
  for (int i = 0; i < 4; i++) {
    const int col = (K - 4) * 16 + (i >> 1) * 8, r = rowc + (i & 1) * 8;
    const uint32_t m = (col > r ? 0xFFFFu : 0u) | (col + 1 > r ? 0xFFFF0000u : 0u);
    PF[i] = P[i] & m; PL[i] = P[i] & ~m;
  }
  wgmma_wait<0>();
  wgmma_fence();
  wgmma_pv(O, PL[0], PL[1], PL[2], PL[3], desc_sw64(kb + 3 * 256 + 2 + K * 64));
  wgmma_pv(O, PF[0], PF[1], PF[2], PF[3], desc_sw64(kb + 2 + (K - 4) * 64));
  wgmma_commit();
}
DEVI void qk_a(float (&S)[64], float (&F)[32], const uint32_t (&q)[4], uint32_t kb) {
  wgmma_fence();
  wgmma_qk128(S, q[0], q[1], q[2], q[3], desc_sw64(kb + 3 * 256));
  wgmma_qk64(F, q[0], q[1], q[2], q[3], desc_sw64(kb));
}
DEVI void fix_a(float (&S)[64], float (&F)[32], const Attn& at) {
  if (at.cmin > 0) { kill32<0>(F); if (at.cmin > 3) kill32<0>(S); }
  merge_fl(S, F, at.rowc);
}
DEVI void scale64(float (&S)[64], float n0, float n1) {
#pragma unroll
  for (int i = 0; i < 64; i++) S[i] = fmaf(S[i], SC, (i & 2) ? n1 : n0);
}
DEVI void fix_b(float (&S)[64], const Attn& at) {
  if (at.cmin > 1) { kill32<0>(S); if (at.cmin > 2) kill32<32>(S); }
}
DEVI void half_a(const float (&SA)[64], float (&SB)[64], float (&O)[8], float (&l)[4], const Attn& at, uint32_t kb, float n0, float n1) {
  uint32_t P[8][4], PL[4][4], PF[4][4];
  wgmma_fence();
  wgmma_qk128(SB, at.q[0][0], at.q[0][1], at.q[0][2], at.q[0][3], desc_sw64(kb + 256));
  wgmma_commit();
  const uint32_t v = kb + 3 * 256 + 2;
  exp8<0, true>(SA, P[0], n0, n1, l); exp8<1, true>(SA, P[1], n0, n1, l);
  pv_step<true>(O, P[0], v);         exp8<2, true>(SA, P[2], n0, n1, l);
  pv_step<false>(O, P[1], v + 64);   exp8<3, true>(SA, P[3], n0, n1, l);
  pv_step<false>(O, P[2], v + 128);  exp8<4, true>(SA, P[4], n0, n1, l);
  pv_step<false>(O, P[3], v + 192);  exp8<5, true>(SA, P[5], n0, n1, l);
  pv_merged<4>(O, P[4], PL[0], PF[0], at.rowc, kb); exp8<6, true>(SA, P[6], n0, n1, l);
  pv_merged<5>(O, P[5], PL[1], PF[1], at.rowc, kb); exp8<7, true>(SA, P[7], n0, n1, l);
  pv_merged<6>(O, P[6], PL[2], PF[2], at.rowc, kb);
  pv_merged<7>(O, P[7], PL[3], PF[3], at.rowc, kb);
  fix_b(SB, at);
}

DEVI void attention(const Ctx& c, Attn& at, int wi) {
  const uint32_t kvb = ((c.sbase & 0x3FFFF) + OFF_KV + c.wg * 4096) >> 4;
  float SA[64];
  float n0 = __uint_as_float(at.nm[0] << 16), n1 = __uint_as_float(at.nm[0] & 0xffff0000u);
  bool exact = false;
  mbar_wait(c.bars + 8 * BAR_KVFULL, 0, c.t0);
  {
    float F[32];
    qk_a(SA, F, at.q[0], kvb);
    wgmma_commit();
    wgmma_wait<0>();
    fix_a(SA, F, at);
    scale64(SA, n0, n1);
  }
  int h = 0;
#pragma unroll 1
  while (h < 4) {
    const uint32_t kb = kvb + (h & 1) * (KVBUF >> 4);
    const uint32_t kn = h == 3 ? kb : kvb + ((h & 1) ^ 1) * (KVBUF >> 4);
    float O[8], l[4] = {0.f, 0.f, 0.f, 0.f};
    float SN[64], F[32];
    {
      float SB[64];
      half_a(SA, SB, O, l, at, kb, n0, n1);
      uint32_t P[8][4];
      const uint32_t v = kb + 256 + 2;
      exp8<0>(SB, P[0], n0, n1, l); exp8<1>(SB, P[1], n0, n1, l);
      pv_step<false>(O, P[0], v);        exp8<2>(SB, P[2], n0, n1, l);
      pv_step<false>(O, P[1], v + 64);   exp8<3>(SB, P[3], n0, n1, l);
      pv_step<false>(O, P[2], v + 128);  exp8<4>(SB, P[4], n0, n1, l);
      if (h < 3) mbar_wait(c.bars + 8 * (BAR_KVFULL + ((h + 1) & 1)), (h + 1) >> 1, c.t0);
      wgmma_wait<0>();
      qk_a(SN, F, at.q[1], kn);
      wgmma_pv(O, P[3][0], P[3][1], P[3][2], P[3][3], desc_sw64(v + 192));
      wgmma_commit();
      ONCE { exp8<5>(SB, P[5], n0, n1, l); }
      pv_step<false>(O, P[4], v + 256);
      fix_a(SN, F, at);
      exp8<6>(SB, P[6], n0, n1, l);
      pv_step<false>(O, P[5], v + 320);
      scale64(SN, __uint_as_float(at.nm[1] << 16), __uint_as_float(at.nm[1] & 0xffff0000u));
      exp8<7>(SB, P[7], n0, n1, l);
      wgmma_wait<0>();
      wgmma_fence();
      wgmma_pv(O, P[6][0], P[6][1], P[6][2], P[6][3], desc_sw64(v + 384));
      wgmma_pv(O, P[7][0], P[7][1], P[7][2], P[7][3], desc_sw64(v + 448));
      wgmma_commit();
    }
    float l0 = l[0] + l[1], l1 = l[2] + l[3];
    l0 += __shfl_xor_sync(0xffffffffu, l0, 1); l1 += __shfl_xor_sync(0xffffffffu, l1, 1);
    l0 += __shfl_xor_sync(0xffffffffu, l0, 2); l1 += __shfl_xor_sync(0xffffffffu, l1, 2);
    const bool bad = !exact && !(l0 > 1e-6f && l0 < 1e18f && l1 > 1e-6f && l1 < 1e18f);
    const bool redo = wg_any(c.wg, bad);
    wgmma_wait<0>();
    if (redo) {
      float x0 = __int_as_float(0xff800000), x1 = x0;
      {
        float T[64];
        wgmma_fence();
        wgmma_qk128(T, at.q[0][0], at.q[0][1], at.q[0][2], at.q[0][3], desc_sw64(kb + 256));
        wgmma_commit();
        wgmma_wait<0>();
        fix_b(T, at);
        row_max(T, x0, x1);
      }
      float T[64], G[32];
      qk_a(T, G, at.q[0], kb);
      wgmma_commit();
      wgmma_wait<0>();
      fix_a(T, G, at);
      row_max(T, x0, x1);
      x0 = fmaxf(x0, __shfl_xor_sync(0xffffffffu, x0, 1)); x1 = fmaxf(x1, __shfl_xor_sync(0xffffffffu, x1, 1));
      x0 = fmaxf(x0, __shfl_xor_sync(0xffffffffu, x0, 2)); x1 = fmaxf(x1, __shfl_xor_sync(0xffffffffu, x1, 2));
      n0 = -x0 * SC; n1 = -x1 * SC;
      scale64(T, n0, n1);
#pragma unroll
      for (int i = 0; i < 64; i++) SA[i] = T[i];
      exact = true;
    } else {
      if (c.lane == 0) mbar_arrive(c.bars + 8 * (BAR_KVEMPTY + (h & 1)));
      const float c0 = __fdividef(at.g0, l0), c1 = __fdividef(at.g1, l1);
      const uint32_t ost = c.sbase + OFF_A + (15 % NA) * SLOT + c.wg * 8192 + h * 2048;
      const int mi = c.lane >> 3;
      const int srow = wi * 16 + (c.lane & 7) + 8 * (mi & 1);
      stsm_x4(ost + srow * 32 + (mi >> 1) * 16, pack_bf16(O[0] * c0, O[1] * c0), pack_bf16(O[2] * c1, O[3] * c1),
              pack_bf16(O[4] * c0, O[5] * c0), pack_bf16(O[6] * c1, O[7] * c1));
      fence_async_smem();
      __syncwarp();
      if (c.lane == 0) mbar_arrive(c.bars + 8 * (BAR_STG + c.wg));
      n0 = __uint_as_float(at.nm[1] << 16); n1 = __uint_as_float(at.nm[1] & 0xffff0000u);
#pragma unroll
      for (int i = 0; i < 64; i++) SA[i] = SN[i];
#pragma unroll
      for (int i = 0; i < 4; i++) { at.q[0][i] = at.q[1][i]; at.q[1][i] = at.q[2][i]; at.q[2][i] = at.q[3][i]; }
      at.nm[1] = at.nm[2]; at.nm[2] = at.nm[3];
      exact = false;
      h++;
    }
  }
}

template <int CH, int NACC>
DEVI void store_h_chunk(const float (&acc)[NACC], uint32_t base  , int lane, float s0, float s1) {
  const int mi = lane >> 3;
#pragma unroll
  for (int tp = 0; tp < 4; tp++) {
    const int t = CH * 8 + tp * 2;
    const uint32_t r0 = pack_bf16(fmaxf(acc[4 * t + 0], 0.f) * s0, fmaxf(acc[4 * t + 1], 0.f) * s0);
    const uint32_t r1 = pack_bf16(fmaxf(acc[4 * t + 2], 0.f) * s1, fmaxf(acc[4 * t + 3], 0.f) * s1);
    const uint32_t r2 = pack_bf16(fmaxf(acc[4 * t + 4], 0.f) * s0, fmaxf(acc[4 * t + 5], 0.f) * s0);
    const uint32_t r3 = pack_bf16(fmaxf(acc[4 * t + 6], 0.f) * s1, fmaxf(acc[4 * t + 7], 0.f) * s1);
    stsm_x4(base + (((tp * 2 + (mi >> 1)) ^ (lane & 7)) << 4), r0, r1, r2, r3);
  }
}

DEVI void get_gate(Attn& at, const Ctx& c, const unsigned* gflag, unsigned gtgt, const float* gp) {
  if (c.lane == 0) flag_wait(gflag, gtgt, c.t0);
  __syncwarp();
  at.g0 = ld_relaxed_f(gp); at.g1 = ld_relaxed_f(gp + 8);
}

template <int N>
DEVI void phase_q(Ctx& c, Attn& at, int warp, const unsigned* gflag, unsigned gtgt, const float* gp) {
  float acc[N / 2];
#pragma unroll
  for (int i = 0; i < N / 2; i++) acc[i] = 0.f;
  bare_groups<N>(acc, c, 0, 14);
  if constexpr (N == 256) get_gate(at, c, gflag, gtgt, gp);
  bare_groups<N>(acc, c, 14, 16);
  drain(c);
  const int lane = c.lane, mi = lane >> 3;
  const int row = warp * 16 + (lane & 7) + 8 * (mi & 1);
  const int sw = (row >> 1) & 3;
#pragma unroll
  for (int hh = 0; hh < 4; hh++) {
    const uint32_t base = c.sbase + OFF_KV + hh * 8192 + row * 64;
#pragma unroll
    for (int kv = 0; kv < 2; kv++) {
      const int t = 8 + kv * 8 + 2 * hh;
      stsm_x4(base + (((kv * 2 + (mi >> 1)) ^ sw) << 4),
              pack_bf16(acc[4 * t + 0], acc[4 * t + 1]), pack_bf16(acc[4 * t + 2], acc[4 * t + 3]),
              pack_bf16(acc[4 * t + 4], acc[4 * t + 5]), pack_bf16(acc[4 * t + 6], acc[4 * t + 7]));
    }
  }
  fence_async_smem();
  __syncwarp();
  if (lane == 0) mbar_arrive(c.bars + 8 * (BAR_STG + c.wg));
  if constexpr (N == 256) {
    store_h_chunk<3>(acc, c.sbase + OFF_KV + 32768 + row * 128, lane, 1.f - at.g0, 1.f - at.g1);
    fence_async_smem();
    __syncwarp();
    if (lane == 0) mbar_arrive(c.bars + 8 * (BAR_STE + c.wg));
  }
#pragma unroll
  for (int hh = 0; hh < 4; hh++) {
#pragma unroll
    for (int i = 0; i < 4; i++) at.q[hh][i] = pack_bf16(acc[8 * hh + 2 * i], acc[8 * hh + 2 * i + 1]);
    const float* q = &acc[8 * hh];
    const float* k = &acc[32 + 8 * hh];
    float d0 = q[0] * k[0] + q[1] * k[1] + q[4] * k[4] + q[5] * k[5], d1 = q[2] * k[2] + q[3] * k[3] + q[6] * k[6] + q[7] * k[7];
    d0 += __shfl_xor_sync(0xffffffffu, d0, 1); d1 += __shfl_xor_sync(0xffffffffu, d1, 1);
    d0 += __shfl_xor_sync(0xffffffffu, d0, 2); d1 += __shfl_xor_sync(0xffffffffu, d1, 2);
    at.nm[hh] = pack_bf16(-d0 * SC, -d1 * SC);
  }
}

DEVI void first_loads(const Params& P, uint32_t sbase, int e, int j, int rb) {
  const uint32_t bars = sbase + OFF_BAR, fb = bars + 8 * (BAR_FULLB + e), fa = bars + 8 * (BAR_FULLA + e);
  mbar_expect_tx(fa, 16384);
  mbar_expect_tx(fb, (j & 1) ? 12288 : 16384);
  if (e == 0) tma_load_2d(sbase + OFF_A, &P.tmX, 0, rb * 128, fa);
#pragma unroll
  for (int r = 0; r < 2; r++) {
    tma_load_3d(sbase + OFF_B + e * SLOT + r * 8192, &P.tmWqkv, 64 * j, e * 32 + r * 16, 0, fb);
    if (!(j & 1)) tma_load_3d(sbase + OFF_B + e * SLOT + r * 8192 + 6144, &P.tmW1a, 0, e * 32 + r * 16, 24 + (j >> 1), fb);
  }
  if (e == 1) tma_load_2d(sbase + OFF_A + SLOT, &P.tmX, 64, rb * 128, fa);
}

__global__ void __cluster_dims__(2, 1, 1) __launch_bounds__(384, 1) fused_kernel(const __grid_constant__ Params P) {
  extern __shared__ uint8_t smem_raw[];
  const uint32_t sbase = (smem_u32(smem_raw) + 1023u) & ~1023u;
  const uint32_t bars = sbase + OFF_BAR;
  const int tid = threadIdx.x, warp = tid >> 5, lane = tid & 31;
  const uint32_t rank = blockIdx.x & 1, peer = rank ^ 1;
  const int j = (blockIdx.x >> 1) & 7, rb = ((blockIdx.x >> 4) << 1) | rank;
  const uint32_t t0 = clk32();

  const int typeB = j & 1;
  if (tid == 288) {
    for (int s = 0; s < NA2; s++) mbar_init(bars + 8 * (BAR_FULLA + s), 1);
    for (int s = 0; s < NB; s++) mbar_init(bars + 8 * (BAR_FULLB + s), 1);
    fence_async_smem();
  } else if (tid < 10) {
    asm volatile("prefetch.tensormap [%0];" ::"l"(&P.tmX + tid) : "memory");
  } else if (tid == 256) {
    for (int s = 0; s < NA2; s++) mbar_init(bars + 8 * (BAR_EMPTYA + s), 10);
    for (int s = 0; s < NB; s++) mbar_init(bars + 8 * (BAR_EMPTYB + s), 16);
  } else if (tid == 320) {
    for (int s = 0; s < 2; s++) { mbar_init(bars + 8 * (BAR_KVFULL + s), 1); mbar_init(bars + 8 * (BAR_KVEMPTY + s), 8); mbar_init(bars + 8 * (BAR_STG + s), 4); mbar_init(bars + 8 * (BAR_STE + s), 4); }
    mbar_init(bars + 8 * BAR_PIN, 1); mbar_init(bars + 8 * BAR_GATE, 1); mbar_init(bars + 8 * (BAR_GATE + 1), 1);
  }
  if (tid >= 256 && lane == 0) asm volatile("fence.mbarrier_init.release.cluster;" ::: "memory");
  const unsigned ep1 = ld_relaxed(&g_epoch) + 1;
  __syncwarp();
  cluster_arrive();
  if (tid == 288) { first_loads(P, sbase, 0, j, rb); first_loads(P, sbase, 1, j, rb); }
  __syncwarp();

  const int on = 12 + 4 * typeB;

  if (warp < 8) {
    asm volatile("setmaxnreg.inc.sync.aligned.u32 232;");
    cluster_wait();
    const int wg = __shfl_sync(0xffffffffu, warp >> 2, 0), wi = warp & 3;
    Ctx c{sbase, bars, peer, t0, ((sbase & 0x3FFFF) + OFF_A + wg * 8192) >> 4, ((sbase & 0x3FFFF) + OFF_B) >> 4, wg, lane, 0, 0, 0u, 0u, 32 + on + 4 - NB, -1, -1};
    Attn at;
    at.cmin = 4 - 2 * rb - wg;
    at.rowc = wi * 16 + (lane >> 2) - (lane & 3) * 2;
    const int row0 = rb * 128 + warp * 16 + (lane >> 2);
    if (tid == 0) TR(0);
    if (typeB) phase_q<192>(c, at, warp, &g_flag_g[rb * FS], ep1 * 16, &g_gate[row0]);
    else phase_q<256>(c, at, warp, &g_flag_g[rb * FS], ep1 * 16, &g_gate[row0]);
    if (tid == 0) TR(2);
    {
      float acc[96];
#pragma unroll
      for (int i = 0; i < 96; i++) acc[i] = 0.f;
      bare_groups<192>(acc, c, 0, 8);
      if (typeB) get_gate(at, c, &g_flag_g[rb * FS], ep1 * 16, &g_gate[row0]);
      bare_groups<192>(acc, c, 8, 16);
      drain(c);
      if (tid == 0) TR(1);
      const uint32_t rowoff = (warp * 16 + (lane & 7) + 8 * ((lane >> 3) & 1)) * 128;
      const float s0 = 1.f - at.g0, s1 = 1.f - at.g1;
      constexpr int e0 = 16 % NA, e1 = 17 % NA, e2 = 18 % NA;
      mbar_wait(bars + 8 * (BAR_FULLA + e0), (16 / NA) & 1, t0);
      store_h_chunk<0>(acc, sbase + OFF_A + e0 * SLOT + rowoff, lane, s0, s1);
      mbar_wait(bars + 8 * (BAR_FULLA + e1), (17 / NA) & 1, t0);
      store_h_chunk<1>(acc, sbase + OFF_A + e1 * SLOT + rowoff, lane, s0, s1);
      mbar_wait(bars + 8 * (BAR_FULLA + e2), (18 / NA) & 1, t0);
      store_h_chunk<2>(acc, sbase + OFF_A + e2 * SLOT + rowoff, lane, s0, s1);
    }
    fence_async_smem();
    wg_bar(wg);
    if (lane == 0) mbar_arrive(bars + 8 * (BAR_STG + wg));
    if (tid == 0) TR(4);
    attention(c, at, wi);
    if (tid == 0) TR(3);
    float own[32];
    {
      float acc[64];
#pragma unroll
      for (int i = 0; i < 64; i++) acc[i] = 0.f;
      bare_groups<128>(acc, c, 0, on);
      drain(c);
      if (tid == 0) TR(5);
      named_bar<3>(256);
      const uint32_t pst = sbase + OFF_B + ((30 + on) % NB) * SLOT + wg * 8192 + (tid & 127) * 16;
#pragma unroll
      for (int i = 0; i < 4; i++) {
        uint32_t r[4];
#pragma unroll
        for (int k = 0; k < 4; k++) {
          const int idx = 8 * i + 2 * k;
          const float lo = typeB ? acc[idx] : acc[32 + idx], hi = typeB ? acc[idx + 1] : acc[32 + idx + 1];
          r[k] = pack_bf16(lo, hi);
        }
        sts128(pst + i * 2048, r[0], r[1], r[2], r[3]);
      }
#pragma unroll
      for (int i = 0; i < 32; i++) own[i] = typeB ? acc[32 + i] : acc[i];
      fence_async_smem();
      __syncwarp();
      if (lane == 0) mbar_arrive(bars + 8 * (BAR_STG + wg));
    }
    for (int g = 0; g < 8; g++) {
      const uint32_t a16 = c.a16 + c.ai * (SLOT >> 4);
      const uint32_t b16 = c.b16 + c.bi * (SLOT >> 4) + (g & 1) * 512;
      gemm_wait(c);
      wgmma_fence();
#pragma unroll
      for (int s = 0; s < 4; s++) wgmma_ss<64>(own, desc_sw128<16>(a16 + s * 2), desc_sw128<2048>(b16 + s * 128));
      wgmma_commit();
      if (++c.ai == NA2) c.ai = 0;
      if (g & 1) { if (++c.bi == NB) { c.bi = 0; c.bph ^= 1; } }
    }
    wgmma_wait<0>();
    if (tid == 0) TR(6);
    mbar_wait(bars + 8 * BAR_PIN, 0, t0);
    if (tid == 0) TR(7);
    {
      const uint32_t pin = sbase + OFF_B + ((31 + on) % NB) * SLOT + wg * 8192 + (tid & 127) * 16;
      wg_bar(wg);
      const uint32_t ob = sbase + OFF_A + wg * 8192;
      const uint32_t orow = ob + (wi * 16 + (lane & 7) + 8 * ((lane >> 3) & 1)) * 128;
#pragma unroll
      for (int i = 0; i < 4; i++) {
        const uint4 v = lds128(pin + i * 2048);
        const uint32_t r[4] = {v.x, v.y, v.z, v.w};
        uint32_t o[4];
#pragma unroll
        for (int k = 0; k < 4; k++) {
          const int idx = 8 * i + 2 * k;
          o[k] = pack_bf16(own[idx] + __uint_as_float(r[k] << 16), own[idx + 1] + __uint_as_float(r[k] & 0xffff0000u));
        }
        stsm_x4(orow + (((i * 2 + (lane >> 4)) ^ (lane & 7)) << 4), o[0], o[1], o[2], o[3]);
      }
      fence_async_smem();
      __syncwarp();
      if (lane == 0) {
        tma_store_2d(&P.tmOut, j * 64, rb * 128 + warp * 16, ob + wi * 2048);
        bulk_commit(); bulk_wait_all();
      }
    }
    if (tid == 0) TR(8);
  } else {
    asm volatile("setmaxnreg.dec.sync.aligned.u32 40;");
    if (warp == 8) {
      __syncwarp();
      cluster_wait();
      if (lane == 0) {
        int bi = 2; uint32_t bph = 1;
        const int nb = 32 + on + 4;
        for (int eb = 2; eb < nb; eb++) {
          if (eb == 4 || eb == 6) {
            for (int ea = eb - 2 - (eb == 6 ? 1 : 0); ea < (eb == 4 ? 3 : NA); ea++) {
              mbar_expect_tx(bars + 8 * (BAR_FULLA + ea), 16384);
              tma_load_2d(sbase + OFF_A + ea * SLOT, &P.tmX, ea * 64, rb * 128, bars + 8 * (BAR_FULLA + ea));
            }
          }
          const uint32_t fb = bars + 8 * (BAR_FULLB + bi), dst = sbase + OFF_B + bi * SLOT + rank * 8192;
          mbar_wait(bars + 8 * (BAR_EMPTYB + bi), bph, t0);
          if (eb < 16) {
            mbar_expect_tx(fb, typeB ? 12288 : 16384);
            tma_load_3d_mc(dst, &P.tmWqkv, 64 * j, eb * 32 + rank * 16, 0, fb);
            if (!typeB) tma_load_3d_mc(dst + 6144, &P.tmW1a, 0, eb * 32 + rank * 16, 24 + (j >> 1), fb);
          }
          else if (eb < 32) { mbar_expect_tx(fb, 12288); tma_load_3d_mc(dst, &P.tmW1b, 0, (eb - 16) * 32 + rank * 16, 3 * j, fb); }
          else if (eb < 32 + on) { int ow; const int ch = oh_chunk(j, eb - 32, ow); mbar_expect_tx(fb, 16384); tma_load_3d_mc(dst, &P.tmW2, 0, ch * 64 + rank * 32, (j >> 1) * 2, fb); }
          else { mbar_expect_tx(fb, 16384); tma_load_4d_mc(dst, &P.tmWo, 64 * j, 0, eb - 32 - on, rank * 4, fb); }
          if (++bi == NB) { bi = 0; bph ^= 1; }
          if (eb == PFAT) {
            const int b = blockIdx.x;
            l2_prefetch((const uint8_t*)P.w1 + b * 14336, 14336);
            l2_prefetch((const uint8_t*)P.w2 + b * 14336, 14336);
            l2_prefetch((const uint8_t*)P.wo + b * 4096, 4096);
          }
        }
      }
    } else if (warp == 9) {
      cluster_wait();
      if (lane == 0) {
        for (int ea = 0; ea < NA; ea++) mbar_arrive_n(bars + 8 * (BAR_EMPTYA + ea), 2);
        int ai = 0; uint32_t aph = 0xE0;
        const int na = 16 + on + 8;
        unsigned ready = 0;
        for (int ea = NA; ea < na; ea++) {
          const uint32_t fb = bars + 8 * (BAR_FULLA + ai), dst = sbase + OFF_A + ai * SLOT;
          int ch = ea & 7, need = -1;
          if (ea >= 16 + on) { need = 8 + ea - 16 - on; ch = 20 + need; }
          else if (ea >= 19) ch = oh_chunk(j, ea - 16, need);
          if (need >= 0 && !((ready >> need) & 1)) {
            const unsigned* fp = need < 8 ? &g_flag_h[rb * 8 * FS] : need < 16 ? &g_flag_o[rb * 8 * FS] : &g_flag_e[rb * 8 * FS];
            const unsigned tgt = (need & 8) ? ep1 * 8 : ep1 * 2;
            do {
              unsigned v[8];
#pragma unroll
              for (int i = 0; i < 8; i++) v[i] = ld_relaxed(fp + i * FS);
#pragma unroll
              for (int i = 0; i < 8; i++) if ((int)(v[i] - tgt) >= 0) ready |= 1u << (i + (need & 24));
            } while (!((ready >> need) & 1) && clk32() - t0 < TIMEOUT);
            fence_async_global();
          }
          if (ea == 20 || ea == 21) {
            mbar_wait(bars + 8 * (BAR_KVEMPTY + ea - 20), 0, t0); mbar_wait(bars + 8 * (BAR_KVEMPTY + ea - 20), 1, t0);
          }
          mbar_wait(bars + 8 * (BAR_EMPTYA + ai), (aph >> ai) & 1, t0);
          if (ea >= 16 && ea < 19) mbar_arrive(fb);
          else {
            if (ea != 15) mbar_arrive_n(bars + 8 * (BAR_EMPTYA + ai), 2);
            mbar_expect_tx(fb, 16384);
            tma_load_2d(dst, ea < 16 ? &P.tmX : &P.tmHO, ch * 64, rb * 128, fb);
          }
          TR(24 + ea);
          aph ^= 1u << ai;
          if (++ai == (ea < 16 ? NA : NA2)) ai = 0;
        }
      }
    } else {
      const int wg = warp - 10;
      cluster_wait();
      {
        const int rowg = rb * 128 + j * 16 + wg * 8;
        const uint32_t xs = sbase + OFF_KV + 32768 + wg * 8192;
        if (lane == 0) {
          mbar_wait(bars + 8 * (BAR_FULLB + 1), 0, t0);
          mbar_expect_tx(bars + 8 * (BAR_GATE + wg), 8192);
          bulk_load(xs, P.x + (size_t)rowg * DM, 8192, bars + 8 * (BAR_GATE + wg));
        }
        const uint4* gw = (const uint4*)P.gate_w;
        const uint4 w0 = __ldg(gw + lane), w1 = __ldg(gw + 32 + lane);
        const uint32_t wa[8] = {w0.x, w0.y, w0.z, w0.w, w1.x, w1.y, w1.z, w1.w};
        mbar_wait(bars + 8 * (BAR_GATE + wg), 0, t0);
        float zz = 0.f;
#pragma unroll 1
        for (int i = 0; i < 8; i++) {
          const uint4 x0 = lds128(xs + i * 1024 + lane * 16), x1 = lds128(xs + i * 1024 + 512 + lane * 16);
          const uint32_t xa[8] = {x0.x, x0.y, x0.z, x0.w, x1.x, x1.y, x1.z, x1.w};
          float z = 0.f;
#pragma unroll
          for (int e = 0; e < 8; e++) {
            z = fmaf(__uint_as_float(xa[e] << 16), __uint_as_float(wa[e] << 16), z);
            z = fmaf(__uint_as_float(xa[e] & 0xffff0000u), __uint_as_float(wa[e] & 0xffff0000u), z);
          }
#pragma unroll
          for (int o = 16; o > 0; o >>= 1) z += __shfl_xor_sync(0xffffffffu, z, o);
          if (lane == i) zz = z;
        }
        if (lane < 8) asm volatile("st.shared.f32 [%0], %1;" ::"r"(sbase + OFF_GST + wg * 32 + lane * 4), "f"(1.f / (1.f + __expf(-zz))) : "memory");
        fence_async_smem();
        __syncwarp();
        if (lane == 0) {
          bulk_store(&g_gate[rowg], sbase + OFF_GST + wg * 32, 32);
          bulk_commit(); bulk_wait_all();
          flag_add(&g_flag_g[rb * FS]);
          if (wg == 0) TR(10);
        }
      }
      if (lane == 0) {
        const uint32_t stg = bars + 8 * (BAR_STG + wg);
        mbar_wait(stg, 0, t0);
        for (int hh = 0; hh < 4; hh++)
          bulk_store(g_kv + ((size_t)(4 * j + hh) * SEQ + rb * 128 + wg * 64) * 64, sbase + OFF_KV + hh * 8192 + wg * 4096, 4096);
        bulk_commit(); bulk_wait_all();
        flag_add(&g_flag_kv[(rb * 8 + j) * FS]);
        if (wg == 0) TR(21);
        if (!typeB) {
          mbar_wait(bars + 8 * (BAR_STE + wg), 0, t0);
          tma_store_2d(&P.tmHOs, (24 + (j >> 1)) * 64, rb * 128 + wg * 64, sbase + OFF_KV + 32768 + wg * 8192);
          bulk_commit(); bulk_wait_all();
          flag_add(&g_flag_e[(rb * 8 + j) * FS]);
          if (wg == 1) flag_wait(&g_flag_e[(rb * 8 + j) * FS], ep1 * 2, t0);
        }
        const int nblk = rb >= 2 ? 3 : rb + 1;
        const uint32_t kvbytes = nblk * 8192;
        const uint8_t* kvsrc = g_kv + ((size_t)(4 * j) * SEQ + (rb + 1 - nblk) * 128) * 64;
        const uint32_t kvdst = sbase + OFF_KV + wg * KVBUF + (3 - nblk) * 8192;
        {
          const unsigned* f0 = &g_flag_kv[(rb * 8 + j) * FS];
          const unsigned* f1 = rb >= 1 ? f0 - 8 * FS : f0;
          const unsigned* f2 = rb >= 2 ? f0 - 16 * FS : f0;
          unsigned v0, v1, v2;
          do { v0 = ld_relaxed(f0); v1 = ld_relaxed(f1); v2 = ld_relaxed(f2); }
          while (((int)(v0 - ep1 * 2) < 0 || (int)(v1 - ep1 * 2) < 0 || (int)(v2 - ep1 * 2) < 0) && clk32() - t0 < TIMEOUT);
        }
        if (wg == 0) TR(11);
        fence_async_global();
        mbar_expect_tx(bars + 8 * (BAR_KVFULL + wg), kvbytes);
        bulk_load(kvdst, kvsrc + (size_t)wg * SEQ * 64, kvbytes, bars + 8 * (BAR_KVFULL + wg));
        for (int ev = 1; ev < 7; ev++) {
          mbar_wait(stg, ev & 1, t0);
          if (ev == 1) {
            for (int i = 0; i < 3; i++)
              tma_store_2d(&P.tmHOs, (3 * j + i) * 64, rb * 128 + wg * 64, sbase + OFF_A + ((16 + i) % NA) * SLOT + wg * 8192);
            bulk_commit(); bulk_wait_all();
            flag_add(&g_flag_h[(rb * 8 + j) * FS]);
            for (int i = 0; i < 3; i++) mbar_arrive(bars + 8 * (BAR_EMPTYA + (16 + i) % NA));
            if (wg == 0) TR(22);
            if (wg == 0) {
              const unsigned old = atomicAdd(&g_done, 1u);
              if (old == gridDim.x - 1) { g_done = 0; *(volatile unsigned*)&g_epoch = ep1; }
            }
          } else if (ev == 6) {
            bulk_store(g_part + (size_t)(rb * 8 + (j ^ 1)) * 16384 + wg * 8192, sbase + OFF_B + ((30 + on) % NB) * SLOT + wg * 8192, 8192);
            bulk_commit(); bulk_wait_all();
            flag_add(&g_flag_p[(rb * 8 + (j ^ 1)) * FS]);
            if (wg == 0) TR(23);
            if (wg == 1) {
              flag_wait(&g_flag_p[(rb * 8 + j) * FS], ep1 * 2, t0);
              fence_async_global();
              mbar_expect_tx(bars + 8 * BAR_PIN, 16384);
              bulk_load(sbase + OFF_B + ((31 + on) % NB) * SLOT, g_part + (size_t)(rb * 8 + j) * 16384, 16384, bars + 8 * BAR_PIN);
            }
          } else {
            const int hh = ev - 2;
            tma_store_2d(&P.tmOs, DFF + hh * 128 + j * 16, rb * 128 + wg * 64, sbase + OFF_A + (15 % NA) * SLOT + wg * 8192 + hh * 2048);
            bulk_commit();
            if (hh == wg) {
              mbar_wait(bars + 8 * (BAR_KVEMPTY + wg), 0, t0);
              mbar_expect_tx(bars + 8 * (BAR_KVFULL + wg), kvbytes);
              bulk_load(kvdst, kvsrc + (size_t)(wg + 2) * SEQ * 64, kvbytes, bars + 8 * (BAR_KVFULL + wg));
            }
            bulk_wait_all();
            flag_add(&g_flag_o[(rb * 8 + hh * 2 + (j >> 2)) * FS]);
            if (hh == 3) mbar_arrive(bars + 8 * (BAR_EMPTYA + 15 % NA));
            if (wg == 0) TR(12 + hh);
          }
        }
      }
    }
  }
}

typedef CUresult (*EncodeFn)(CUtensorMap*, CUtensorMapDataType, cuuint32_t, void*, const cuuint64_t*, const cuuint64_t*, const cuuint32_t*,
                             const cuuint32_t*, CUtensorMapInterleave, CUtensorMapSwizzle, CUtensorMapL2promotion, CUtensorMapFloatOOBfill);

void make_map(EncodeFn enc, CUtensorMap* m, const void* ptr, int rank, const cuuint64_t* dims, const cuuint64_t* strides, const cuuint32_t* box,
              CUtensorMapSwizzle sw = CU_TENSOR_MAP_SWIZZLE_128B) {
  cuuint32_t es[4] = {1, 1, 1, 1};
  enc(m, CU_TENSOR_MAP_DATA_TYPE_BFLOAT16, rank, const_cast<void*>(ptr), dims, strides, box, es, CU_TENSOR_MAP_INTERLEAVE_NONE, sw,
      CU_TENSOR_MAP_L2_PROMOTION_L2_256B, CU_TENSOR_MAP_FLOAT_OOB_FILL_NONE);
}

}

extern "C" void kernel_launch(void* const* d_in, const int* in_sizes, int n_in, void* d_out, int out_size) {
  (void)in_sizes; (void)n_in; (void)out_size;
  static EncodeFn enc = nullptr;
  static void* ho_ptr = nullptr;
  if (!enc) {
    void* fn = nullptr; cudaDriverEntryPointQueryResult st;
    cudaGetDriverEntryPoint("cuTensorMapEncodeTiled", &fn, cudaEnableDefault, &st);
    enc = (EncodeFn)fn;
    cudaGetSymbolAddress(&ho_ptr, g_ho);
    cudaFuncSetAttribute(fused_kernel, cudaFuncAttributeMaxDynamicSharedMemorySize, SMEM_BYTES);
  }
  const __nv_bfloat16* x = (const __nv_bfloat16*)d_in[0];
  const __nv_bfloat16* wqkv = (const __nv_bfloat16*)d_in[1];
  const __nv_bfloat16* wo = (const __nv_bfloat16*)d_in[2];
  const __nv_bfloat16* w1 = (const __nv_bfloat16*)d_in[4];
  const __nv_bfloat16* w2 = (const __nv_bfloat16*)d_in[5];
  const __nv_bfloat16* gate_w = (const __nv_bfloat16*)d_in[6];
  Params P;
  { cuuint64_t d[2] = {DM, SEQ}, s[1] = {DM * 2}; cuuint32_t b[2] = {64, 128}; make_map(enc, &P.tmX, x, 2, d, s, b); }
  { cuuint64_t d[3] = {512, 512, 3}, s[2] = {1536 * 2, 512 * 2}; cuuint32_t b[3] = {64, 16, 3}; make_map(enc, &P.tmWqkv, wqkv, 3, d, s, b); }
  { cuuint64_t d[3] = {64, 512, 28}, s[2] = {DFF * 2, 128}; cuuint32_t b[3] = {64, 16, 1}; make_map(enc, &P.tmW1a, w1, 3, d, s, b);
    b[2] = 3; make_map(enc, &P.tmW1b, w1, 3, d, s, b); }
  { cuuint64_t d[3] = {64, DFF, 8}, s[2] = {DM * 2, 128}; cuuint32_t b[3] = {64, 32, 2}; make_map(enc, &P.tmW2, w2, 3, d, s, b); }
  { cuuint64_t d[4] = {DM, 16, 4, 8}, s[3] = {DM * 2, 16 * DM * 2, 64 * DM * 2}; cuuint32_t b[4] = {64, 16, 1, 4}; make_map(enc, &P.tmWo, wo, 4, d, s, b); }
  { cuuint64_t d[2] = {KHO, SEQ}, s[1] = {KHO * 2}; cuuint32_t b[2] = {64, 128}; make_map(enc, &P.tmHO, ho_ptr, 2, d, s, b);
    b[1] = 64; make_map(enc, &P.tmHOs, ho_ptr, 2, d, s, b);
    b[0] = 16; make_map(enc, &P.tmOs, ho_ptr, 2, d, s, b, CU_TENSOR_MAP_SWIZZLE_NONE); }
  { cuuint64_t d[2] = {DM, SEQ}, s[1] = {DM * 2}; cuuint32_t b[2] = {64, 16}; make_map(enc, &P.tmOut, d_out, 2, d, s, b); }
  P.x = x; P.gate_w = gate_w; P.w1 = w1; P.w2 = w2; P.wo = wo; P.out = (__nv_bfloat16*)d_out;
  fused_kernel<<<128, 384, SMEM_BYTES>>>(P);
}
```

```cpp
#include <cuda_runtime.h>
#include <cuda_bf16.h>
#include <cuda.h>
#include <stdint.h>

#define DEVI __device__ __forceinline__

namespace {

constexpr int SEQ = 2048, DM = 512, DFF = 1792, KHO = 2304;
constexpr int NA = 5, NB = 6, SLOT = 16384, KVBUF = 24576;
constexpr int NA2 = 8;
constexpr int OFF_B = 0, OFF_A = NB * SLOT, OFF_KV = OFF_A + NA * SLOT, OFF_BAR = OFF_KV + 2 * KVBUF;
constexpr int OFF_GST = OFF_BAR + 512;
constexpr int SMEM_BYTES = OFF_BAR + 1024 + 1024;
constexpr uint32_t TIMEOUT = 1u << 28;
#define WAIT_HINT_NS 20000u
#define PFAT 8
#define HK0 2
#define HK1 1
constexpr int FS = 8;

constexpr int BAR_FULLA = 0, BAR_EMPTYA = BAR_FULLA + NA2, BAR_FULLB = BAR_EMPTYA + NA2, BAR_EMPTYB = BAR_FULLB + NB,
              BAR_KVFULL = BAR_EMPTYB + NB, BAR_KVEMPTY = BAR_KVFULL + 2, BAR_STG = BAR_KVEMPTY + 2, BAR_PIN = BAR_STG + 2, BAR_GATE = BAR_PIN + 1, BAR_STE = BAR_GATE + 2, BAR_ATTDONE = BAR_STE + 2;

__device__ __align__(1024) uint8_t g_kv[32 * SEQ * 64];
__device__ __align__(1024) __nv_bfloat16 g_ho[SEQ * KHO];
__device__ __align__(1024) uint8_t g_part[128 * 16384];
__device__ __align__(128) float g_gate[SEQ];
__device__ unsigned g_flag_kv[128 * FS], g_flag_h[128 * FS], g_flag_o[128 * FS], g_flag_g[16 * FS], g_flag_p[128 * FS], g_flag_e[128 * FS];
__device__ unsigned g_epoch, g_done;
#define TR(i) do {} while (0)

struct Params {
  CUtensorMap tmX, tmWqkv, tmW1a, tmW1b, tmW2, tmWo, tmHO, tmHOs, tmOs, tmOut;
  const __nv_bfloat16* x;
  const __nv_bfloat16* gate_w;
  const __nv_bfloat16* w1;
  const __nv_bfloat16* w2;
  const __nv_bfloat16* wo;
  __nv_bfloat16* out;
};

DEVI uint32_t smem_u32(const void* p) { return (uint32_t)__cvta_generic_to_shared(p); }
DEVI uint32_t clk32() { uint32_t c; asm volatile("mov.u32 %0, %%clock;" : "=r"(c)); return c; }
DEVI void mbar_init(uint32_t bar, uint32_t cnt) { asm volatile("mbarrier.init.shared::cta.b64 [%0], %1;" ::"r"(bar), "r"(cnt)); }
DEVI void mbar_expect_tx(uint32_t bar, uint32_t bytes) { asm volatile("mbarrier.arrive.expect_tx.shared::cta.b64 _, [%0], %1;" ::"r"(bar), "r"(bytes) : "memory"); }
DEVI void mbar_arrive(uint32_t bar) { asm volatile("mbarrier.arrive.shared::cta.b64 _, [%0];" ::"r"(bar) : "memory"); }
DEVI void mbar_arrive_n(uint32_t bar, uint32_t n) { asm volatile("mbarrier.arrive.shared::cta.b64 _, [%0], %1;" ::"r"(bar), "r"(n) : "memory"); }
DEVI void mbar_arrive_cluster(uint32_t bar, uint32_t cta) {
  asm volatile("{ .reg .b32 ra; mapa.shared::cluster.u32 ra, %0, %1; mbarrier.arrive.shared::cluster.b64 _, [ra]; }" ::"r"(bar), "r"(cta) : "memory");
}
DEVI void mbar_wait(uint32_t bar, uint32_t parity, uint32_t t0) {
  asm volatile("{ .reg .pred p; .reg .u32 c;\n"
               "mbarrier.try_wait.parity.shared::cta.b64 p, [%0], %1;\n"
               "@p bra DONE_%=;\n"
               "WAIT_%=:\n"
               "mbarrier.try_wait.parity.shared::cta.b64 p, [%0], %1, %4;\n"
               "@p bra DONE_%=;\n"
               "mov.u32 c, %%clock; sub.u32 c, c, %2; setp.lt.u32 p, c, %3;\n"
               "@p bra WAIT_%=;\n"
               "DONE_%=: }" ::"r"(bar), "r"(parity), "r"(t0), "n"(TIMEOUT), "r"(WAIT_HINT_NS) : "memory");
}
DEVI unsigned ld_relaxed(const unsigned* p) { unsigned v; asm volatile("ld.relaxed.gpu.global.u32 %0, [%1];" : "=r"(v) : "l"(p) : "memory"); return v; }
DEVI float ld_relaxed_f(const float* p) { float v; asm volatile("ld.relaxed.gpu.global.f32 %0, [%1];" : "=f"(v) : "l"(p) : "memory"); return v; }
DEVI void flag_wait(const unsigned* p, unsigned target, uint32_t t0) {
  while ((int)(ld_relaxed(p) - target) < 0) { if (clk32() - t0 > TIMEOUT) break; }
}
DEVI void flag_add(unsigned* p) { asm volatile("red.relaxed.gpu.global.add.u32 [%0], 1;" ::"l"(p) : "memory"); }
DEVI void fence_async_smem() { asm volatile("fence.proxy.async.shared::cta;" ::: "memory"); }
DEVI void fence_async_global() { asm volatile("fence.proxy.async.global;" ::: "memory"); }
DEVI void tma_load_2d(uint32_t dst, const CUtensorMap* m, int c0, int c1, uint32_t bar) {
  asm volatile("cp.async.bulk.tensor.2d.shared::cluster.global.mbarrier::complete_tx::bytes [%0], [%1, {%3, %4}], [%2];" ::"r"(dst), "l"(m), "r"(bar), "r"(c0), "r"(c1) : "memory");
}
DEVI void tma_load_3d(uint32_t dst, const CUtensorMap* m, int c0, int c1, int c2, uint32_t bar) {
  asm volatile("cp.async.bulk.tensor.3d.shared::cluster.global.mbarrier::complete_tx::bytes [%0], [%1, {%3, %4, %5}], [%2];"
               ::"r"(dst), "l"(m), "r"(bar), "r"(c0), "r"(c1), "r"(c2) : "memory");
}
DEVI void tma_load_3d_mc(uint32_t dst, const CUtensorMap* m, int c0, int c1, int c2, uint32_t bar) {
  asm volatile("cp.async.bulk.tensor.3d.shared::cluster.global.mbarrier::complete_tx::bytes.multicast::cluster [%0], [%1, {%3, %4, %5}], [%2], %6;"
               ::"r"(dst), "l"(m), "r"(bar), "r"(c0), "r"(c1), "r"(c2), "h"((uint16_t)3) : "memory");
}
DEVI void tma_load_4d_mc(uint32_t dst, const CUtensorMap* m, int c0, int c1, int c2, int c3, uint32_t bar) {
  asm volatile("cp.async.bulk.tensor.4d.shared::cluster.global.mbarrier::complete_tx::bytes.multicast::cluster [%0], [%1, {%3, %4, %5, %6}], [%2], %7;"
               ::"r"(dst), "l"(m), "r"(bar), "r"(c0), "r"(c1), "r"(c2), "r"(c3), "h"((uint16_t)3) : "memory");
}
DEVI void tma_store_2d(const CUtensorMap* m, int c0, int c1, uint32_t src) {
  asm volatile("cp.async.bulk.tensor.2d.global.shared::cta.bulk_group [%0, {%1, %2}], [%3];" ::"l"(m), "r"(c0), "r"(c1), "r"(src) : "memory");
}
DEVI void bulk_store(void* dst, uint32_t src, uint32_t bytes) {
  asm volatile("cp.async.bulk.global.shared::cta.bulk_group [%0], [%1], %2;" ::"l"(dst), "r"(src), "r"(bytes) : "memory");
}
DEVI void bulk_load(uint32_t dst, const void* src, uint32_t bytes, uint32_t bar) {
  asm volatile("cp.async.bulk.shared::cluster.global.mbarrier::complete_tx::bytes [%0], [%1], %2, [%3];" ::"r"(dst), "l"(src), "r"(bytes), "r"(bar) : "memory");
}
DEVI void bulk_commit() { asm volatile("cp.async.bulk.commit_group;" ::: "memory"); }
DEVI void bulk_wait_all() { asm volatile("cp.async.bulk.wait_group 0;" ::: "memory"); }
DEVI void l2_prefetch(const void* p, uint32_t bytes) { asm volatile("cp.async.bulk.prefetch.L2.global [%0], %1;" ::"l"(p), "r"(bytes) : "memory"); }
DEVI void cluster_arrive() { asm volatile("barrier.cluster.arrive.relaxed.aligned;" ::: "memory"); }
DEVI void cluster_wait() { asm volatile("barrier.cluster.wait.aligned;" ::: "memory"); }
template <int ID> DEVI void named_bar(int n) { asm volatile("bar.sync %0, %1;" ::"n"(ID), "r"(n) : "memory"); }
DEVI void wg_bar(int wg) { if (wg == 0) named_bar<1>(128); else named_bar<2>(128); }
DEVI void wgmma_fence() { asm volatile("wgmma.fence.sync.aligned;" ::: "memory"); }
DEVI void wgmma_commit() { asm volatile("wgmma.commit_group.sync.aligned;" ::: "memory"); }
template <int N> DEVI void wgmma_wait() { asm volatile("wgmma.wait_group.sync.aligned %0;" ::"n"(N) : "memory"); }
template <uint32_t LBO> DEVI uint64_t desc_sw128(uint32_t a16) {
  return ((uint64_t)(0x40000000u | (1024 >> 4)) << 32) | (a16 + ((LBO >> 4) << 16));
}
DEVI uint64_t desc_sw64(uint32_t a16) {
  return ((uint64_t)(0x80000000u | (512 >> 4)) << 32) | (a16 + ((512 >> 4) << 16));
}
DEVI uint32_t pack_bf16(float lo, float hi) { uint32_t r; asm("cvt.rn.bf16x2.f32 %0, %1, %2;" : "=r"(r) : "f"(hi), "f"(lo)); return r; }
DEVI void stsm_x4(uint32_t addr, uint32_t r0, uint32_t r1, uint32_t r2, uint32_t r3) {
  asm volatile("stmatrix.sync.aligned.m8n8.x4.shared.b16 [%0], {%1, %2, %3, %4};" ::"r"(addr), "r"(r0), "r"(r1), "r"(r2), "r"(r3) : "memory");
}
DEVI void sts128(uint32_t addr, uint32_t r0, uint32_t r1, uint32_t r2, uint32_t r3) {
  asm volatile("st.shared.v4.b32 [%0], {%1, %2, %3, %4};" ::"r"(addr), "r"(r0), "r"(r1), "r"(r2), "r"(r3) : "memory");
}
DEVI uint4 lds128(uint32_t addr) {
  uint4 v; asm volatile("ld.shared.v4.b32 {%0, %1, %2, %3}, [%4];" : "=r"(v.x), "=r"(v.y), "=r"(v.z), "=r"(v.w) : "r"(addr) : "memory"); return v;
}
DEVI float ex2(float x) { float y; asm("ex2.approx.ftz.f32 %0, %1;" : "=f"(y) : "f"(x)); return y; }

DEVI void wgmma_ss_n64(float (&d)[32], uint64_t da, uint64_t db) {
  asm volatile("wgmma.mma_async.sync.aligned.m64n64k16.f32.bf16.bf16 {%0, %1, %2, %3, %4, %5, %6, %7, %8, %9, %10, %11, %12, %13, %14, %15, %16, %17, %18, %19, %20, %21, %22, %23, %24, %25, %26, %27, %28, %29, %30, %31}, %32, %33, 1, 1, 1, 0, 1;"
    : "+f"(d[0]), "+f"(d[1]), "+f"(d[2]), "+f"(d[3]), "+f"(d[4]), "+f"(d[5]), "+f"(d[6]), "+f"(d[7]), "+f"(d[8]), "+f"(d[9]), "+f"(d[10]), "+f"(d[11]), "+f"(d[12]), "+f"(d[13]), "+f"(d[14]), "+f"(d[15]), "+f"(d[16]), "+f"(d[17]), "+f"(d[18]), "+f"(d[19]), "+f"(d[20]), "+f"(d[21]), "+f"(d[22]), "+f"(d[23]), "+f"(d[24]), "+f"(d[25]), "+f"(d[26]), "+f"(d[27]), "+f"(d[28]), "+f"(d[29]), "+f"(d[30]), "+f"(d[31])
    : "l"(da), "l"(db));
}
DEVI void wgmma_ss_n128(float (&d)[64], uint64_t da, uint64_t db) {
  asm volatile("wgmma.mma_async.sync.aligned.m64n128k16.f32.bf16.bf16 {%0, %1, %2, %3, %4, %5, %6, %7, %8, %9, %10, %11, %12, %13, %14, %15, %16, %17, %18, %19, %20, %21, %22, %23, %24, %25, %26, %27, %28, %29, %30, %31, %32, %33, %34, %35, %36, %37, %38, %39, %40, %41, %42, %43, %44, %45, %46, %47, %48, %49, %50, %51, %52, %53, %54, %55, %56, %57, %58, %59, %60, %61, %62, %63}, %64, %65, 1, 1, 1, 0, 1;"
    : "+f"(d[0]), "+f"(d[1]), "+f"(d[2]), "+f"(d[3]), "+f"(d[4]), "+f"(d[5]), "+f"(d[6]), "+f"(d[7]), "+f"(d[8]), "+f"(d[9]), "+f"(d[10]), "+f"(d[11]), "+f"(d[12]), "+f"(d[13]), "+f"(d[14]), "+f"(d[15]), "+f"(d[16]), "+f"(d[17]), "+f"(d[18]), "+f"(d[19]), "+f"(d[20]), "+f"(d[21]), "+f"(d[22]), "+f"(d[23]), "+f"(d[24]), "+f"(d[25]), "+f"(d[26]), "+f"(d[27]), "+f"(d[28]), "+f"(d[29]), "+f"(d[30]), "+f"(d[31]), "+f"(d[32]), "+f"(d[33]), "+f"(d[34]), "+f"(d[35]), "+f"(d[36]), "+f"(d[37]), "+f"(d[38]), "+f"(d[39]), "+f"(d[40]), "+f"(d[41]), "+f"(d[42]), "+f"(d[43]), "+f"(d[44]), "+f"(d[45]), "+f"(d[46]), "+f"(d[47]), "+f"(d[48]), "+f"(d[49]), "+f"(d[50]), "+f"(d[51]), "+f"(d[52]), "+f"(d[53]), "+f"(d[54]), "+f"(d[55]), "+f"(d[56]), "+f"(d[57]), "+f"(d[58]), "+f"(d[59]), "+f"(d[60]), "+f"(d[61]), "+f"(d[62]), "+f"(d[63])
    : "l"(da), "l"(db));
}
DEVI void wgmma_ss_n192(float (&d)[96], uint64_t da, uint64_t db) {
  asm volatile("wgmma.mma_async.sync.aligned.m64n192k16.f32.bf16.bf16 {%0, %1, %2, %3, %4, %5, %6, %7, %8, %9, %10, %11, %12, %13, %14, %15, %16, %17, %18, %19, %20, %21, %22, %23, %24, %25, %26, %27, %28, %29, %30, %31, %32, %33, %34, %35, %36, %37, %38, %39, %40, %41, %42, %43, %44, %45, %46, %47, %48, %49, %50, %51, %52, %53, %54, %55, %56, %57, %58, %59, %60, %61, %62, %63, %64, %65, %66, %67, %68, %69, %70, %71, %72, %73, %74, %75, %76, %77, %78, %79, %80, %81, %82, %83, %84, %85, %86, %87, %88, %89, %90, %91, %92, %93, %94, %95}, %96, %97, 1, 1, 1, 0, 1;"
    : "+f"(d[0]), "+f"(d[1]), "+f"(d[2]), "+f"(d[3]), "+f"(d[4]), "+f"(d[5]), "+f"(d[6]), "+f"(d[7]), "+f"(d[8]), "+f"(d[9]), "+f"(d[10]), "+f"(d[11]), "+f"(d[12]), "+f"(d[13]), "+f"(d[14]), "+f"(d[15]), "+f"(d[16]), "+f"(d[17]), "+f"(d[18]), "+f"(d[19]), "+f"(d[20]), "+f"(d[21]), "+f"(d[22]), "+f"(d[23]), "+f"(d[24]), "+f"(d[25]), "+f"(d[26]), "+f"(d[27]), "+f"(d[28]), "+f"(d[29]), "+f"(d[30]), "+f"(d[31]), "+f"(d[32]), "+f"(d[33]), "+f"(d[34]), "+f"(d[35]), "+f"(d[36]), "+f"(d[37]), "+f"(d[38]), "+f"(d[39]), "+f"(d[40]), "+f"(d[41]), "+f"(d[42]), "+f"(d[43]), "+f"(d[44]), "+f"(d[45]), "+f"(d[46]), "+f"(d[47]), "+f"(d[48]), "+f"(d[49]), "+f"(d[50]), "+f"(d[51]), "+f"(d[52]), "+f"(d[53]), "+f"(d[54]), "+f"(d[55]), "+f"(d[56]), "+f"(d[57]), "+f"(d[58]), "+f"(d[59]), "+f"(d[60]), "+f"(d[61]), "+f"(d[62]), "+f"(d[63]), "+f"(d[64]), "+f"(d[65]), "+f"(d[66]), "+f"(d[67]), "+f"(d[68]), "+f"(d[69]), "+f"(d[70]), "+f"(d[71]), "+f"(d[72]), "+f"(d[73]), "+f"(d[74]), "+f"(d[75]), "+f"(d[76]), "+f"(d[77]), "+f"(d[78]), "+f"(d[79]), "+f"(d[80]), "+f"(d[81]), "+f"(d[82]), "+f"(d[83]), "+f"(d[84]), "+f"(d[85]), "+f"(d[86]), "+f"(d[87]), "+f"(d[88]), "+f"(d[89]), "+f"(d[90]), "+f"(d[91]), "+f"(d[92]), "+f"(d[93]), "+f"(d[94]), "+f"(d[95])
    : "l"(da), "l"(db));
}
DEVI void wgmma_ss_n256(float (&d)[128], uint64_t da, uint64_t db) {
  asm volatile("wgmma.mma_async.sync.aligned.m64n256k16.f32.bf16.bf16 {%0, %1, %2, %3, %4, %5, %6, %7, %8, %9, %10, %11, %12, %13, %14, %15, %16, %17, %18, %19, %20, %21, %22, %23, %24, %25, %26, %27, %28, %29, %30, %31, %32, %33, %34, %35, %36, %37, %38, %39, %40, %41, %42, %43, %44, %45, %46, %47, %48, %49, %50, %51, %52, %53, %54, %55, %56, %57, %58, %59, %60, %61, %62, %63, %64, %65, %66, %67, %68, %69, %70, %71, %72, %73, %74, %75, %76, %77, %78, %79, %80, %81, %82, %83, %84, %85, %86, %87, %88, %89, %90, %91, %92, %93, %94, %95, %96, %97, %98, %99, %100, %101, %102, %103, %104, %105, %106, %107, %108, %109, %110, %111, %112, %113, %114, %115, %116, %117, %118, %119, %120, %121, %122, %123, %124, %125, %126, %127}, %128, %129, 1, 1, 1, 0, 1;"
    : "+f"(d[0]), "+f"(d[1]), "+f"(d[2]), "+f"(d[3]), "+f"(d[4]), "+f"(d[5]), "+f"(d[6]), "+f"(d[7]), "+f"(d[8]), "+f"(d[9]), "+f"(d[10]), "+f"(d[11]), "+f"(d[12]), "+f"(d[13]), "+f"(d[14]), "+f"(d[15]), "+f"(d[16]), "+f"(d[17]), "+f"(d[18]), "+f"(d[19]), "+f"(d[20]), "+f"(d[21]), "+f"(d[22]), "+f"(d[23]), "+f"(d[24]), "+f"(d[25]), "+f"(d[26]), "+f"(d[27]), "+f"(d[28]), "+f"(d[29]), "+f"(d[30]), "+f"(d[31]), "+f"(d[32]), "+f"(d[33]), "+f"(d[34]), "+f"(d[35]), "+f"(d[36]), "+f"(d[37]), "+f"(d[38]), "+f"(d[39]), "+f"(d[40]), "+f"(d[41]), "+f"(d[42]), "+f"(d[43]), "+f"(d[44]), "+f"(d[45]), "+f"(d[46]), "+f"(d[47]), "+f"(d[48]), "+f"(d[49]), "+f"(d[50]), "+f"(d[51]), "+f"(d[52]), "+f"(d[53]), "+f"(d[54]), "+f"(d[55]), "+f"(d[56]), "+f"(d[57]), "+f"(d[58]), "+f"(d[59]), "+f"(d[60]), "+f"(d[61]), "+f"(d[62]), "+f"(d[63]), "+f"(d[64]), "+f"(d[65]), "+f"(d[66]), "+f"(d[67]), "+f"(d[68]), "+f"(d[69]), "+f"(d[70]), "+f"(d[71]), "+f"(d[72]), "+f"(d[73]), "+f"(d[74]), "+f"(d[75]), "+f"(d[76]), "+f"(d[77]), "+f"(d[78]), "+f"(d[79]), "+f"(d[80]), "+f"(d[81]), "+f"(d[82]), "+f"(d[83]), "+f"(d[84]), "+f"(d[85]), "+f"(d[86]), "+f"(d[87]), "+f"(d[88]), "+f"(d[89]), "+f"(d[90]), "+f"(d[91]), "+f"(d[92]), "+f"(d[93]), "+f"(d[94]), "+f"(d[95]), "+f"(d[96]), "+f"(d[97]), "+f"(d[98]), "+f"(d[99]), "+f"(d[100]), "+f"(d[101]), "+f"(d[102]), "+f"(d[103]), "+f"(d[104]), "+f"(d[105]), "+f"(d[106]), "+f"(d[107]), "+f"(d[108]), "+f"(d[109]), "+f"(d[110]), "+f"(d[111]), "+f"(d[112]), "+f"(d[113]), "+f"(d[114]), "+f"(d[115]), "+f"(d[116]), "+f"(d[117]), "+f"(d[118]), "+f"(d[119]), "+f"(d[120]), "+f"(d[121]), "+f"(d[122]), "+f"(d[123]), "+f"(d[124]), "+f"(d[125]), "+f"(d[126]), "+f"(d[127])
    : "l"(da), "l"(db));
}
DEVI void wgmma_qk64(float (&d)[32], uint32_t a0, uint32_t a1, uint32_t a2, uint32_t a3, uint64_t db) {
  asm volatile("wgmma.mma_async.sync.aligned.m64n64k16.f32.bf16.bf16 {%0, %1, %2, %3, %4, %5, %6, %7, %8, %9, %10, %11, %12, %13, %14, %15, %16, %17, %18, %19, %20, %21, %22, %23, %24, %25, %26, %27, %28, %29, %30, %31}, {%32, %33, %34, %35}, %36, 0, 1, 1, 0;"
    : "=f"(d[0]), "=f"(d[1]), "=f"(d[2]), "=f"(d[3]), "=f"(d[4]), "=f"(d[5]), "=f"(d[6]), "=f"(d[7]), "=f"(d[8]), "=f"(d[9]), "=f"(d[10]), "=f"(d[11]), "=f"(d[12]), "=f"(d[13]), "=f"(d[14]), "=f"(d[15]), "=f"(d[16]), "=f"(d[17]), "=f"(d[18]), "=f"(d[19]), "=f"(d[20]), "=f"(d[21]), "=f"(d[22]), "=f"(d[23]), "=f"(d[24]), "=f"(d[25]), "=f"(d[26]), "=f"(d[27]), "=f"(d[28]), "=f"(d[29]), "=f"(d[30]), "=f"(d[31])
    : "r"(a0), "r"(a1), "r"(a2), "r"(a3), "l"(db));
}
DEVI void wgmma_qk128(float (&d)[64], uint32_t a0, uint32_t a1, uint32_t a2, uint32_t a3, uint64_t db) {
  asm volatile("wgmma.mma_async.sync.aligned.m64n128k16.f32.bf16.bf16 {%0, %1, %2, %3, %4, %5, %6, %7, %8, %9, %10, %11, %12, %13, %14, %15, %16, %17, %18, %19, %20, %21, %22, %23, %24, %25, %26, %27, %28, %29, %30, %31, %32, %33, %34, %35, %36, %37, %38, %39, %40, %41, %42, %43, %44, %45, %46, %47, %48, %49, %50, %51, %52, %53, %54, %55, %56, %57, %58, %59, %60, %61, %62, %63}, {%64, %65, %66, %67}, %68, 0, 1, 1, 0;"
    : "=f"(d[0]), "=f"(d[1]), "=f"(d[2]), "=f"(d[3]), "=f"(d[4]), "=f"(d[5]), "=f"(d[6]), "=f"(d[7]), "=f"(d[8]), "=f"(d[9]), "=f"(d[10]), "=f"(d[11]), "=f"(d[12]), "=f"(d[13]), "=f"(d[14]), "=f"(d[15]), "=f"(d[16]), "=f"(d[17]), "=f"(d[18]), "=f"(d[19]), "=f"(d[20]), "=f"(d[21]), "=f"(d[22]), "=f"(d[23]), "=f"(d[24]), "=f"(d[25]), "=f"(d[26]), "=f"(d[27]), "=f"(d[28]), "=f"(d[29]), "=f"(d[30]), "=f"(d[31]), "=f"(d[32]), "=f"(d[33]), "=f"(d[34]), "=f"(d[35]), "=f"(d[36]), "=f"(d[37]), "=f"(d[38]), "=f"(d[39]), "=f"(d[40]), "=f"(d[41]), "=f"(d[42]), "=f"(d[43]), "=f"(d[44]), "=f"(d[45]), "=f"(d[46]), "=f"(d[47]), "=f"(d[48]), "=f"(d[49]), "=f"(d[50]), "=f"(d[51]), "=f"(d[52]), "=f"(d[53]), "=f"(d[54]), "=f"(d[55]), "=f"(d[56]), "=f"(d[57]), "=f"(d[58]), "=f"(d[59]), "=f"(d[60]), "=f"(d[61]), "=f"(d[62]), "=f"(d[63])
    : "r"(a0), "r"(a1), "r"(a2), "r"(a3), "l"(db));
}
DEVI void wgmma_pv(float (&d)[8], uint32_t a0, uint32_t a1, uint32_t a2, uint32_t a3, uint64_t db) {
  asm volatile("wgmma.mma_async.sync.aligned.m64n16k16.f32.bf16.bf16 {%0, %1, %2, %3, %4, %5, %6, %7}, {%8, %9, %10, %11}, %12, 1, 1, 1, 1;"
    : "+f"(d[0]), "+f"(d[1]), "+f"(d[2]), "+f"(d[3]), "+f"(d[4]), "+f"(d[5]), "+f"(d[6]), "+f"(d[7])
    : "r"(a0), "r"(a1), "r"(a2), "r"(a3), "l"(db));
}
DEVI void wgmma_pv0(float (&d)[8], uint32_t a0, uint32_t a1, uint32_t a2, uint32_t a3, uint64_t db) {
  asm volatile("wgmma.mma_async.sync.aligned.m64n16k16.f32.bf16.bf16 {%0, %1, %2, %3, %4, %5, %6, %7}, {%8, %9, %10, %11}, %12, 0, 1, 1, 1;"
    : "=f"(d[0]), "=f"(d[1]), "=f"(d[2]), "=f"(d[3]), "=f"(d[4]), "=f"(d[5]), "=f"(d[6]), "=f"(d[7])
    : "r"(a0), "r"(a1), "r"(a2), "r"(a3), "l"(db));
}

template <int N> DEVI void wgmma_ss(float (&d)[N / 2], uint64_t da, uint64_t db) {
  if constexpr (N == 64) wgmma_ss_n64(d, da, db);
  else if constexpr (N == 128) wgmma_ss_n128(d, da, db);
  else if constexpr (N == 192) wgmma_ss_n192(d, da, db);
  else wgmma_ss_n256(d, da, db);
}

DEVI int oh_chunk(int j, int i, int& need) {
  if (j & 1) {
    if (i >= 3 && i < 7) { need = 16 + 2 * (i - 3); return 24 + (i - 3); }
    if (i >= 7) i -= 4;
  }
  const int g = i / 3, o = (j + 2 * g) & 7;
  need = o;
  return 3 * o + (i - 3 * g);
}

DEVI int next_a_slot(int e, int ai) {
  e++;
  return e < 16 ? (ai == NA - 1 ? 0 : ai + 1) : e < 32 ? 1 + (e & 3) : (e - 27) & 7;
}

struct Ctx {
  uint32_t sbase, bars, peer, t0, a16, b16;
  int wg, lane;
  int ai, bi; uint32_t aph, bph;
  int brem, ae;
  int pa2, pb2;
  int pa, pb;
};

DEVI void release_prev(Ctx& c) {
  if (c.pb >= 0) {
    if (c.lane == 0) mbar_arrive(c.bars + 8 * (BAR_EMPTYB + c.pb));
    if (c.lane == 1) mbar_arrive_cluster(c.bars + 8 * (BAR_EMPTYB + c.pb), c.peer);
  }
  if (c.pa >= 0 && c.lane == 2) mbar_arrive(c.bars + 8 * (BAR_EMPTYA + c.pa));
}

DEVI void gemm_wait(Ctx& c) {
  asm volatile("{ .reg .pred p, q; .reg .u32 c;\n"
               "WAIT_%=:\n"
               "mbarrier.try_wait.parity.shared::cta.b64 p, [%0], %1;\n"
               "mbarrier.try_wait.parity.shared::cta.b64 q, [%2], %3;\n"
               "and.pred p, p, q;\n"
               "@p bra DONE_%=;\n"
               "mov.u32 c, %%clock; sub.u32 c, c, %4; setp.lt.u32 p, c, %5;\n"
               "@p bra WAIT_%=;\n"
               "DONE_%=: }" ::"r"(c.bars + 8 * (BAR_FULLA + c.ai)), "r"((c.aph >> c.ai) & 1), "r"(c.bars + 8 * (BAR_FULLB + c.bi)), "r"(c.bph), "r"(c.t0), "n"(TIMEOUT) : "memory");
}
template <int N>
DEVI void gemm_group(float (&acc)[N / 2], Ctx& c, int g, int& npa, int& npb) {
  const uint32_t a16 = c.a16 + c.ai * (SLOT >> 4);
  const uint32_t b16 = c.b16 + c.bi * (SLOT >> 4);
  bool adv;
  if constexpr (N >= 192) {
    const uint32_t a2 = a16 + (g & 1) * 4;
    wgmma_ss<N>(acc, desc_sw128<16>(a2), desc_sw128<2048>(b16));
    wgmma_ss<N>(acc, desc_sw128<16>(a2 + 2), desc_sw128<2048>(b16 + 512));
    adv = g & 1;
  } else {
#pragma unroll
    for (int s = 0; s < 4; s++) wgmma_ss<N>(acc, desc_sw128<16>(a16 + s * 2), desc_sw128<4096>(b16 + (s >> 1) * 512 + (s & 1) * 128));
    adv = true;
  }
  wgmma_commit();
  npb = c.brem > 0 ? c.bi : -1;
  c.brem--;
  if (++c.bi == NB) { c.bi = 0; c.bph ^= 1; }
  npa = -1;
  if (adv) { npa = c.ai; c.aph ^= 1u << c.ai; c.ai = next_a_slot(c.ae, c.ai); c.ae++; }
}

template <int N>
DEVI void bare_groups(float (&acc)[N / 2], Ctx& c, int g0, int g1) {
  for (int g = g0; g < g1; g++) {
    int npa, npb;
    gemm_wait(c);
    wgmma_fence();
    gemm_group<N>(acc, c, g, npa, npb);
    wgmma_wait<1>();
    release_prev(c);
    c.pa = npa; c.pb = npb;
  }
}
DEVI void drain(Ctx& c) {
  wgmma_wait<0>();
  release_prev(c);
  c.pa = c.pb = -1;
}

constexpr float SC = 0.25f * 1.4426950408889634f;

#define ONCE _Pragma("unroll 1") for (unsigned once_ = 0; once_ < gridDim.y; once_++)

struct Attn {
  uint32_t q[4][4];
  uint32_t nm[4];
  float g0, g1;
  int cmin;
  int rowc;
};

template <int O0, int NS>
DEVI void kill32(float (&S)[NS]) {
#pragma unroll
  for (int i = 0; i < 32; i++) S[O0 + i] = __int_as_float(0xff800000);
}
DEVI void row_max(const float (&S)[64], float& x0, float& x1) {
#pragma unroll
  for (int n = 0; n < 16; n++) {
    x0 = fmaxf(x0, fmaxf(S[4 * n], S[4 * n + 1])); x1 = fmaxf(x1, fmaxf(S[4 * n + 2], S[4 * n + 3]));
  }
}
template <int K, bool PRE = false>
DEVI void exp8(const float (&S)[64], uint32_t (&P)[4], float n0, float n1, float (&l)[4]) {
  float e[8];
#pragma unroll
  for (int i = 0; i < 8; i++) e[i] = ex2(PRE ? S[8 * K + i] : fmaf(S[8 * K + i], SC, (i & 2) ? n1 : n0));
  l[0] += e[0]; l[1] += e[1]; l[2] += e[2]; l[3] += e[3];
  l[0] += e[4]; l[1] += e[5]; l[2] += e[6]; l[3] += e[7];
#pragma unroll
  for (int i = 0; i < 4; i++) P[i] = pack_bf16(e[2 * i], e[2 * i + 1]) | (__float_as_uint(l[i]) & blockIdx.y);
}
DEVI void merge_fl(float (&S)[64], const float (&F)[32], int rowc) {
#pragma unroll
  for (int n = 0; n < 8; n++) {
    if (n * 8 > rowc) S[32 + 4 * n] = F[4 * n];
    if (n * 8 + 1 > rowc) S[32 + 4 * n + 1] = F[4 * n + 1];
    if (n * 8 > rowc + 8) S[32 + 4 * n + 2] = F[4 * n + 2];
    if (n * 8 + 1 > rowc + 8) S[32 + 4 * n + 3] = F[4 * n + 3];
  }
}
DEVI bool wg_any(int wg, bool v) {
  uint32_t r;
  if (wg == 0) asm volatile("{ .reg .pred p, q; setp.ne.u32 p, %1, 0; bar.red.or.pred q, 1, 128, p; selp.u32 %0, 1, 0, q; }" : "=r"(r) : "r"((uint32_t)v) : "memory");
  else asm volatile("{ .reg .pred p, q; setp.ne.u32 p, %1, 0; bar.red.or.pred q, 2, 128, p; selp.u32 %0, 1, 0, q; }" : "=r"(r) : "r"((uint32_t)v) : "memory");
  return r != 0;
}

DEVI void qk_a(float (&S)[64], float (&F)[32], const uint32_t (&q)[4], uint32_t kb) {
  wgmma_fence();
  wgmma_qk128(S, q[0], q[1], q[2], q[3], desc_sw64(kb + 3 * 256));
  wgmma_qk64(F, q[0], q[1], q[2], q[3], desc_sw64(kb));
}
DEVI void fix_a(float (&S)[64], float (&F)[32], const Attn& at) {
  if (at.cmin > 0) { kill32<0>(F); if (at.cmin > 3) kill32<0>(S); }
  merge_fl(S, F, at.rowc);
}
DEVI void fix_b(float (&S)[64], const Attn& at) {
  if (at.cmin > 1) { kill32<0>(S); if (at.cmin > 2) kill32<32>(S); }
}
DEVI void exp_all(const float (&S)[64], uint32_t (&P)[8][4], float n0, float n1, float (&l)[4]) {
  exp8<0>(S, P[0], n0, n1, l); exp8<1>(S, P[1], n0, n1, l); exp8<2>(S, P[2], n0, n1, l); exp8<3>(S, P[3], n0, n1, l);
  exp8<4>(S, P[4], n0, n1, l); exp8<5>(S, P[5], n0, n1, l); exp8<6>(S, P[6], n0, n1, l); exp8<7>(S, P[7], n0, n1, l);
}
template <int W> DEVI void hook(float (&acc)[64], Ctx& c) {
  int npa, npb;
  gemm_wait(c);
  wgmma_fence();
  gemm_group<128>(acc, c, 0, npa, npb);
  if (W == 0) { c.pa = npa; c.pb = npb; } else { c.pa2 = npa; c.pb2 = npb; }
}
DEVI void release_all(Ctx& c) {
  release_prev(c);
  c.pa = c.pa2; c.pb = c.pb2;
  release_prev(c);
  c.pa = c.pb = c.pa2 = c.pb2 = -1;
}
template <int NH> DEVI void hooks(float (&acc)[64], Ctx& c) {
  if (NH > 0) hook<0>(acc, c);
  if (NH > 1) hook<1>(acc, c);
}

template <int NH0, int NH1>
DEVI void head_pass(float (&acc)[64], Ctx& c, const Attn& at, uint32_t kb, float n0, float n1, float (&O)[8], float& l0, float& l1) {
  float S[64], l[4] = {0.f, 0.f, 0.f, 0.f};
  uint32_t P[8][4];
  {
    float F[32];
    qk_a(S, F, at.q[0], kb);
    wgmma_commit();
    wgmma_wait<0>();
    hooks<NH0>(acc, c);
    fix_a(S, F, at);
  }
  exp_all(S, P, n0, n1, l);
  {
    uint32_t PF[4][4];
#pragma unroll
    for (int k = 0; k < 4; k++) {
#pragma unroll
      for (int i = 0; i < 4; i++) {
        const int col = k * 16 + (i >> 1) * 8, r = at.rowc + (i & 1) * 8;
        const uint32_t m = (col > r ? 0xFFFFu : 0u) | (col + 1 > r ? 0xFFFF0000u : 0u);
        PF[k][i] = P[4 + k][i] & m; P[4 + k][i] &= ~m;
      }
    }
    wgmma_fence();
    wgmma_pv0(O, P[0][0], P[0][1], P[0][2], P[0][3], desc_sw64(kb + 3 * 256 + 2));
#pragma unroll
    for (int k = 1; k < 8; k++) wgmma_pv(O, P[k][0], P[k][1], P[k][2], P[k][3], desc_sw64(kb + 3 * 256 + 2 + k * 64));
#pragma unroll
    for (int k = 0; k < 4; k++) wgmma_pv(O, PF[k][0], PF[k][1], PF[k][2], PF[k][3], desc_sw64(kb + 2 + k * 64));
    wgmma_qk128(S, at.q[0][0], at.q[0][1], at.q[0][2], at.q[0][3], desc_sw64(kb + 256));
    wgmma_commit();
    wgmma_wait<0>();
  }
  if (NH0 > 0) release_all(c);
  hooks<NH1>(acc, c);
  fix_b(S, at);
  exp_all(S, P, n0, n1, l);
  wgmma_fence();
#pragma unroll
  for (int k = 0; k < 8; k++) wgmma_pv(O, P[k][0], P[k][1], P[k][2], P[k][3], desc_sw64(kb + 256 + 2 + k * 64));
  wgmma_commit();
  l0 = l[0] + l[1]; l1 = l[2] + l[3];
  l0 += __shfl_xor_sync(0xffffffffu, l0, 1); l1 += __shfl_xor_sync(0xffffffffu, l1, 1);
  l0 += __shfl_xor_sync(0xffffffffu, l0, 2); l1 += __shfl_xor_sync(0xffffffffu, l1, 2);
  wgmma_wait<0>();
  if (NH1 > 0) release_all(c);
}

DEVI void attention(float (&acc)[64], Ctx& c, Attn& at, int wi) {
  const uint32_t kvb = ((c.sbase & 0x3FFFF) + OFF_KV + c.wg * 4096) >> 4;
#pragma unroll 1
  for (int h = 0; h < 4; h++) {
    const uint32_t kb = kvb + (h & 1) * (KVBUF >> 4);
    float O[8], l0, l1;
    mbar_wait(c.bars + 8 * (BAR_KVFULL + (h & 1)), h >> 1, c.t0);
    head_pass<HK0, HK1>(acc, c, at, kb, __uint_as_float(at.nm[0] << 16), __uint_as_float(at.nm[0] & 0xffff0000u), O, l0, l1);
    const bool bad = !(l0 > 1e-6f && l0 < 1e18f && l1 > 1e-6f && l1 < 1e18f);
    float c0, c1;
    uint32_t o0, o1, o2, o3;
    if (wg_any(c.wg, bad)) {
      float x0 = __int_as_float(0xff800000), x1 = x0;
      {
        float T[64];
        wgmma_fence();
        wgmma_qk128(T, at.q[0][0], at.q[0][1], at.q[0][2], at.q[0][3], desc_sw64(kb + 256));
        wgmma_commit();
        wgmma_wait<0>();
        fix_b(T, at);
        row_max(T, x0, x1);
      }
      ONCE { asm volatile("" : "+f"(x0), "+f"(x1)); }
      {
        float T[64], G[32];
        qk_a(T, G, at.q[0], kb);
        wgmma_commit();
        wgmma_wait<0>();
        fix_a(T, G, at);
        row_max(T, x0, x1);
      }
      x0 = fmaxf(x0, __shfl_xor_sync(0xffffffffu, x0, 1)); x1 = fmaxf(x1, __shfl_xor_sync(0xffffffffu, x1, 1));
      x0 = fmaxf(x0, __shfl_xor_sync(0xffffffffu, x0, 2)); x1 = fmaxf(x1, __shfl_xor_sync(0xffffffffu, x1, 2));
      float O2[8];
      head_pass<0, 0>(acc, c, at, kb, -x0 * SC, -x1 * SC, O2, l0, l1);
      c0 = __fdividef(at.g0, l0); c1 = __fdividef(at.g1, l1);
      o0 = pack_bf16(O2[0] * c0, O2[1] * c0); o1 = pack_bf16(O2[2] * c1, O2[3] * c1);
      o2 = pack_bf16(O2[4] * c0, O2[5] * c0); o3 = pack_bf16(O2[6] * c1, O2[7] * c1);
    } else {
      c0 = __fdividef(at.g0, l0); c1 = __fdividef(at.g1, l1);
      o0 = pack_bf16(O[0] * c0, O[1] * c0); o1 = pack_bf16(O[2] * c1, O[3] * c1);
      o2 = pack_bf16(O[4] * c0, O[5] * c0); o3 = pack_bf16(O[6] * c1, O[7] * c1);
    }
    if (c.lane == 0) mbar_arrive(c.bars + 8 * (h == 3 ? BAR_ATTDONE : BAR_KVEMPTY + (h & 1)));
    const uint32_t ost = c.sbase + OFF_A + c.wg * 8192 + h * 2048;
    const int mi = c.lane >> 3;
    const int srow = wi * 16 + (c.lane & 7) + 8 * (mi & 1);
    stsm_x4(ost + srow * 32 + (mi >> 1) * 16, o0, o1, o2, o3);
    fence_async_smem();
    __syncwarp();
    if (c.lane == 0) mbar_arrive(c.bars + 8 * (BAR_STG + c.wg));
#pragma unroll
    for (int i = 0; i < 4; i++) { at.q[0][i] = at.q[1][i]; at.q[1][i] = at.q[2][i]; at.q[2][i] = at.q[3][i]; }
    at.nm[0] = at.nm[1]; at.nm[1] = at.nm[2]; at.nm[2] = at.nm[3];
  }
}

template <int CH, int NACC>
DEVI void store_h_chunk(const float (&acc)[NACC], uint32_t base  , int lane, float s0, float s1) {
  const int mi = lane >> 3;
#pragma unroll
  for (int tp = 0; tp < 4; tp++) {
    const int t = CH * 8 + tp * 2;
    const uint32_t r0 = pack_bf16(fmaxf(acc[4 * t + 0], 0.f) * s0, fmaxf(acc[4 * t + 1], 0.f) * s0);
    const uint32_t r1 = pack_bf16(fmaxf(acc[4 * t + 2], 0.f) * s1, fmaxf(acc[4 * t + 3], 0.f) * s1);
    const uint32_t r2 = pack_bf16(fmaxf(acc[4 * t + 4], 0.f) * s0, fmaxf(acc[4 * t + 5], 0.f) * s0);
    const uint32_t r3 = pack_bf16(fmaxf(acc[4 * t + 6], 0.f) * s1, fmaxf(acc[4 * t + 7], 0.f) * s1);
    stsm_x4(base + (((tp * 2 + (mi >> 1)) ^ (lane & 7)) << 4), r0, r1, r2, r3);
  }
}

DEVI void get_gate(Attn& at, const Ctx& c, const unsigned* gflag, unsigned gtgt, const float* gp) {
  if (c.lane == 0) flag_wait(gflag, gtgt, c.t0);
  __syncwarp();
  at.g0 = ld_relaxed_f(gp); at.g1 = ld_relaxed_f(gp + 8);
}

template <int N>
DEVI void phase_q(Ctx& c, Attn& at, int warp, const unsigned* gflag, unsigned gtgt, const float* gp) {
  float acc[N / 2];
#pragma unroll
  for (int i = 0; i < N / 2; i++) acc[i] = 0.f;
  bare_groups<N>(acc, c, 0, 14);
  if constexpr (N == 256) get_gate(at, c, gflag, gtgt, gp);
  bare_groups<N>(acc, c, 14, 16);
  drain(c);
  const int lane = c.lane, mi = lane >> 3;
  const int row = warp * 16 + (lane & 7) + 8 * (mi & 1);
  const int sw = (row >> 1) & 3;
#pragma unroll
  for (int hh = 0; hh < 4; hh++) {
    const uint32_t base = c.sbase + OFF_KV + hh * 8192 + row * 64;
#pragma unroll
    for (int kv = 0; kv < 2; kv++) {
      const int t = 8 + kv * 8 + 2 * hh;
      stsm_x4(base + (((kv * 2 + (mi >> 1)) ^ sw) << 4),
              pack_bf16(acc[4 * t + 0], acc[4 * t + 1]), pack_bf16(acc[4 * t + 2], acc[4 * t + 3]),
              pack_bf16(acc[4 * t + 4], acc[4 * t + 5]), pack_bf16(acc[4 * t + 6], acc[4 * t + 7]));
    }
  }
  fence_async_smem();
  __syncwarp();
  if (lane == 0) mbar_arrive(c.bars + 8 * (BAR_STG + c.wg));
  if constexpr (N == 256) {
    store_h_chunk<3>(acc, c.sbase + OFF_KV + 32768 + row * 128, lane, 1.f - at.g0, 1.f - at.g1);
    fence_async_smem();
    __syncwarp();
    if (lane == 0) mbar_arrive(c.bars + 8 * (BAR_STE + c.wg));
  }
#pragma unroll
  for (int hh = 0; hh < 4; hh++) {
#pragma unroll
    for (int i = 0; i < 4; i++) at.q[hh][i] = pack_bf16(acc[8 * hh + 2 * i], acc[8 * hh + 2 * i + 1]);
    const float* q = &acc[8 * hh];
    const float* k = &acc[32 + 8 * hh];
    float d0 = q[0] * k[0] + q[1] * k[1] + q[4] * k[4] + q[5] * k[5], d1 = q[2] * k[2] + q[3] * k[3] + q[6] * k[6] + q[7] * k[7];
    d0 += __shfl_xor_sync(0xffffffffu, d0, 1); d1 += __shfl_xor_sync(0xffffffffu, d1, 1);
    d0 += __shfl_xor_sync(0xffffffffu, d0, 2); d1 += __shfl_xor_sync(0xffffffffu, d1, 2);
    at.nm[hh] = pack_bf16(-d0 * SC, -d1 * SC);
  }
}

DEVI void first_loads(const Params& P, uint32_t sbase, int e, int j, int rb) {
  const uint32_t bars = sbase + OFF_BAR, fb = bars + 8 * (BAR_FULLB + e), fa = bars + 8 * (BAR_FULLA + e);
  mbar_expect_tx(fa, 16384);
  mbar_expect_tx(fb, (j & 1) ? 12288 : 16384);
  if (e == 0) tma_load_2d(sbase + OFF_A, &P.tmX, 0, rb * 128, fa);
#pragma unroll
  for (int r = 0; r < 2; r++) {
    tma_load_3d(sbase + OFF_B + e * SLOT + r * 8192, &P.tmWqkv, 64 * j, e * 32 + r * 16, 0, fb);
    if (!(j & 1)) tma_load_3d(sbase + OFF_B + e * SLOT + r * 8192 + 6144, &P.tmW1a, 0, e * 32 + r * 16, 24 + (j >> 1), fb);
  }
  if (e == 1) tma_load_2d(sbase + OFF_A + SLOT, &P.tmX, 64, rb * 128, fa);
}

__global__ void __cluster_dims__(2, 1, 1) __launch_bounds__(384, 1) fused_kernel(const __grid_constant__ Params P) {
  extern __shared__ uint8_t smem_raw[];
  const uint32_t sbase = (smem_u32(smem_raw) + 1023u) & ~1023u;
  const uint32_t bars = sbase + OFF_BAR;
  const int tid = threadIdx.x, warp = tid >> 5, lane = tid & 31;
  const uint32_t rank = blockIdx.x & 1, peer = rank ^ 1;
  const int j = (blockIdx.x >> 1) & 7, rb = ((blockIdx.x >> 4) << 1) | rank;
  const uint32_t t0 = clk32();

  const int typeB = j & 1;
  if (tid == 288) {
    for (int s = 0; s < NA2; s++) mbar_init(bars + 8 * (BAR_FULLA + s), 1);
    for (int s = 0; s < NB; s++) mbar_init(bars + 8 * (BAR_FULLB + s), 1);
    fence_async_smem();
  } else if (tid < 10) {
    asm volatile("prefetch.tensormap [%0];" ::"l"(&P.tmX + tid) : "memory");
  } else if (tid == 256) {
    for (int s = 0; s < NA2; s++) mbar_init(bars + 8 * (BAR_EMPTYA + s), 10);
    for (int s = 0; s < NB; s++) mbar_init(bars + 8 * (BAR_EMPTYB + s), 16);
  } else if (tid == 320) {
    for (int s = 0; s < 2; s++) { mbar_init(bars + 8 * (BAR_KVFULL + s), 1); mbar_init(bars + 8 * (BAR_KVEMPTY + s), 8); mbar_init(bars + 8 * (BAR_STG + s), 4); mbar_init(bars + 8 * (BAR_STE + s), 4); }
    mbar_init(bars + 8 * BAR_PIN, 1); mbar_init(bars + 8 * BAR_ATTDONE, 8); mbar_init(bars + 8 * BAR_GATE, 1); mbar_init(bars + 8 * (BAR_GATE + 1), 1);
  }
  if (tid >= 256 && lane == 0) asm volatile("fence.mbarrier_init.release.cluster;" ::: "memory");
  const unsigned ep1 = ld_relaxed(&g_epoch) + 1;
  __syncwarp();
  cluster_arrive();
  if (tid == 288) { first_loads(P, sbase, 0, j, rb); first_loads(P, sbase, 1, j, rb); }
  __syncwarp();

  const int on = 12 + 4 * typeB;

  if (warp < 8) {
    asm volatile("setmaxnreg.inc.sync.aligned.u32 232;");
    cluster_wait();
    const int wg = __shfl_sync(0xffffffffu, warp >> 2, 0), wi = warp & 3;
    Ctx c{sbase, bars, peer, t0, ((sbase & 0x3FFFF) + OFF_A + wg * 8192) >> 4, ((sbase & 0x3FFFF) + OFF_B) >> 4, wg, lane, 0, 0, 0u, 0u, 32 + on + 4 - NB, 0, -1, -1, -1, -1};
    Attn at;
    at.cmin = 4 - 2 * rb - wg;
    at.rowc = wi * 16 + (lane >> 2) - (lane & 3) * 2;
    const int row0 = rb * 128 + warp * 16 + (lane >> 2);
    if (tid == 0) TR(0);
    if (typeB) phase_q<192>(c, at, warp, &g_flag_g[rb * FS], ep1 * 16, &g_gate[row0]);
    else phase_q<256>(c, at, warp, &g_flag_g[rb * FS], ep1 * 16, &g_gate[row0]);
    if (tid == 0) TR(2);
    {
      float acc[96];
#pragma unroll
      for (int i = 0; i < 96; i++) acc[i] = 0.f;
      bare_groups<192>(acc, c, 0, 8);
      if (typeB) get_gate(at, c, &g_flag_g[rb * FS], ep1 * 16, &g_gate[row0]);
      bare_groups<192>(acc, c, 8, 16);
      drain(c);
      if (tid == 0) TR(1);
      const uint32_t rowoff = (warp * 16 + (lane & 7) + 8 * ((lane >> 3) & 1)) * 128;
      const float s0 = 1.f - at.g0, s1 = 1.f - at.g1;
      constexpr int e0 = 16 % NA, e1 = 17 % NA, e2 = 18 % NA;
      mbar_wait(bars + 8 * (BAR_FULLA + e0), (16 / NA) & 1, t0);
      store_h_chunk<0>(acc, sbase + OFF_A + e0 * SLOT + rowoff, lane, s0, s1);
      mbar_wait(bars + 8 * (BAR_FULLA + e1), (17 / NA) & 1, t0);
      store_h_chunk<1>(acc, sbase + OFF_A + e1 * SLOT + rowoff, lane, s0, s1);
      mbar_wait(bars + 8 * (BAR_FULLA + e2), (18 / NA) & 1, t0);
      store_h_chunk<2>(acc, sbase + OFF_A + e2 * SLOT + rowoff, lane, s0, s1);
    }
    fence_async_smem();
    wg_bar(wg);
    if (lane == 0) mbar_arrive(bars + 8 * (BAR_STG + wg));
    if (tid == 0) TR(4);
    float own[32];
    {
      float acc[64];
#pragma unroll
      for (int i = 0; i < 64; i++) acc[i] = 0.f;
      attention(acc, c, at, wi);
      if (tid == 0) TR(3);
      bare_groups<128>(acc, c, 4 * (HK0 + HK1), on);
      drain(c);
      if (tid == 0) TR(5);
      named_bar<3>(256);
      const uint32_t pst = sbase + OFF_B + ((30 + on) % NB) * SLOT + wg * 8192 + (tid & 127) * 16;
#pragma unroll
      for (int i = 0; i < 4; i++) {
        uint32_t r[4];
#pragma unroll
        for (int k = 0; k < 4; k++) {
          const int idx = 8 * i + 2 * k;
          const float lo = typeB ? acc[idx] : acc[32 + idx], hi = typeB ? acc[idx + 1] : acc[32 + idx + 1];
          r[k] = pack_bf16(lo, hi);
        }
        sts128(pst + i * 2048, r[0], r[1], r[2], r[3]);
      }
#pragma unroll
      for (int i = 0; i < 32; i++) own[i] = typeB ? acc[32 + i] : acc[i];
      fence_async_smem();
      __syncwarp();
      if (lane == 0) mbar_arrive(bars + 8 * (BAR_STG + wg));
    }
    for (int g = 0; g < 8; g++) {
      const uint32_t a16 = c.a16 + c.ai * (SLOT >> 4);
      const uint32_t b16 = c.b16 + c.bi * (SLOT >> 4) + (g & 1) * 512;
      gemm_wait(c);
      wgmma_fence();
#pragma unroll
      for (int s = 0; s < 4; s++) wgmma_ss<64>(own, desc_sw128<16>(a16 + s * 2), desc_sw128<2048>(b16 + s * 128));
      wgmma_commit();
      c.ai = next_a_slot(c.ae, c.ai); c.ae++;
      if (g & 1) { if (++c.bi == NB) { c.bi = 0; c.bph ^= 1; } }
    }
    wgmma_wait<0>();
    if (tid == 0) TR(6);
    mbar_wait(bars + 8 * BAR_PIN, 0, t0);
    if (tid == 0) TR(7);
    {
      const uint32_t pin = sbase + OFF_B + ((31 + on) % NB) * SLOT + wg * 8192 + (tid & 127) * 16;
      wg_bar(wg);
      const uint32_t ob = sbase + OFF_A + wg * 8192;
      const uint32_t orow = ob + (wi * 16 + (lane & 7) + 8 * ((lane >> 3) & 1)) * 128;
#pragma unroll
      for (int i = 0; i < 4; i++) {
        const uint4 v = lds128(pin + i * 2048);
        const uint32_t r[4] = {v.x, v.y, v.z, v.w};
        uint32_t o[4];
#pragma unroll
        for (int k = 0; k < 4; k++) {
          const int idx = 8 * i + 2 * k;
          o[k] = pack_bf16(own[idx] + __uint_as_float(r[k] << 16), own[idx + 1] + __uint_as_float(r[k] & 0xffff0000u));
        }
        stsm_x4(orow + (((i * 2 + (lane >> 4)) ^ (lane & 7)) << 4), o[0], o[1], o[2], o[3]);
      }
      fence_async_smem();
      __syncwarp();
      if (lane == 0) {
        tma_store_2d(&P.tmOut, j * 64, rb * 128 + warp * 16, ob + wi * 2048);
        bulk_commit(); bulk_wait_all();
      }
    }
    if (tid == 0) TR(8);
  } else {
    asm volatile("setmaxnreg.dec.sync.aligned.u32 40;");
    if (warp == 8) {
      __syncwarp();
      cluster_wait();
      if (lane == 0) {
        int bi = 2; uint32_t bph = 1;
        const int nb = 32 + on + 4;
        for (int eb = 2; eb < nb; eb++) {
          if (eb == 4 || eb == 6) {
            for (int ea = eb - 2 - (eb == 6 ? 1 : 0); ea < (eb == 4 ? 3 : NA); ea++) {
              mbar_expect_tx(bars + 8 * (BAR_FULLA + ea), 16384);
              tma_load_2d(sbase + OFF_A + ea * SLOT, &P.tmX, ea * 64, rb * 128, bars + 8 * (BAR_FULLA + ea));
            }
          }
          const uint32_t fb = bars + 8 * (BAR_FULLB + bi), dst = sbase + OFF_B + bi * SLOT + rank * 8192;
          mbar_wait(bars + 8 * (BAR_EMPTYB + bi), bph, t0);
          if (eb < 16) {
            mbar_expect_tx(fb, typeB ? 12288 : 16384);
            tma_load_3d_mc(dst, &P.tmWqkv, 64 * j, eb * 32 + rank * 16, 0, fb);
            if (!typeB) tma_load_3d_mc(dst + 6144, &P.tmW1a, 0, eb * 32 + rank * 16, 24 + (j >> 1), fb);
          }
          else if (eb < 32) { mbar_expect_tx(fb, 12288); tma_load_3d_mc(dst, &P.tmW1b, 0, (eb - 16) * 32 + rank * 16, 3 * j, fb); }
          else if (eb < 32 + on) { int ow; const int ch = oh_chunk(j, eb - 32, ow); mbar_expect_tx(fb, 16384); tma_load_3d_mc(dst, &P.tmW2, 0, ch * 64 + rank * 32, (j >> 1) * 2, fb); }
          else { mbar_expect_tx(fb, 16384); tma_load_4d_mc(dst, &P.tmWo, 64 * j, 0, eb - 32 - on, rank * 4, fb); }
          if (++bi == NB) { bi = 0; bph ^= 1; }
          if (eb == PFAT) {
            const int b = blockIdx.x;
            l2_prefetch((const uint8_t*)P.w1 + b * 14336, 14336);
            l2_prefetch((const uint8_t*)P.w2 + b * 14336, 14336);
            l2_prefetch((const uint8_t*)P.wo + b * 4096, 4096);
          }
        }
      }
    } else if (warp == 9) {
      cluster_wait();
      if (lane == 0) {
        for (int ea = 0; ea < NA; ea++) mbar_arrive_n(bars + 8 * (BAR_EMPTYA + ea), 2);
        int ai = 0; uint32_t aph = 0xE0;
        const int na = 16 + on + 8;
        unsigned ready = 0;
        for (int ea = NA; ea < na; ea++) {
          const uint32_t fb = bars + 8 * (BAR_FULLA + ai), dst = sbase + OFF_A + ai * SLOT;
          int ch = ea & 7, need = -1;
          if (ea >= 16 + on) { need = 8 + ea - 16 - on; ch = 20 + need; }
          else if (ea >= 19) ch = oh_chunk(j, ea - 16, need);
          if (need >= 0 && !((ready >> need) & 1)) {
            const unsigned* fp = need < 8 ? &g_flag_h[rb * 8 * FS] : need < 16 ? &g_flag_o[rb * 8 * FS] : &g_flag_e[rb * 8 * FS];
            const unsigned tgt = (need & 8) ? ep1 * 8 : ep1 * 2;
            do {
              unsigned v[8];
#pragma unroll
              for (int i = 0; i < 8; i++) v[i] = ld_relaxed(fp + i * FS);
#pragma unroll
              for (int i = 0; i < 8; i++) if ((int)(v[i] - tgt) >= 0) ready |= 1u << (i + (need & 24));
            } while (!((ready >> need) & 1) && clk32() - t0 < TIMEOUT);
            fence_async_global();
          }
          if (ea == 32) mbar_wait(bars + 8 * BAR_ATTDONE, 0, t0);
          mbar_wait(bars + 8 * (BAR_EMPTYA + ai), (aph >> ai) & 1, t0);
          if (ea >= 16 && ea < 19) mbar_arrive(fb);
          else {
            if (ea != 15) mbar_arrive_n(bars + 8 * (BAR_EMPTYA + ai), 2);
            mbar_expect_tx(fb, 16384);
            tma_load_2d(dst, ea < 16 ? &P.tmX : &P.tmHO, ch * 64, rb * 128, fb);
          }
          TR(24 + ea);
          aph ^= 1u << ai;
          ai = next_a_slot(ea, ai);
        }
      }
    } else {
      const int wg = warp - 10;
      cluster_wait();
      {
        const int rowg = rb * 128 + j * 16 + wg * 8;
        const uint32_t xs = sbase + OFF_KV + 32768 + wg * 8192;
        if (lane == 0) {
          mbar_wait(bars + 8 * (BAR_FULLB + 1), 0, t0);
          mbar_expect_tx(bars + 8 * (BAR_GATE + wg), 8192);
          bulk_load(xs, P.x + (size_t)rowg * DM, 8192, bars + 8 * (BAR_GATE + wg));
        }
        const uint4* gw = (const uint4*)P.gate_w;
        const uint4 w0 = __ldg(gw + lane), w1 = __ldg(gw + 32 + lane);
        const uint32_t wa[8] = {w0.x, w0.y, w0.z, w0.w, w1.x, w1.y, w1.z, w1.w};
        mbar_wait(bars + 8 * (BAR_GATE + wg), 0, t0);
        float zz = 0.f;
#pragma unroll 1
        for (int i = 0; i < 8; i++) {
          const uint4 x0 = lds128(xs + i * 1024 + lane * 16), x1 = lds128(xs + i * 1024 + 512 + lane * 16);
          const uint32_t xa[8] = {x0.x, x0.y, x0.z, x0.w, x1.x, x1.y, x1.z, x1.w};
          float z = 0.f;
#pragma unroll
          for (int e = 0; e < 8; e++) {
            z = fmaf(__uint_as_float(xa[e] << 16), __uint_as_float(wa[e] << 16), z);
            z = fmaf(__uint_as_float(xa[e] & 0xffff0000u), __uint_as_float(wa[e] & 0xffff0000u), z);
          }
#pragma unroll
          for (int o = 16; o > 0; o >>= 1) z += __shfl_xor_sync(0xffffffffu, z, o);
          if (lane == i) zz = z;
        }
        if (lane < 8) asm volatile("st.shared.f32 [%0], %1;" ::"r"(sbase + OFF_GST + wg * 32 + lane * 4), "f"(1.f / (1.f + __expf(-zz))) : "memory");
        fence_async_smem();
        __syncwarp();
        if (lane == 0) {
          bulk_store(&g_gate[rowg], sbase + OFF_GST + wg * 32, 32);
          bulk_commit(); bulk_wait_all();
          flag_add(&g_flag_g[rb * FS]);
          if (wg == 0) TR(10);
        }
      }
      if (lane == 0) {
        const uint32_t stg = bars + 8 * (BAR_STG + wg);
        mbar_wait(stg, 0, t0);
        for (int hh = 0; hh < 4; hh++)
          bulk_store(g_kv + ((size_t)(4 * j + hh) * SEQ + rb * 128 + wg * 64) * 64, sbase + OFF_KV + hh * 8192 + wg * 4096, 4096);
        bulk_commit(); bulk_wait_all();
        flag_add(&g_flag_kv[(rb * 8 + j) * FS]);
        if (wg == 0) TR(21);
        if (!typeB) {
          mbar_wait(bars + 8 * (BAR_STE + wg), 0, t0);
          tma_store_2d(&P.tmHOs, (24 + (j >> 1)) * 64, rb * 128 + wg * 64, sbase + OFF_KV + 32768 + wg * 8192);
          bulk_commit(); bulk_wait_all();
          flag_add(&g_flag_e[(rb * 8 + j) * FS]);
          if (wg == 1) flag_wait(&g_flag_e[(rb * 8 + j) * FS], ep1 * 2, t0);
        }
        const int nblk = rb >= 2 ? 3 : rb + 1;
        const uint32_t kvbytes = nblk * 8192;
        const uint8_t* kvsrc = g_kv + ((size_t)(4 * j) * SEQ + (rb + 1 - nblk) * 128) * 64;
        const uint32_t kvdst = sbase + OFF_KV + wg * KVBUF + (3 - nblk) * 8192;
        {
          const unsigned* f0 = &g_flag_kv[(rb * 8 + j) * FS];
          const unsigned* f1 = rb >= 1 ? f0 - 8 * FS : f0;
          const unsigned* f2 = rb >= 2 ? f0 - 16 * FS : f0;
          unsigned v0, v1, v2;
          do { v0 = ld_relaxed(f0); v1 = ld_relaxed(f1); v2 = ld_relaxed(f2); }
          while (((int)(v0 - ep1 * 2) < 0 || (int)(v1 - ep1 * 2) < 0 || (int)(v2 - ep1 * 2) < 0) && clk32() - t0 < TIMEOUT);
        }
        if (wg == 0) TR(11);
        fence_async_global();
        mbar_expect_tx(bars + 8 * (BAR_KVFULL + wg), kvbytes);
        bulk_load(kvdst, kvsrc + (size_t)wg * SEQ * 64, kvbytes, bars + 8 * (BAR_KVFULL + wg));
        for (int ev = 1; ev < 7; ev++) {
          mbar_wait(stg, ev & 1, t0);
          if (ev == 1) {
            for (int i = 0; i < 3; i++)
              tma_store_2d(&P.tmHOs, (3 * j + i) * 64, rb * 128 + wg * 64, sbase + OFF_A + ((16 + i) % NA) * SLOT + wg * 8192);
            bulk_commit(); bulk_wait_all();
            flag_add(&g_flag_h[(rb * 8 + j) * FS]);
            for (int i = 0; i < 3; i++) mbar_arrive(bars + 8 * (BAR_EMPTYA + (16 + i) % NA));
            if (wg == 0) TR(22);
            if (wg == 0) {
              const unsigned old = atomicAdd(&g_done, 1u);
              if (old == gridDim.x - 1) { g_done = 0; *(volatile unsigned*)&g_epoch = ep1; }
            }
          } else if (ev == 6) {
            bulk_store(g_part + (size_t)(rb * 8 + (j ^ 1)) * 16384 + wg * 8192, sbase + OFF_B + ((30 + on) % NB) * SLOT + wg * 8192, 8192);
            bulk_commit(); bulk_wait_all();
            flag_add(&g_flag_p[(rb * 8 + (j ^ 1)) * FS]);
            if (wg == 0) TR(23);
            if (wg == 1) {
              flag_wait(&g_flag_p[(rb * 8 + j) * FS], ep1 * 2, t0);
              fence_async_global();
              mbar_expect_tx(bars + 8 * BAR_PIN, 16384);
              bulk_load(sbase + OFF_B + ((31 + on) % NB) * SLOT, g_part + (size_t)(rb * 8 + j) * 16384, 16384, bars + 8 * BAR_PIN);
            }
          } else {
            const int hh = ev - 2;
            tma_store_2d(&P.tmOs, DFF + hh * 128 + j * 16, rb * 128 + wg * 64, sbase + OFF_A + (15 % NA) * SLOT + wg * 8192 + hh * 2048);
            bulk_commit();
            if (hh == wg) {
              mbar_wait(bars + 8 * (BAR_KVEMPTY + wg), 0, t0);
              mbar_expect_tx(bars + 8 * (BAR_KVFULL + wg), kvbytes);
              bulk_load(kvdst, kvsrc + (size_t)(wg + 2) * SEQ * 64, kvbytes, bars + 8 * (BAR_KVFULL + wg));
            }
            bulk_wait_all();
            flag_add(&g_flag_o[(rb * 8 + hh * 2 + (j >> 2)) * FS]);
            if (hh == 3) mbar_arrive(bars + 8 * (BAR_EMPTYA + 15 % NA));
            if (wg == 0) TR(12 + hh);
          }
        }
      }
    }
  }
}

typedef CUresult (*EncodeFn)(CUtensorMap*, CUtensorMapDataType, cuuint32_t, void*, const cuuint64_t*, const cuuint64_t*, const cuuint32_t*,
                             const cuuint32_t*, CUtensorMapInterleave, CUtensorMapSwizzle, CUtensorMapL2promotion, CUtensorMapFloatOOBfill);

void make_map(EncodeFn enc, CUtensorMap* m, const void* ptr, int rank, const cuuint64_t* dims, const cuuint64_t* strides, const cuuint32_t* box,
              CUtensorMapSwizzle sw = CU_TENSOR_MAP_SWIZZLE_128B) {
  cuuint32_t es[4] = {1, 1, 1, 1};
  enc(m, CU_TENSOR_MAP_DATA_TYPE_BFLOAT16, rank, const_cast<void*>(ptr), dims, strides, box, es, CU_TENSOR_MAP_INTERLEAVE_NONE, sw,
      CU_TENSOR_MAP_L2_PROMOTION_L2_256B, CU_TENSOR_MAP_FLOAT_OOB_FILL_NONE);
}

}

extern "C" void kernel_launch(void* const* d_in, const int* in_sizes, int n_in, void* d_out, int out_size) {
  (void)in_sizes; (void)n_in; (void)out_size;
  static EncodeFn enc = nullptr;
  static void* ho_ptr = nullptr;
  if (!enc) {
    void* fn = nullptr; cudaDriverEntryPointQueryResult st;
    cudaGetDriverEntryPoint("cuTensorMapEncodeTiled", &fn, cudaEnableDefault, &st);
    enc = (EncodeFn)fn;
    cudaGetSymbolAddress(&ho_ptr, g_ho);
    cudaFuncSetAttribute(fused_kernel, cudaFuncAttributeMaxDynamicSharedMemorySize, SMEM_BYTES);
  }
  const __nv_bfloat16* x = (const __nv_bfloat16*)d_in[0];
  const __nv_bfloat16* wqkv = (const __nv_bfloat16*)d_in[1];
  const __nv_bfloat16* wo = (const __nv_bfloat16*)d_in[2];
  const __nv_bfloat16* w1 = (const __nv_bfloat16*)d_in[4];
  const __nv_bfloat16* w2 = (const __nv_bfloat16*)d_in[5];
  const __nv_bfloat16* gate_w = (const __nv_bfloat16*)d_in[6];
  Params P;
  { cuuint64_t d[2] = {DM, SEQ}, s[1] = {DM * 2}; cuuint32_t b[2] = {64, 128}; make_map(enc, &P.tmX, x, 2, d, s, b); }
  { cuuint64_t d[3] = {512, 512, 3}, s[2] = {1536 * 2, 512 * 2}; cuuint32_t b[3] = {64, 16, 3}; make_map(enc, &P.tmWqkv, wqkv, 3, d, s, b); }
  { cuuint64_t d[3] = {64, 512, 28}, s[2] = {DFF * 2, 128}; cuuint32_t b[3] = {64, 16, 1}; make_map(enc, &P.tmW1a, w1, 3, d, s, b);
    b[2] = 3; make_map(enc, &P.tmW1b, w1, 3, d, s, b); }
  { cuuint64_t d[3] = {64, DFF, 8}, s[2] = {DM * 2, 128}; cuuint32_t b[3] = {64, 32, 2}; make_map(enc, &P.tmW2, w2, 3, d, s, b); }
  { cuuint64_t d[4] = {DM, 16, 4, 8}, s[3] = {DM * 2, 16 * DM * 2, 64 * DM * 2}; cuuint32_t b[4] = {64, 16, 1, 4}; make_map(enc, &P.tmWo, wo, 4, d, s, b); }
  { cuuint64_t d[2] = {KHO, SEQ}, s[1] = {KHO * 2}; cuuint32_t b[2] = {64, 128}; make_map(enc, &P.tmHO, ho_ptr, 2, d, s, b);
    b[1] = 64; make_map(enc, &P.tmHOs, ho_ptr, 2, d, s, b);
    b[0] = 16; make_map(enc, &P.tmOs, ho_ptr, 2, d, s, b, CU_TENSOR_MAP_SWIZZLE_NONE); }
  { cuuint64_t d[2] = {DM, SEQ}, s[1] = {DM * 2}; cuuint32_t b[2] = {64, 16}; make_map(enc, &P.tmOut, d_out, 2, d, s, b); }
  P.x = x; P.gate_w = gate_w; P.w1 = w1; P.w2 = w2; P.wo = wo; P.out = (__nv_bfloat16*)d_out;
  fused_kernel<<<128, 384, SMEM_BYTES>>>(P);
}
```

```cpp
#include <cuda_runtime.h>
#include <cuda_bf16.h>
#include <cuda.h>
#include <stdint.h>

#define DEVI __device__ __forceinline__

namespace {

constexpr int SEQ = 2048, DM = 512, DFF = 1792, KHO = 2304;
constexpr int NA = 5, NB = 6, SLOT = 16384, KVBUF = 24576;
constexpr int NA2 = 8;
constexpr int OFF_B = 0, OFF_A = NB * SLOT, OFF_KV = OFF_A + NA * SLOT, OFF_BAR = OFF_KV + 2 * KVBUF;
constexpr int OFF_GST = OFF_BAR + 512;
constexpr int OFF_GIN = OFF_BAR + 1024;
constexpr int SMEM_BYTES = OFF_BAR + 1536 + 1024;
constexpr uint32_t TIMEOUT = 1u << 28;
#define WAIT_HINT_NS 20000u
#define PFAT 8
#define HK0 2
#define HK1 1
constexpr int FS = 8;

constexpr int BAR_FULLA = 0, BAR_EMPTYA = BAR_FULLA + NA2, BAR_FULLB = BAR_EMPTYA + NA2, BAR_EMPTYB = BAR_FULLB + NB,
              BAR_KVFULL = BAR_EMPTYB + NB, BAR_KVEMPTY = BAR_KVFULL + 2, BAR_STG = BAR_KVEMPTY + 2, BAR_PIN = BAR_STG + 2, BAR_GATE = BAR_PIN + 1, BAR_STE = BAR_GATE + 2, BAR_ATTDONE = BAR_STE + 2, BAR_GIN = BAR_ATTDONE + 1;

__device__ __align__(1024) uint8_t g_kv[32 * SEQ * 64];
__device__ __align__(1024) __nv_bfloat16 g_ho[SEQ * KHO];
__device__ __align__(1024) uint8_t g_part[128 * 16384];
__device__ __align__(128) float g_gate[SEQ];
__device__ unsigned g_flag_kv[128 * FS], g_flag_h[128 * FS], g_flag_o[128 * FS], g_flag_g[16 * FS], g_flag_p[128 * FS], g_flag_e[128 * FS];
__device__ unsigned g_epoch, g_done;
#define TR(i) do {} while (0)

struct Params {
  CUtensorMap tmX, tmWqkv, tmW1a, tmW1b, tmW2, tmWo, tmHO, tmHOs, tmOs, tmOut;
  const __nv_bfloat16* x;
  const __nv_bfloat16* gate_w;
  const __nv_bfloat16* w1;
  const __nv_bfloat16* w2;
  const __nv_bfloat16* wo;
  __nv_bfloat16* out;
};

DEVI uint32_t smem_u32(const void* p) { return (uint32_t)__cvta_generic_to_shared(p); }
DEVI uint32_t clk32() { uint32_t c; asm volatile("mov.u32 %0, %%clock;" : "=r"(c)); return c; }
DEVI void mbar_init(uint32_t bar, uint32_t cnt) { asm volatile("mbarrier.init.shared::cta.b64 [%0], %1;" ::"r"(bar), "r"(cnt)); }
DEVI void mbar_expect_tx(uint32_t bar, uint32_t bytes) { asm volatile("mbarrier.arrive.expect_tx.shared::cta.b64 _, [%0], %1;" ::"r"(bar), "r"(bytes) : "memory"); }
DEVI void mbar_arrive(uint32_t bar) { asm volatile("mbarrier.arrive.shared::cta.b64 _, [%0];" ::"r"(bar) : "memory"); }
DEVI void mbar_arrive_n(uint32_t bar, uint32_t n) { asm volatile("mbarrier.arrive.shared::cta.b64 _, [%0], %1;" ::"r"(bar), "r"(n) : "memory"); }
DEVI void mbar_arrive_cluster(uint32_t bar, uint32_t cta) {
  asm volatile("{ .reg .b32 ra; mapa.shared::cluster.u32 ra, %0, %1; mbarrier.arrive.shared::cluster.b64 _, [ra]; }" ::"r"(bar), "r"(cta) : "memory");
}
DEVI void mbar_wait(uint32_t bar, uint32_t parity, uint32_t t0) {
  asm volatile("{ .reg .pred p; .reg .u32 c;\n"
               "mbarrier.try_wait.parity.shared::cta.b64 p, [%0], %1;\n"
               "@p bra DONE_%=;\n"
               "WAIT_%=:\n"
               "mbarrier.try_wait.parity.shared::cta.b64 p, [%0], %1, %4;\n"
               "@p bra DONE_%=;\n"
               "mov.u32 c, %%clock; sub.u32 c, c, %2; setp.lt.u32 p, c, %3;\n"
               "@p bra WAIT_%=;\n"
               "DONE_%=: }" ::"r"(bar), "r"(parity), "r"(t0), "n"(TIMEOUT), "r"(WAIT_HINT_NS) : "memory");
}
DEVI unsigned ld_relaxed(const unsigned* p) { unsigned v; asm volatile("ld.relaxed.gpu.global.u32 %0, [%1];" : "=r"(v) : "l"(p) : "memory"); return v; }
DEVI void flag_wait(const unsigned* p, unsigned target, uint32_t t0) {
  while ((int)(ld_relaxed(p) - target) < 0) { if (clk32() - t0 > TIMEOUT) break; }
}
DEVI void flag_add(unsigned* p) { asm volatile("red.relaxed.gpu.global.add.u32 [%0], 1;" ::"l"(p) : "memory"); }
DEVI void fence_async_smem() { asm volatile("fence.proxy.async.shared::cta;" ::: "memory"); }
DEVI void fence_async_global() { asm volatile("fence.proxy.async.global;" ::: "memory"); }
DEVI void tma_load_2d(uint32_t dst, const CUtensorMap* m, int c0, int c1, uint32_t bar) {
  asm volatile("cp.async.bulk.tensor.2d.shared::cluster.global.mbarrier::complete_tx::bytes [%0], [%1, {%3, %4}], [%2];" ::"r"(dst), "l"(m), "r"(bar), "r"(c0), "r"(c1) : "memory");
}
DEVI void tma_load_3d(uint32_t dst, const CUtensorMap* m, int c0, int c1, int c2, uint32_t bar) {
  asm volatile("cp.async.bulk.tensor.3d.shared::cluster.global.mbarrier::complete_tx::bytes [%0], [%1, {%3, %4, %5}], [%2];"
               ::"r"(dst), "l"(m), "r"(bar), "r"(c0), "r"(c1), "r"(c2) : "memory");
}
DEVI void tma_load_3d_mc(uint32_t dst, const CUtensorMap* m, int c0, int c1, int c2, uint32_t bar) {
  asm volatile("cp.async.bulk.tensor.3d.shared::cluster.global.mbarrier::complete_tx::bytes.multicast::cluster [%0], [%1, {%3, %4, %5}], [%2], %6;"
               ::"r"(dst), "l"(m), "r"(bar), "r"(c0), "r"(c1), "r"(c2), "h"((uint16_t)3) : "memory");
}
DEVI void tma_load_4d_mc(uint32_t dst, const CUtensorMap* m, int c0, int c1, int c2, int c3, uint32_t bar) {
  asm volatile("cp.async.bulk.tensor.4d.shared::cluster.global.mbarrier::complete_tx::bytes.multicast::cluster [%0], [%1, {%3, %4, %5, %6}], [%2], %7;"
               ::"r"(dst), "l"(m), "r"(bar), "r"(c0), "r"(c1), "r"(c2), "r"(c3), "h"((uint16_t)3) : "memory");
}
DEVI void tma_store_2d(const CUtensorMap* m, int c0, int c1, uint32_t src) {
  asm volatile("cp.async.bulk.tensor.2d.global.shared::cta.bulk_group [%0, {%1, %2}], [%3];" ::"l"(m), "r"(c0), "r"(c1), "r"(src) : "memory");
}
DEVI void bulk_store(void* dst, uint32_t src, uint32_t bytes) {
  asm volatile("cp.async.bulk.global.shared::cta.bulk_group [%0], [%1], %2;" ::"l"(dst), "r"(src), "r"(bytes) : "memory");
}
DEVI void bulk_load(uint32_t dst, const void* src, uint32_t bytes, uint32_t bar) {
  asm volatile("cp.async.bulk.shared::cluster.global.mbarrier::complete_tx::bytes [%0], [%1], %2, [%3];" ::"r"(dst), "l"(src), "r"(bytes), "r"(bar) : "memory");
}
DEVI void bulk_commit() { asm volatile("cp.async.bulk.commit_group;" ::: "memory"); }
DEVI void bulk_wait_all() { asm volatile("cp.async.bulk.wait_group 0;" ::: "memory"); }
DEVI void l2_prefetch(const void* p, uint32_t bytes) { asm volatile("cp.async.bulk.prefetch.L2.global [%0], %1;" ::"l"(p), "r"(bytes) : "memory"); }
DEVI void cluster_arrive() { asm volatile("barrier.cluster.arrive.relaxed.aligned;" ::: "memory"); }
DEVI void cluster_wait() { asm volatile("barrier.cluster.wait.aligned;" ::: "memory"); }
template <int ID> DEVI void named_bar(int n) { asm volatile("bar.sync %0, %1;" ::"n"(ID), "r"(n) : "memory"); }
DEVI void wg_bar(int wg) { if (wg == 0) named_bar<1>(128); else named_bar<2>(128); }
DEVI void wgmma_fence() { asm volatile("wgmma.fence.sync.aligned;" ::: "memory"); }
DEVI void wgmma_commit() { asm volatile("wgmma.commit_group.sync.aligned;" ::: "memory"); }
template <int N> DEVI void wgmma_wait() { asm volatile("wgmma.wait_group.sync.aligned %0;" ::"n"(N) : "memory"); }
template <uint32_t LBO> DEVI uint64_t desc_sw128(uint32_t a16) {
  return ((uint64_t)(0x40000000u | (1024 >> 4)) << 32) | (a16 + ((LBO >> 4) << 16));
}
DEVI uint64_t desc_sw64(uint32_t a16) {
  return ((uint64_t)(0x80000000u | (512 >> 4)) << 32) | (a16 + ((512 >> 4) << 16));
}
DEVI uint32_t pack_bf16(float lo, float hi) { uint32_t r; asm("cvt.rn.bf16x2.f32 %0, %1, %2;" : "=r"(r) : "f"(hi), "f"(lo)); return r; }
DEVI void stsm_x4(uint32_t addr, uint32_t r0, uint32_t r1, uint32_t r2, uint32_t r3) {
  asm volatile("stmatrix.sync.aligned.m8n8.x4.shared.b16 [%0], {%1, %2, %3, %4};" ::"r"(addr), "r"(r0), "r"(r1), "r"(r2), "r"(r3) : "memory");
}
DEVI void sts128(uint32_t addr, uint32_t r0, uint32_t r1, uint32_t r2, uint32_t r3) {
  asm volatile("st.shared.v4.b32 [%0], {%1, %2, %3, %4};" ::"r"(addr), "r"(r0), "r"(r1), "r"(r2), "r"(r3) : "memory");
}
DEVI uint4 lds128(uint32_t addr) {
  uint4 v; asm volatile("ld.shared.v4.b32 {%0, %1, %2, %3}, [%4];" : "=r"(v.x), "=r"(v.y), "=r"(v.z), "=r"(v.w) : "r"(addr) : "memory"); return v;
}
DEVI float ex2(float x) { float y; asm("ex2.approx.ftz.f32 %0, %1;" : "=f"(y) : "f"(x)); return y; }

DEVI void wgmma_ss_n64(float (&d)[32], uint64_t da, uint64_t db) {
  asm volatile("wgmma.mma_async.sync.aligned.m64n64k16.f32.bf16.bf16 {%0, %1, %2, %3, %4, %5, %6, %7, %8, %9, %10, %11, %12, %13, %14, %15, %16, %17, %18, %19, %20, %21, %22, %23, %24, %25, %26, %27, %28, %29, %30, %31}, %32, %33, 1, 1, 1, 0, 1;"
    : "+f"(d[0]), "+f"(d[1]), "+f"(d[2]), "+f"(d[3]), "+f"(d[4]), "+f"(d[5]), "+f"(d[6]), "+f"(d[7]), "+f"(d[8]), "+f"(d[9]), "+f"(d[10]), "+f"(d[11]), "+f"(d[12]), "+f"(d[13]), "+f"(d[14]), "+f"(d[15]), "+f"(d[16]), "+f"(d[17]), "+f"(d[18]), "+f"(d[19]), "+f"(d[20]), "+f"(d[21]), "+f"(d[22]), "+f"(d[23]), "+f"(d[24]), "+f"(d[25]), "+f"(d[26]), "+f"(d[27]), "+f"(d[28]), "+f"(d[29]), "+f"(d[30]), "+f"(d[31])
    : "l"(da), "l"(db));
}
DEVI void wgmma_ss_n128(float (&d)[64], uint64_t da, uint64_t db) {
  asm volatile("wgmma.mma_async.sync.aligned.m64n128k16.f32.bf16.bf16 {%0, %1, %2, %3, %4, %5, %6, %7, %8, %9, %10, %11, %12, %13, %14, %15, %16, %17, %18, %19, %20, %21, %22, %23, %24, %25, %26, %27, %28, %29, %30, %31, %32, %33, %34, %35, %36, %37, %38, %39, %40, %41, %42, %43, %44, %45, %46, %47, %48, %49, %50, %51, %52, %53, %54, %55, %56, %57, %58, %59, %60, %61, %62, %63}, %64, %65, 1, 1, 1, 0, 1;"
    : "+f"(d[0]), "+f"(d[1]), "+f"(d[2]), "+f"(d[3]), "+f"(d[4]), "+f"(d[5]), "+f"(d[6]), "+f"(d[7]), "+f"(d[8]), "+f"(d[9]), "+f"(d[10]), "+f"(d[11]), "+f"(d[12]), "+f"(d[13]), "+f"(d[14]), "+f"(d[15]), "+f"(d[16]), "+f"(d[17]), "+f"(d[18]), "+f"(d[19]), "+f"(d[20]), "+f"(d[21]), "+f"(d[22]), "+f"(d[23]), "+f"(d[24]), "+f"(d[25]), "+f"(d[26]), "+f"(d[27]), "+f"(d[28]), "+f"(d[29]), "+f"(d[30]), "+f"(d[31]), "+f"(d[32]), "+f"(d[33]), "+f"(d[34]), "+f"(d[35]), "+f"(d[36]), "+f"(d[37]), "+f"(d[38]), "+f"(d[39]), "+f"(d[40]), "+f"(d[41]), "+f"(d[42]), "+f"(d[43]), "+f"(d[44]), "+f"(d[45]), "+f"(d[46]), "+f"(d[47]), "+f"(d[48]), "+f"(d[49]), "+f"(d[50]), "+f"(d[51]), "+f"(d[52]), "+f"(d[53]), "+f"(d[54]), "+f"(d[55]), "+f"(d[56]), "+f"(d[57]), "+f"(d[58]), "+f"(d[59]), "+f"(d[60]), "+f"(d[61]), "+f"(d[62]), "+f"(d[63])
    : "l"(da), "l"(db));
}
DEVI void wgmma_ss_n192(float (&d)[96], uint64_t da, uint64_t db) {
  asm volatile("wgmma.mma_async.sync.aligned.m64n192k16.f32.bf16.bf16 {%0, %1, %2, %3, %4, %5, %6, %7, %8, %9, %10, %11, %12, %13, %14, %15, %16, %17, %18, %19, %20, %21, %22, %23, %24, %25, %26, %27, %28, %29, %30, %31, %32, %33, %34, %35, %36, %37, %38, %39, %40, %41, %42, %43, %44, %45, %46, %47, %48, %49, %50, %51, %52, %53, %54, %55, %56, %57, %58, %59, %60, %61, %62, %63, %64, %65, %66, %67, %68, %69, %70, %71, %72, %73, %74, %75, %76, %77, %78, %79, %80, %81, %82, %83, %84, %85, %86, %87, %88, %89, %90, %91, %92, %93, %94, %95}, %96, %97, 1, 1, 1, 0, 1;"
    : "+f"(d[0]), "+f"(d[1]), "+f"(d[2]), "+f"(d[3]), "+f"(d[4]), "+f"(d[5]), "+f"(d[6]), "+f"(d[7]), "+f"(d[8]), "+f"(d[9]), "+f"(d[10]), "+f"(d[11]), "+f"(d[12]), "+f"(d[13]), "+f"(d[14]), "+f"(d[15]), "+f"(d[16]), "+f"(d[17]), "+f"(d[18]), "+f"(d[19]), "+f"(d[20]), "+f"(d[21]), "+f"(d[22]), "+f"(d[23]), "+f"(d[24]), "+f"(d[25]), "+f"(d[26]), "+f"(d[27]), "+f"(d[28]), "+f"(d[29]), "+f"(d[30]), "+f"(d[31]), "+f"(d[32]), "+f"(d[33]), "+f"(d[34]), "+f"(d[35]), "+f"(d[36]), "+f"(d[37]), "+f"(d[38]), "+f"(d[39]), "+f"(d[40]), "+f"(d[41]), "+f"(d[42]), "+f"(d[43]), "+f"(d[44]), "+f"(d[45]), "+f"(d[46]), "+f"(d[47]), "+f"(d[48]), "+f"(d[49]), "+f"(d[50]), "+f"(d[51]), "+f"(d[52]), "+f"(d[53]), "+f"(d[54]), "+f"(d[55]), "+f"(d[56]), "+f"(d[57]), "+f"(d[58]), "+f"(d[59]), "+f"(d[60]), "+f"(d[61]), "+f"(d[62]), "+f"(d[63]), "+f"(d[64]), "+f"(d[65]), "+f"(d[66]), "+f"(d[67]), "+f"(d[68]), "+f"(d[69]), "+f"(d[70]), "+f"(d[71]), "+f"(d[72]), "+f"(d[73]), "+f"(d[74]), "+f"(d[75]), "+f"(d[76]), "+f"(d[77]), "+f"(d[78]), "+f"(d[79]), "+f"(d[80]), "+f"(d[81]), "+f"(d[82]), "+f"(d[83]), "+f"(d[84]), "+f"(d[85]), "+f"(d[86]), "+f"(d[87]), "+f"(d[88]), "+f"(d[89]), "+f"(d[90]), "+f"(d[91]), "+f"(d[92]), "+f"(d[93]), "+f"(d[94]), "+f"(d[95])
    : "l"(da), "l"(db));
}
DEVI void wgmma_ss_n256(float (&d)[128], uint64_t da, uint64_t db) {
  asm volatile("wgmma.mma_async.sync.aligned.m64n256k16.f32.bf16.bf16 {%0, %1, %2, %3, %4, %5, %6, %7, %8, %9, %10, %11, %12, %13, %14, %15, %16, %17, %18, %19, %20, %21, %22, %23, %24, %25, %26, %27, %28, %29, %30, %31, %32, %33, %34, %35, %36, %37, %38, %39, %40, %41, %42, %43, %44, %45, %46, %47, %48, %49, %50, %51, %52, %53, %54, %55, %56, %57, %58, %59, %60, %61, %62, %63, %64, %65, %66, %67, %68, %69, %70, %71, %72, %73, %74, %75, %76, %77, %78, %79, %80, %81, %82, %83, %84, %85, %86, %87, %88, %89, %90, %91, %92, %93, %94, %95, %96, %97, %98, %99, %100, %101, %102, %103, %104, %105, %106, %107, %108, %109, %110, %111, %112, %113, %114, %115, %116, %117, %118, %119, %120, %121, %122, %123, %124, %125, %126, %127}, %128, %129, 1, 1, 1, 0, 1;"
    : "+f"(d[0]), "+f"(d[1]), "+f"(d[2]), "+f"(d[3]), "+f"(d[4]), "+f"(d[5]), "+f"(d[6]), "+f"(d[7]), "+f"(d[8]), "+f"(d[9]), "+f"(d[10]), "+f"(d[11]), "+f"(d[12]), "+f"(d[13]), "+f"(d[14]), "+f"(d[15]), "+f"(d[16]), "+f"(d[17]), "+f"(d[18]), "+f"(d[19]), "+f"(d[20]), "+f"(d[21]), "+f"(d[22]), "+f"(d[23]), "+f"(d[24]), "+f"(d[25]), "+f"(d[26]), "+f"(d[27]), "+f"(d[28]), "+f"(d[29]), "+f"(d[30]), "+f"(d[31]), "+f"(d[32]), "+f"(d[33]), "+f"(d[34]), "+f"(d[35]), "+f"(d[36]), "+f"(d[37]), "+f"(d[38]), "+f"(d[39]), "+f"(d[40]), "+f"(d[41]), "+f"(d[42]), "+f"(d[43]), "+f"(d[44]), "+f"(d[45]), "+f"(d[46]), "+f"(d[47]), "+f"(d[48]), "+f"(d[49]), "+f"(d[50]), "+f"(d[51]), "+f"(d[52]), "+f"(d[53]), "+f"(d[54]), "+f"(d[55]), "+f"(d[56]), "+f"(d[57]), "+f"(d[58]), "+f"(d[59]), "+f"(d[60]), "+f"(d[61]), "+f"(d[62]), "+f"(d[63]), "+f"(d[64]), "+f"(d[65]), "+f"(d[66]), "+f"(d[67]), "+f"(d[68]), "+f"(d[69]), "+f"(d[70]), "+f"(d[71]), "+f"(d[72]), "+f"(d[73]), "+f"(d[74]), "+f"(d[75]), "+f"(d[76]), "+f"(d[77]), "+f"(d[78]), "+f"(d[79]), "+f"(d[80]), "+f"(d[81]), "+f"(d[82]), "+f"(d[83]), "+f"(d[84]), "+f"(d[85]), "+f"(d[86]), "+f"(d[87]), "+f"(d[88]), "+f"(d[89]), "+f"(d[90]), "+f"(d[91]), "+f"(d[92]), "+f"(d[93]), "+f"(d[94]), "+f"(d[95]), "+f"(d[96]), "+f"(d[97]), "+f"(d[98]), "+f"(d[99]), "+f"(d[100]), "+f"(d[101]), "+f"(d[102]), "+f"(d[103]), "+f"(d[104]), "+f"(d[105]), "+f"(d[106]), "+f"(d[107]), "+f"(d[108]), "+f"(d[109]), "+f"(d[110]), "+f"(d[111]), "+f"(d[112]), "+f"(d[113]), "+f"(d[114]), "+f"(d[115]), "+f"(d[116]), "+f"(d[117]), "+f"(d[118]), "+f"(d[119]), "+f"(d[120]), "+f"(d[121]), "+f"(d[122]), "+f"(d[123]), "+f"(d[124]), "+f"(d[125]), "+f"(d[126]), "+f"(d[127])
    : "l"(da), "l"(db));
}
DEVI void wgmma_qk64(float (&d)[32], uint32_t a0, uint32_t a1, uint32_t a2, uint32_t a3, uint64_t db) {
  asm volatile("wgmma.mma_async.sync.aligned.m64n64k16.f32.bf16.bf16 {%0, %1, %2, %3, %4, %5, %6, %7, %8, %9, %10, %11, %12, %13, %14, %15, %16, %17, %18, %19, %20, %21, %22, %23, %24, %25, %26, %27, %28, %29, %30, %31}, {%32, %33, %34, %35}, %36, 0, 1, 1, 0;"
    : "=f"(d[0]), "=f"(d[1]), "=f"(d[2]), "=f"(d[3]), "=f"(d[4]), "=f"(d[5]), "=f"(d[6]), "=f"(d[7]), "=f"(d[8]), "=f"(d[9]), "=f"(d[10]), "=f"(d[11]), "=f"(d[12]), "=f"(d[13]), "=f"(d[14]), "=f"(d[15]), "=f"(d[16]), "=f"(d[17]), "=f"(d[18]), "=f"(d[19]), "=f"(d[20]), "=f"(d[21]), "=f"(d[22]), "=f"(d[23]), "=f"(d[24]), "=f"(d[25]), "=f"(d[26]), "=f"(d[27]), "=f"(d[28]), "=f"(d[29]), "=f"(d[30]), "=f"(d[31])
    : "r"(a0), "r"(a1), "r"(a2), "r"(a3), "l"(db));
}
DEVI void wgmma_qk128(float (&d)[64], uint32_t a0, uint32_t a1, uint32_t a2, uint32_t a3, uint64_t db) {
  asm volatile("wgmma.mma_async.sync.aligned.m64n128k16.f32.bf16.bf16 {%0, %1, %2, %3, %4, %5, %6, %7, %8, %9, %10, %11, %12, %13, %14, %15, %16, %17, %18, %19, %20, %21, %22, %23, %24, %25, %26, %27, %28, %29, %30, %31, %32, %33, %34, %35, %36, %37, %38, %39, %40, %41, %42, %43, %44, %45, %46, %47, %48, %49, %50, %51, %52, %53, %54, %55, %56, %57, %58, %59, %60, %61, %62, %63}, {%64, %65, %66, %67}, %68, 0, 1, 1, 0;"
    : "=f"(d[0]), "=f"(d[1]), "=f"(d[2]), "=f"(d[3]), "=f"(d[4]), "=f"(d[5]), "=f"(d[6]), "=f"(d[7]), "=f"(d[8]), "=f"(d[9]), "=f"(d[10]), "=f"(d[11]), "=f"(d[12]), "=f"(d[13]), "=f"(d[14]), "=f"(d[15]), "=f"(d[16]), "=f"(d[17]), "=f"(d[18]), "=f"(d[19]), "=f"(d[20]), "=f"(d[21]), "=f"(d[22]), "=f"(d[23]), "=f"(d[24]), "=f"(d[25]), "=f"(d[26]), "=f"(d[27]), "=f"(d[28]), "=f"(d[29]), "=f"(d[30]), "=f"(d[31]), "=f"(d[32]), "=f"(d[33]), "=f"(d[34]), "=f"(d[35]), "=f"(d[36]), "=f"(d[37]), "=f"(d[38]), "=f"(d[39]), "=f"(d[40]), "=f"(d[41]), "=f"(d[42]), "=f"(d[43]), "=f"(d[44]), "=f"(d[45]), "=f"(d[46]), "=f"(d[47]), "=f"(d[48]), "=f"(d[49]), "=f"(d[50]), "=f"(d[51]), "=f"(d[52]), "=f"(d[53]), "=f"(d[54]), "=f"(d[55]), "=f"(d[56]), "=f"(d[57]), "=f"(d[58]), "=f"(d[59]), "=f"(d[60]), "=f"(d[61]), "=f"(d[62]), "=f"(d[63])
    : "r"(a0), "r"(a1), "r"(a2), "r"(a3), "l"(db));
}
DEVI void wgmma_pv(float (&d)[8], uint32_t a0, uint32_t a1, uint32_t a2, uint32_t a3, uint64_t db) {
  asm volatile("wgmma.mma_async.sync.aligned.m64n16k16.f32.bf16.bf16 {%0, %1, %2, %3, %4, %5, %6, %7}, {%8, %9, %10, %11}, %12, 1, 1, 1, 1;"
    : "+f"(d[0]), "+f"(d[1]), "+f"(d[2]), "+f"(d[3]), "+f"(d[4]), "+f"(d[5]), "+f"(d[6]), "+f"(d[7])
    : "r"(a0), "r"(a1), "r"(a2), "r"(a3), "l"(db));
}
DEVI void wgmma_pv0(float (&d)[8], uint32_t a0, uint32_t a1, uint32_t a2, uint32_t a3, uint64_t db) {
  asm volatile("wgmma.mma_async.sync.aligned.m64n16k16.f32.bf16.bf16 {%0, %1, %2, %3, %4, %5, %6, %7}, {%8, %9, %10, %11}, %12, 0, 1, 1, 1;"
    : "=f"(d[0]), "=f"(d[1]), "=f"(d[2]), "=f"(d[3]), "=f"(d[4]), "=f"(d[5]), "=f"(d[6]), "=f"(d[7])
    : "r"(a0), "r"(a1), "r"(a2), "r"(a3), "l"(db));
}

template <int N> DEVI void wgmma_ss(float (&d)[N / 2], uint64_t da, uint64_t db) {
  if constexpr (N == 64) wgmma_ss_n64(d, da, db);
  else if constexpr (N == 128) wgmma_ss_n128(d, da, db);
  else if constexpr (N == 192) wgmma_ss_n192(d, da, db);
  else wgmma_ss_n256(d, da, db);
}

DEVI int oh_chunk(int j, int i, int& need) {
  if (j & 1) {
    if (i >= 3 && i < 7) { need = 16 + 2 * (i - 3); return 24 + (i - 3); }
    if (i >= 7) i -= 4;
  }
  const int g = i / 3, o = (j + 2 * g) & 7;
  need = o;
  return 3 * o + (i - 3 * g);
}

DEVI int next_a_slot(int e, int ai) {
  e++;
  return e < 16 ? (ai == NA - 1 ? 0 : ai + 1) : e < 32 ? 1 + (e & 3) : (e - 27) & 7;
}

struct Ctx {
  uint32_t sbase, bars, peer, t0, a16, b16;
  int wg, lane;
  int ai, bi; uint32_t aph, bph;
  int brem, ae;
  int pa2, pb2;
  int pa, pb;
};

DEVI void release_prev(Ctx& c) {
  if (c.pb >= 0) {
    if (c.lane == 0) mbar_arrive(c.bars + 8 * (BAR_EMPTYB + c.pb));
    if (c.lane == 1) mbar_arrive_cluster(c.bars + 8 * (BAR_EMPTYB + c.pb), c.peer);
  }
  if (c.pa >= 0 && c.lane == 2) mbar_arrive(c.bars + 8 * (BAR_EMPTYA + c.pa));
}

DEVI void gemm_wait(Ctx& c) {
  asm volatile("{ .reg .pred p, q; .reg .u32 c;\n"
               "WAIT_%=:\n"
               "mbarrier.try_wait.parity.shared::cta.b64 p, [%0], %1;\n"
               "mbarrier.try_wait.parity.shared::cta.b64 q, [%2], %3;\n"
               "and.pred p, p, q;\n"
               "@p bra DONE_%=;\n"
               "mov.u32 c, %%clock; sub.u32 c, c, %4; setp.lt.u32 p, c, %5;\n"
               "@p bra WAIT_%=;\n"
               "DONE_%=: }" ::"r"(c.bars + 8 * (BAR_FULLA + c.ai)), "r"((c.aph >> c.ai) & 1), "r"(c.bars + 8 * (BAR_FULLB + c.bi)), "r"(c.bph), "r"(c.t0), "n"(TIMEOUT) : "memory");
}
template <int N>
DEVI void gemm_group(float (&acc)[N / 2], Ctx& c, int g, int& npa, int& npb) {
  const uint32_t a16 = c.a16 + c.ai * (SLOT >> 4);
  const uint32_t b16 = c.b16 + c.bi * (SLOT >> 4);
  bool adv;
  if constexpr (N >= 192) {
    const uint32_t a2 = a16 + (g & 1) * 4;
    wgmma_ss<N>(acc, desc_sw128<16>(a2), desc_sw128<2048>(b16));
    wgmma_ss<N>(acc, desc_sw128<16>(a2 + 2), desc_sw128<2048>(b16 + 512));
    adv = g & 1;
  } else {
#pragma unroll
    for (int s = 0; s < 4; s++) wgmma_ss<N>(acc, desc_sw128<16>(a16 + s * 2), desc_sw128<4096>(b16 + (s >> 1) * 512 + (s & 1) * 128));
    adv = true;
  }
  wgmma_commit();
  npb = c.brem > 0 ? c.bi : -1;
  c.brem--;
  if (++c.bi == NB) { c.bi = 0; c.bph ^= 1; }
  npa = -1;
  if (adv) { npa = c.ai; c.aph ^= 1u << c.ai; c.ai = next_a_slot(c.ae, c.ai); c.ae++; }
}

template <int N>
DEVI void bare_groups(float (&acc)[N / 2], Ctx& c, int g0, int g1) {
  for (int g = g0; g < g1; g++) {
    int npa, npb;
    gemm_wait(c);
    wgmma_fence();
    gemm_group<N>(acc, c, g, npa, npb);
    wgmma_wait<1>();
    release_prev(c);
    c.pa = npa; c.pb = npb;
  }
}
DEVI void drain(Ctx& c) {
  wgmma_wait<0>();
  release_prev(c);
  c.pa = c.pb = -1;
}

constexpr float SC = 0.25f * 1.4426950408889634f;

#define ONCE _Pragma("unroll 1") for (unsigned once_ = 0; once_ < gridDim.y; once_++)

struct Attn {
  uint32_t q[4][4];
  uint32_t nm[4];
  float g0, g1;
  int cmin;
  int rowc;
};

template <int O0, int NS>
DEVI void kill32(float (&S)[NS]) {
#pragma unroll
  for (int i = 0; i < 32; i++) S[O0 + i] = __int_as_float(0xff800000);
}
DEVI void row_max(const float (&S)[64], float& x0, float& x1) {
#pragma unroll
  for (int n = 0; n < 16; n++) {
    x0 = fmaxf(x0, fmaxf(S[4 * n], S[4 * n + 1])); x1 = fmaxf(x1, fmaxf(S[4 * n + 2], S[4 * n + 3]));
  }
}
template <int K, bool PRE = false>
DEVI void exp8(const float (&S)[64], uint32_t (&P)[4], float n0, float n1, float (&l)[4]) {
  float e[8];
#pragma unroll
  for (int i = 0; i < 8; i++) e[i] = ex2(PRE ? S[8 * K + i] : fmaf(S[8 * K + i], SC, (i & 2) ? n1 : n0));
  l[0] += e[0]; l[1] += e[1]; l[2] += e[2]; l[3] += e[3];
  l[0] += e[4]; l[1] += e[5]; l[2] += e[6]; l[3] += e[7];
#pragma unroll
  for (int i = 0; i < 4; i++) P[i] = pack_bf16(e[2 * i], e[2 * i + 1]) | (__float_as_uint(l[i]) & blockIdx.y);
}
DEVI void merge_fl(float (&S)[64], const float (&F)[32], int rowc) {
#pragma unroll
  for (int n = 0; n < 8; n++) {
    if (n * 8 > rowc) S[32 + 4 * n] = F[4 * n];
    if (n * 8 + 1 > rowc) S[32 + 4 * n + 1] = F[4 * n + 1];
    if (n * 8 > rowc + 8) S[32 + 4 * n + 2] = F[4 * n + 2];
    if (n * 8 + 1 > rowc + 8) S[32 + 4 * n + 3] = F[4 * n + 3];
  }
}
DEVI bool wg_any(int wg, bool v) {
  uint32_t r;
  if (wg == 0) asm volatile("{ .reg .pred p, q; setp.ne.u32 p, %1, 0; bar.red.or.pred q, 1, 128, p; selp.u32 %0, 1, 0, q; }" : "=r"(r) : "r"((uint32_t)v) : "memory");
  else asm volatile("{ .reg .pred p, q; setp.ne.u32 p, %1, 0; bar.red.or.pred q, 2, 128, p; selp.u32 %0, 1, 0, q; }" : "=r"(r) : "r"((uint32_t)v) : "memory");
  return r != 0;
}

DEVI void qk_a(float (&S)[64], float (&F)[32], const uint32_t (&q)[4], uint32_t kb) {
  wgmma_fence();
  wgmma_qk128(S, q[0], q[1], q[2], q[3], desc_sw64(kb + 3 * 256));
  wgmma_qk64(F, q[0], q[1], q[2], q[3], desc_sw64(kb));
}
DEVI void fix_a(float (&S)[64], float (&F)[32], const Attn& at) {
  if (at.cmin > 0) { kill32<0>(F); if (at.cmin > 3) kill32<0>(S); }
  merge_fl(S, F, at.rowc);
}
DEVI void fix_b(float (&S)[64], const Attn& at) {
  if (at.cmin > 1) { kill32<0>(S); if (at.cmin > 2) kill32<32>(S); }
}
template <int W> DEVI void hook(float (&acc)[64], Ctx& c) {
  int npa, npb;
  gemm_wait(c);
  wgmma_fence();
  gemm_group<128>(acc, c, 0, npa, npb);
  if (W == 0) { c.pa = npa; c.pb = npb; } else { c.pa2 = npa; c.pb2 = npb; }
}
DEVI void release_all(Ctx& c) {
  release_prev(c);
  c.pa = c.pa2; c.pb = c.pb2;
  release_prev(c);
  c.pa = c.pb = c.pa2 = c.pb2 = -1;
}
template <int NH>
DEVI void exp_all(Ctx& c, const float (&S)[64], uint32_t (&P)[8][4], float n0, float n1, float (&l)[4]) {
  exp8<0>(S, P[0], n0, n1, l); exp8<1>(S, P[1], n0, n1, l); exp8<2>(S, P[2], n0, n1, l); exp8<3>(S, P[3], n0, n1, l);
  if (NH > 1) { exp8<4>(S, P[4], n0, n1, l); exp8<5>(S, P[5], n0, n1, l); }
  if (NH > 0) {
    ONCE { asm volatile("" : "+r"(P[NH > 1 ? 5 : 3][3])); }
    wgmma_wait<0>();
    release_all(c);
  }
  if (NH <= 1) { exp8<4>(S, P[4], n0, n1, l); exp8<5>(S, P[5], n0, n1, l); }
  exp8<6>(S, P[6], n0, n1, l); exp8<7>(S, P[7], n0, n1, l);
}
template <int NH> DEVI void hooks(float (&acc)[64], Ctx& c) {
  if (NH > 0) hook<0>(acc, c);
  if (NH > 1) hook<1>(acc, c);
}

template <int NH0, int NH1>
DEVI void head_pass(float (&acc)[64], Ctx& c, const Attn& at, uint32_t kb, float n0, float n1, float (&O)[8], float& l0, float& l1) {
  float S[64], l[4] = {0.f, 0.f, 0.f, 0.f};
  uint32_t P[8][4];
  {
    float F[32];
    qk_a(S, F, at.q[0], kb);
    wgmma_commit();
    wgmma_wait<0>();
    hooks<NH0>(acc, c);
    fix_a(S, F, at);
  }
  exp_all<NH0>(c, S, P, n0, n1, l);
  {
    uint32_t PF[4][4];
#pragma unroll
    for (int k = 0; k < 4; k++) {
#pragma unroll
      for (int i = 0; i < 4; i++) {
        const int col = k * 16 + (i >> 1) * 8, r = at.rowc + (i & 1) * 8;
        const uint32_t m = (col > r ? 0xFFFFu : 0u) | (col + 1 > r ? 0xFFFF0000u : 0u);
        PF[k][i] = P[4 + k][i] & m; P[4 + k][i] &= ~m;
      }
    }
    wgmma_fence();
    wgmma_pv0(O, P[0][0], P[0][1], P[0][2], P[0][3], desc_sw64(kb + 3 * 256 + 2));
#pragma unroll
    for (int k = 1; k < 8; k++) wgmma_pv(O, P[k][0], P[k][1], P[k][2], P[k][3], desc_sw64(kb + 3 * 256 + 2 + k * 64));
#pragma unroll
    for (int k = 0; k < 4; k++) wgmma_pv(O, PF[k][0], PF[k][1], PF[k][2], PF[k][3], desc_sw64(kb + 2 + k * 64));
    wgmma_qk128(S, at.q[0][0], at.q[0][1], at.q[0][2], at.q[0][3], desc_sw64(kb + 256));
    wgmma_commit();
    wgmma_wait<0>();
  }
  hooks<NH1>(acc, c);
  fix_b(S, at);
  exp_all<NH1>(c, S, P, n0, n1, l);
  wgmma_fence();
#pragma unroll
  for (int k = 0; k < 8; k++) wgmma_pv(O, P[k][0], P[k][1], P[k][2], P[k][3], desc_sw64(kb + 256 + 2 + k * 64));
  wgmma_commit();
  l0 = l[0] + l[1]; l1 = l[2] + l[3];
  l0 += __shfl_xor_sync(0xffffffffu, l0, 1); l1 += __shfl_xor_sync(0xffffffffu, l1, 1);
  l0 += __shfl_xor_sync(0xffffffffu, l0, 2); l1 += __shfl_xor_sync(0xffffffffu, l1, 2);
  wgmma_wait<0>();
}

DEVI void attention(float (&acc)[64], Ctx& c, Attn& at, int wi) {
  const uint32_t kvb = ((c.sbase & 0x3FFFF) + OFF_KV + c.wg * 4096) >> 4;
#pragma unroll 1
  for (int h = 0; h < 4; h++) {
    const uint32_t kb = kvb + (h & 1) * (KVBUF >> 4);
    float O[8], l0, l1;
    mbar_wait(c.bars + 8 * (BAR_KVFULL + (h & 1)), h >> 1, c.t0);
    head_pass<HK0, HK1>(acc, c, at, kb, __uint_as_float(at.nm[0] << 16), __uint_as_float(at.nm[0] & 0xffff0000u), O, l0, l1);
    const bool bad = !(l0 > 1e-6f && l0 < 1e18f && l1 > 1e-6f && l1 < 1e18f);
    float c0, c1;
    uint32_t o0, o1, o2, o3;
    if (wg_any(c.wg, bad)) {
      float x0 = __int_as_float(0xff800000), x1 = x0;
      {
        float T[64];
        wgmma_fence();
        wgmma_qk128(T, at.q[0][0], at.q[0][1], at.q[0][2], at.q[0][3], desc_sw64(kb + 256));
        wgmma_commit();
        wgmma_wait<0>();
        fix_b(T, at);
        row_max(T, x0, x1);
      }
      ONCE { asm volatile("" : "+f"(x0), "+f"(x1)); }
      {
        float T[64], G[32];
        qk_a(T, G, at.q[0], kb);
        wgmma_commit();
        wgmma_wait<0>();
        fix_a(T, G, at);
        row_max(T, x0, x1);
      }
      x0 = fmaxf(x0, __shfl_xor_sync(0xffffffffu, x0, 1)); x1 = fmaxf(x1, __shfl_xor_sync(0xffffffffu, x1, 1));
      x0 = fmaxf(x0, __shfl_xor_sync(0xffffffffu, x0, 2)); x1 = fmaxf(x1, __shfl_xor_sync(0xffffffffu, x1, 2));
      float O2[8];
      head_pass<0, 0>(acc, c, at, kb, -x0 * SC, -x1 * SC, O2, l0, l1);
      c0 = __fdividef(at.g0, l0); c1 = __fdividef(at.g1, l1);
      o0 = pack_bf16(O2[0] * c0, O2[1] * c0); o1 = pack_bf16(O2[2] * c1, O2[3] * c1);
      o2 = pack_bf16(O2[4] * c0, O2[5] * c0); o3 = pack_bf16(O2[6] * c1, O2[7] * c1);
    } else {
      c0 = __fdividef(at.g0, l0); c1 = __fdividef(at.g1, l1);
      o0 = pack_bf16(O[0] * c0, O[1] * c0); o1 = pack_bf16(O[2] * c1, O[3] * c1);
      o2 = pack_bf16(O[4] * c0, O[5] * c0); o3 = pack_bf16(O[6] * c1, O[7] * c1);
    }
    if (c.lane == 0) mbar_arrive(c.bars + 8 * (h == 3 ? BAR_ATTDONE : BAR_KVEMPTY + (h & 1)));
    const uint32_t ost = c.sbase + OFF_A + c.wg * 8192 + h * 2048;
    const int mi = c.lane >> 3;
    const int srow = wi * 16 + (c.lane & 7) + 8 * (mi & 1);
    stsm_x4(ost + srow * 32 + (mi >> 1) * 16, o0, o1, o2, o3);
    fence_async_smem();
    __syncwarp();
    if (c.lane == 0) mbar_arrive(c.bars + 8 * (BAR_STG + c.wg));
#pragma unroll
    for (int i = 0; i < 4; i++) { at.q[0][i] = at.q[1][i]; at.q[1][i] = at.q[2][i]; at.q[2][i] = at.q[3][i]; }
    at.nm[0] = at.nm[1]; at.nm[1] = at.nm[2]; at.nm[2] = at.nm[3];
  }
}

template <int CH, int NACC>
DEVI void store_h_chunk(const float (&acc)[NACC], uint32_t base  , int lane, float s0, float s1) {
  const int mi = lane >> 3;
#pragma unroll
  for (int tp = 0; tp < 4; tp++) {
    const int t = CH * 8 + tp * 2;
    const uint32_t r0 = pack_bf16(fmaxf(acc[4 * t + 0], 0.f) * s0, fmaxf(acc[4 * t + 1], 0.f) * s0);
    const uint32_t r1 = pack_bf16(fmaxf(acc[4 * t + 2], 0.f) * s1, fmaxf(acc[4 * t + 3], 0.f) * s1);
    const uint32_t r2 = pack_bf16(fmaxf(acc[4 * t + 4], 0.f) * s0, fmaxf(acc[4 * t + 5], 0.f) * s0);
    const uint32_t r3 = pack_bf16(fmaxf(acc[4 * t + 6], 0.f) * s1, fmaxf(acc[4 * t + 7], 0.f) * s1);
    stsm_x4(base + (((tp * 2 + (mi >> 1)) ^ (lane & 7)) << 4), r0, r1, r2, r3);
  }
}

DEVI void get_gate(Attn& at, const Ctx& c, int warp) {
  mbar_wait(c.bars + 8 * BAR_GIN, 0, c.t0);
  const uint32_t a = c.sbase + OFF_GIN + (warp * 16 + (c.lane >> 2)) * 4;
  asm volatile("ld.shared.f32 %0, [%1];" : "=f"(at.g0) : "r"(a) : "memory");
  asm volatile("ld.shared.f32 %0, [%1];" : "=f"(at.g1) : "r"(a + 32) : "memory");
}

template <int N>
DEVI void phase_q(Ctx& c, Attn& at, int warp) {
  float acc[N / 2];
#pragma unroll
  for (int i = 0; i < N / 2; i++) acc[i] = 0.f;
  bare_groups<N>(acc, c, 0, 16);
  drain(c);
  const int lane = c.lane, mi = lane >> 3;
  const int row = warp * 16 + (lane & 7) + 8 * (mi & 1);
  const int sw = (row >> 1) & 3;
#pragma unroll
  for (int hh = 0; hh < 4; hh++) {
    const uint32_t base = c.sbase + OFF_KV + hh * 8192 + row * 64;
#pragma unroll
    for (int kv = 0; kv < 2; kv++) {
      const int t = 8 + kv * 8 + 2 * hh;
      stsm_x4(base + (((kv * 2 + (mi >> 1)) ^ sw) << 4),
              pack_bf16(acc[4 * t + 0], acc[4 * t + 1]), pack_bf16(acc[4 * t + 2], acc[4 * t + 3]),
              pack_bf16(acc[4 * t + 4], acc[4 * t + 5]), pack_bf16(acc[4 * t + 6], acc[4 * t + 7]));
    }
  }
  fence_async_smem();
  __syncwarp();
  if (lane == 0) mbar_arrive(c.bars + 8 * (BAR_STG + c.wg));
  if constexpr (N == 256) {
    get_gate(at, c, warp);
    store_h_chunk<3>(acc, c.sbase + OFF_KV + 32768 + row * 128, lane, 1.f - at.g0, 1.f - at.g1);
    fence_async_smem();
    __syncwarp();
    if (lane == 0) mbar_arrive(c.bars + 8 * (BAR_STE + c.wg));
  }
#pragma unroll
  for (int hh = 0; hh < 4; hh++) {
#pragma unroll
    for (int i = 0; i < 4; i++) at.q[hh][i] = pack_bf16(acc[8 * hh + 2 * i], acc[8 * hh + 2 * i + 1]);
    const float* q = &acc[8 * hh];
    const float* k = &acc[32 + 8 * hh];
    float d0 = q[0] * k[0] + q[1] * k[1] + q[4] * k[4] + q[5] * k[5], d1 = q[2] * k[2] + q[3] * k[3] + q[6] * k[6] + q[7] * k[7];
    d0 += __shfl_xor_sync(0xffffffffu, d0, 1); d1 += __shfl_xor_sync(0xffffffffu, d1, 1);
    d0 += __shfl_xor_sync(0xffffffffu, d0, 2); d1 += __shfl_xor_sync(0xffffffffu, d1, 2);
    at.nm[hh] = pack_bf16(-d0 * SC, -d1 * SC);
  }
}

DEVI void first_loads(const Params& P, uint32_t sbase, int e, int j, int rb) {
  const uint32_t bars = sbase + OFF_BAR, fb = bars + 8 * (BAR_FULLB + e), fa = bars + 8 * (BAR_FULLA + e);
  mbar_expect_tx(fa, 16384);
  mbar_expect_tx(fb, (j & 1) ? 12288 : 16384);
  if (e == 0) tma_load_2d(sbase + OFF_A, &P.tmX, 0, rb * 128, fa);
#pragma unroll
  for (int r = 0; r < 2; r++) {
    tma_load_3d(sbase + OFF_B + e * SLOT + r * 8192, &P.tmWqkv, 64 * j, e * 32 + r * 16, 0, fb);
    if (!(j & 1)) tma_load_3d(sbase + OFF_B + e * SLOT + r * 8192 + 6144, &P.tmW1a, 0, e * 32 + r * 16, 24 + (j >> 1), fb);
  }
  if (e == 1) tma_load_2d(sbase + OFF_A + SLOT, &P.tmX, 64, rb * 128, fa);
}

__global__ void __cluster_dims__(2, 1, 1) __launch_bounds__(384, 1) fused_kernel(const __grid_constant__ Params P) {
  extern __shared__ uint8_t smem_raw[];
  const uint32_t sbase = (smem_u32(smem_raw) + 1023u) & ~1023u;
  const uint32_t bars = sbase + OFF_BAR;
  const int tid = threadIdx.x, warp = tid >> 5, lane = tid & 31;
  const uint32_t rank = blockIdx.x & 1, peer = rank ^ 1;
  const int j = (blockIdx.x >> 1) & 7, rb = ((blockIdx.x >> 4) << 1) | rank;
  const uint32_t t0 = clk32();

  const int typeB = j & 1;
  if (tid == 288) {
    for (int s = 0; s < NA2; s++) mbar_init(bars + 8 * (BAR_FULLA + s), 1);
    for (int s = 0; s < NB; s++) mbar_init(bars + 8 * (BAR_FULLB + s), 1);
    fence_async_smem();
  } else if (tid < 10) {
    asm volatile("prefetch.tensormap [%0];" ::"l"(&P.tmX + tid) : "memory");
  } else if (tid == 256) {
    for (int s = 0; s < NA2; s++) mbar_init(bars + 8 * (BAR_EMPTYA + s), 10);
    for (int s = 0; s < NB; s++) mbar_init(bars + 8 * (BAR_EMPTYB + s), 16);
  } else if (tid == 320) {
    for (int s = 0; s < 2; s++) { mbar_init(bars + 8 * (BAR_KVFULL + s), 1); mbar_init(bars + 8 * (BAR_KVEMPTY + s), 8); mbar_init(bars + 8 * (BAR_STG + s), 4); mbar_init(bars + 8 * (BAR_STE + s), 4); }
    mbar_init(bars + 8 * BAR_PIN, 1); mbar_init(bars + 8 * BAR_ATTDONE, 8); mbar_init(bars + 8 * BAR_GIN, 1); mbar_init(bars + 8 * BAR_GATE, 1); mbar_init(bars + 8 * (BAR_GATE + 1), 1);
  }
  if (tid >= 256 && lane == 0) asm volatile("fence.mbarrier_init.release.cluster;" ::: "memory");
  const unsigned ep1 = ld_relaxed(&g_epoch) + 1;
  __syncwarp();
  cluster_arrive();
  if (tid == 288) { first_loads(P, sbase, 0, j, rb); first_loads(P, sbase, 1, j, rb); }
  __syncwarp();

  const int on = 12 + 4 * typeB;

  if (warp < 8) {
    asm volatile("setmaxnreg.inc.sync.aligned.u32 232;");
    cluster_wait();
    const int wg = __shfl_sync(0xffffffffu, warp >> 2, 0), wi = warp & 3;
    Ctx c{sbase, bars, peer, t0, ((sbase & 0x3FFFF) + OFF_A + wg * 8192) >> 4, ((sbase & 0x3FFFF) + OFF_B) >> 4, wg, lane, 0, 0, 0u, 0u, 32 + on + 4 - NB, 0, -1, -1, -1, -1};
    Attn at;
    at.cmin = 4 - 2 * rb - wg;
    at.rowc = wi * 16 + (lane >> 2) - (lane & 3) * 2;
    if (tid == 0) TR(0);
    if (typeB) phase_q<192>(c, at, warp);
    else phase_q<256>(c, at, warp);
    if (tid == 0) TR(2);
    {
      float acc[96];
#pragma unroll
      for (int i = 0; i < 96; i++) acc[i] = 0.f;
      bare_groups<192>(acc, c, 0, 16);
      get_gate(at, c, warp);
      drain(c);
      if (tid == 0) TR(1);
      const uint32_t rowoff = (warp * 16 + (lane & 7) + 8 * ((lane >> 3) & 1)) * 128;
      const float s0 = 1.f - at.g0, s1 = 1.f - at.g1;
      constexpr int e0 = 16 % NA, e1 = 17 % NA, e2 = 18 % NA;
      mbar_wait(bars + 8 * (BAR_FULLA + e0), (16 / NA) & 1, t0);
      store_h_chunk<0>(acc, sbase + OFF_A + e0 * SLOT + rowoff, lane, s0, s1);
      mbar_wait(bars + 8 * (BAR_FULLA + e1), (17 / NA) & 1, t0);
      store_h_chunk<1>(acc, sbase + OFF_A + e1 * SLOT + rowoff, lane, s0, s1);
      mbar_wait(bars + 8 * (BAR_FULLA + e2), (18 / NA) & 1, t0);
      store_h_chunk<2>(acc, sbase + OFF_A + e2 * SLOT + rowoff, lane, s0, s1);
    }
    fence_async_smem();
    wg_bar(wg);
    if (lane == 0) mbar_arrive(bars + 8 * (BAR_STG + wg));
    if (tid == 0) TR(4);
    float own[32];
    {
      float acc[64];
#pragma unroll
      for (int i = 0; i < 64; i++) acc[i] = 0.f;
      attention(acc, c, at, wi);
      if (tid == 0) TR(3);
      bare_groups<128>(acc, c, 4 * (HK0 + HK1), on);
      drain(c);
      if (tid == 0) TR(5);
      named_bar<3>(256);
      const uint32_t pst = sbase + OFF_B + ((30 + on) % NB) * SLOT + wg * 8192 + (tid & 127) * 16;
#pragma unroll
      for (int i = 0; i < 4; i++) {
        uint32_t r[4];
#pragma unroll
        for (int k = 0; k < 4; k++) {
          const int idx = 8 * i + 2 * k;
          const float lo = typeB ? acc[idx] : acc[32 + idx], hi = typeB ? acc[idx + 1] : acc[32 + idx + 1];
          r[k] = pack_bf16(lo, hi);
        }
        sts128(pst + i * 2048, r[0], r[1], r[2], r[3]);
      }
#pragma unroll
      for (int i = 0; i < 32; i++) own[i] = typeB ? acc[32 + i] : acc[i];
      fence_async_smem();
      __syncwarp();
      if (lane == 0) mbar_arrive(bars + 8 * (BAR_STG + wg));
    }
    for (int g = 0; g < 8; g++) {
      const uint32_t a16 = c.a16 + c.ai * (SLOT >> 4);
      const uint32_t b16 = c.b16 + c.bi * (SLOT >> 4) + (g & 1) * 512;
      gemm_wait(c);
      wgmma_fence();
#pragma unroll
      for (int s = 0; s < 4; s++) wgmma_ss<64>(own, desc_sw128<16>(a16 + s * 2), desc_sw128<2048>(b16 + s * 128));
      wgmma_commit();
      c.ai = next_a_slot(c.ae, c.ai); c.ae++;
      if (g & 1) { if (++c.bi == NB) { c.bi = 0; c.bph ^= 1; } }
    }
    wgmma_wait<0>();
    if (tid == 0) TR(6);
    mbar_wait(bars + 8 * BAR_PIN, 0, t0);
    if (tid == 0) TR(7);
    {
      const uint32_t pin = sbase + OFF_B + ((31 + on) % NB) * SLOT + wg * 8192 + (tid & 127) * 16;
      wg_bar(wg);
      const uint32_t ob = sbase + OFF_A + wg * 8192;
      const uint32_t orow = ob + (wi * 16 + (lane & 7) + 8 * ((lane >> 3) & 1)) * 128;
#pragma unroll
      for (int i = 0; i < 4; i++) {
        const uint4 v = lds128(pin + i * 2048);
        const uint32_t r[4] = {v.x, v.y, v.z, v.w};
        uint32_t o[4];
#pragma unroll
        for (int k = 0; k < 4; k++) {
          const int idx = 8 * i + 2 * k;
          o[k] = pack_bf16(own[idx] + __uint_as_float(r[k] << 16), own[idx + 1] + __uint_as_float(r[k] & 0xffff0000u));
        }
        stsm_x4(orow + (((i * 2 + (lane >> 4)) ^ (lane & 7)) << 4), o[0], o[1], o[2], o[3]);
      }
      fence_async_smem();
      __syncwarp();
      if (lane == 0) {
        tma_store_2d(&P.tmOut, j * 64, rb * 128 + warp * 16, ob + wi * 2048);
        bulk_commit();
        asm volatile("cp.async.bulk.wait_group.read 0;" ::: "memory");
      }
    }
    if (tid == 0) TR(8);
  } else {
    asm volatile("setmaxnreg.dec.sync.aligned.u32 40;");
    if (warp == 8) {
      __syncwarp();
      cluster_wait();
      if (lane == 0) {
        int bi = 2; uint32_t bph = 1;
        const int nb = 32 + on + 4;
        for (int eb = 2; eb < nb; eb++) {
          if (eb == 4 || eb == 6) {
            for (int ea = eb - 2 - (eb == 6 ? 1 : 0); ea < (eb == 4 ? 3 : NA); ea++) {
              mbar_expect_tx(bars + 8 * (BAR_FULLA + ea), 16384);
              tma_load_2d(sbase + OFF_A + ea * SLOT, &P.tmX, ea * 64, rb * 128, bars + 8 * (BAR_FULLA + ea));
            }
          }
          const uint32_t fb = bars + 8 * (BAR_FULLB + bi), dst = sbase + OFF_B + bi * SLOT + rank * 8192;
          mbar_wait(bars + 8 * (BAR_EMPTYB + bi), bph, t0);
          if (eb < 16) {
            mbar_expect_tx(fb, typeB ? 12288 : 16384);
            tma_load_3d_mc(dst, &P.tmWqkv, 64 * j, eb * 32 + rank * 16, 0, fb);
            if (!typeB) tma_load_3d_mc(dst + 6144, &P.tmW1a, 0, eb * 32 + rank * 16, 24 + (j >> 1), fb);
          }
          else if (eb < 32) { mbar_expect_tx(fb, 12288); tma_load_3d_mc(dst, &P.tmW1b, 0, (eb - 16) * 32 + rank * 16, 3 * j, fb); }
          else if (eb < 32 + on) { int ow; const int ch = oh_chunk(j, eb - 32, ow); mbar_expect_tx(fb, 16384); tma_load_3d_mc(dst, &P.tmW2, 0, ch * 64 + rank * 32, (j >> 1) * 2, fb); }
          else { mbar_expect_tx(fb, 16384); tma_load_4d_mc(dst, &P.tmWo, 64 * j, 0, eb - 32 - on, rank * 4, fb); }
          if (++bi == NB) { bi = 0; bph ^= 1; }
          if (eb == PFAT) {
            const int b = blockIdx.x;
            l2_prefetch((const uint8_t*)P.w1 + b * 14336, 14336);
            l2_prefetch((const uint8_t*)P.w2 + b * 14336, 14336);
            l2_prefetch((const uint8_t*)P.wo + b * 4096, 4096);
          }
        }
      }
    } else if (warp == 9) {
      cluster_wait();
      if (lane == 0) {
        for (int ea = 0; ea < NA; ea++) mbar_arrive_n(bars + 8 * (BAR_EMPTYA + ea), 2);
        int ai = 0; uint32_t aph = 0xE0;
        const int na = 16 + on + 8;
        unsigned ready = 0;
        for (int ea = NA; ea < na; ea++) {
          const uint32_t fb = bars + 8 * (BAR_FULLA + ai), dst = sbase + OFF_A + ai * SLOT;
          int ch = ea & 7, need = -1;
          if (ea >= 16 + on) { need = 8 + ea - 16 - on; ch = 20 + need; }
          else if (ea >= 19) ch = oh_chunk(j, ea - 16, need);
          if (need >= 0 && !((ready >> need) & 1)) {
            const unsigned* fp = need < 8 ? &g_flag_h[rb * 8 * FS] : need < 16 ? &g_flag_o[rb * 8 * FS] : &g_flag_e[rb * 8 * FS];
            const unsigned tgt = (need & 8) ? ep1 * 8 : ep1 * 2;
            do {
              unsigned v[8];
#pragma unroll
              for (int i = 0; i < 8; i++) v[i] = ld_relaxed(fp + i * FS);
#pragma unroll
              for (int i = 0; i < 8; i++) if ((int)(v[i] - tgt) >= 0) ready |= 1u << (i + (need & 24));
            } while (!((ready >> need) & 1) && clk32() - t0 < TIMEOUT);
            fence_async_global();
          }
          if (ea == 32) mbar_wait(bars + 8 * BAR_ATTDONE, 0, t0);
          mbar_wait(bars + 8 * (BAR_EMPTYA + ai), (aph >> ai) & 1, t0);
          if (ea >= 16 && ea < 19) mbar_arrive(fb);
          else {
            if (ea != 15) mbar_arrive_n(bars + 8 * (BAR_EMPTYA + ai), 2);
            mbar_expect_tx(fb, 16384);
            tma_load_2d(dst, ea < 16 ? &P.tmX : &P.tmHO, ch * 64, rb * 128, fb);
          }
          TR(24 + ea);
          aph ^= 1u << ai;
          ai = next_a_slot(ea, ai);
        }
      }
    } else {
      const int wg = warp - 10;
      cluster_wait();
      {
        const int rowg = rb * 128 + j * 16 + wg * 8;
        const uint32_t xs = sbase + OFF_KV + 32768 + wg * 8192;
        if (lane == 0) {
          mbar_wait(bars + 8 * (BAR_FULLB + 1), 0, t0);
          mbar_expect_tx(bars + 8 * (BAR_GATE + wg), 8192);
          bulk_load(xs, P.x + (size_t)rowg * DM, 8192, bars + 8 * (BAR_GATE + wg));
        }
        const uint4* gw = (const uint4*)P.gate_w;
        const uint4 w0 = __ldg(gw + lane), w1 = __ldg(gw + 32 + lane);
        const uint32_t wa[8] = {w0.x, w0.y, w0.z, w0.w, w1.x, w1.y, w1.z, w1.w};
        mbar_wait(bars + 8 * (BAR_GATE + wg), 0, t0);
        float zz = 0.f;
#pragma unroll 1
        for (int i = 0; i < 8; i++) {
          const uint4 x0 = lds128(xs + i * 1024 + lane * 16), x1 = lds128(xs + i * 1024 + 512 + lane * 16);
          const uint32_t xa[8] = {x0.x, x0.y, x0.z, x0.w, x1.x, x1.y, x1.z, x1.w};
          float z = 0.f;
#pragma unroll
          for (int e = 0; e < 8; e++) {
            z = fmaf(__uint_as_float(xa[e] << 16), __uint_as_float(wa[e] << 16), z);
            z = fmaf(__uint_as_float(xa[e] & 0xffff0000u), __uint_as_float(wa[e] & 0xffff0000u), z);
          }
#pragma unroll
          for (int o = 16; o > 0; o >>= 1) z += __shfl_xor_sync(0xffffffffu, z, o);
          if (lane == i) zz = z;
        }
        if (lane < 8) asm volatile("st.shared.f32 [%0], %1;" ::"r"(sbase + OFF_GST + wg * 32 + lane * 4), "f"(1.f / (1.f + __expf(-zz))) : "memory");
        fence_async_smem();
        __syncwarp();
        if (lane == 0) {
          bulk_store(&g_gate[rowg], sbase + OFF_GST + wg * 32, 32);
          bulk_commit(); bulk_wait_all();
          flag_add(&g_flag_g[rb * FS]);
          if (wg == 1) {
            flag_wait(&g_flag_g[rb * FS], ep1 * 16, t0);
            fence_async_global();
            mbar_expect_tx(bars + 8 * BAR_GIN, 512);
            bulk_load(sbase + OFF_GIN, &g_gate[rb * 128], 512, bars + 8 * BAR_GIN);
          }
          if (wg == 0) TR(10);
        }
      }
      if (lane == 0) {
        const uint32_t stg = bars + 8 * (BAR_STG + wg);
        mbar_wait(stg, 0, t0);
        for (int hh = 0; hh < 4; hh++)
          bulk_store(g_kv + ((size_t)(4 * j + hh) * SEQ + rb * 128 + wg * 64) * 64, sbase + OFF_KV + hh * 8192 + wg * 4096, 4096);
        bulk_commit(); bulk_wait_all();
        flag_add(&g_flag_kv[(rb * 8 + j) * FS]);
        if (wg == 0) TR(21);
        if (!typeB) {
          mbar_wait(bars + 8 * (BAR_STE + wg), 0, t0);
          tma_store_2d(&P.tmHOs, (24 + (j >> 1)) * 64, rb * 128 + wg * 64, sbase + OFF_KV + 32768 + wg * 8192);
          bulk_commit(); bulk_wait_all();
          flag_add(&g_flag_e[(rb * 8 + j) * FS]);
          if (wg == 1) flag_wait(&g_flag_e[(rb * 8 + j) * FS], ep1 * 2, t0);
        }
        const int nblk = rb >= 2 ? 3 : rb + 1;
        const uint32_t kvbytes = nblk * 8192;
        const uint8_t* kvsrc = g_kv + ((size_t)(4 * j) * SEQ + (rb + 1 - nblk) * 128) * 64;
        const uint32_t kvdst = sbase + OFF_KV + wg * KVBUF + (3 - nblk) * 8192;
        {
          const unsigned* f0 = &g_flag_kv[(rb * 8 + j) * FS];
          const unsigned* f1 = rb >= 1 ? f0 - 8 * FS : f0;
          const unsigned* f2 = rb >= 2 ? f0 - 16 * FS : f0;
          unsigned v0, v1, v2;
          do { v0 = ld_relaxed(f0); v1 = ld_relaxed(f1); v2 = ld_relaxed(f2); }
          while (((int)(v0 - ep1 * 2) < 0 || (int)(v1 - ep1 * 2) < 0 || (int)(v2 - ep1 * 2) < 0) && clk32() - t0 < TIMEOUT);
        }
        if (wg == 0) TR(11);
        fence_async_global();
        mbar_expect_tx(bars + 8 * (BAR_KVFULL + wg), kvbytes);
        bulk_load(kvdst, kvsrc + (size_t)wg * SEQ * 64, kvbytes, bars + 8 * (BAR_KVFULL + wg));
        for (int ev = 1; ev < 7; ev++) {
          mbar_wait(stg, ev & 1, t0);
          if (ev == 1) {
            for (int i = 0; i < 3; i++)
              tma_store_2d(&P.tmHOs, (3 * j + i) * 64, rb * 128 + wg * 64, sbase + OFF_A + ((16 + i) % NA) * SLOT + wg * 8192);
            bulk_commit(); bulk_wait_all();
            flag_add(&g_flag_h[(rb * 8 + j) * FS]);
            for (int i = 0; i < 3; i++) mbar_arrive(bars + 8 * (BAR_EMPTYA + (16 + i) % NA));
            if (wg == 0) TR(22);
            if (wg == 0) {
              const unsigned old = atomicAdd(&g_done, 1u);
              if (old == gridDim.x - 1) { g_done = 0; *(volatile unsigned*)&g_epoch = ep1; }
            }
          } else if (ev == 6) {
            bulk_store(g_part + (size_t)(rb * 8 + (j ^ 1)) * 16384 + wg * 8192, sbase + OFF_B + ((30 + on) % NB) * SLOT + wg * 8192, 8192);
            bulk_commit(); bulk_wait_all();
            flag_add(&g_flag_p[(rb * 8 + (j ^ 1)) * FS]);
            if (wg == 0) TR(23);
            if (wg == 1) {
              flag_wait(&g_flag_p[(rb * 8 + j) * FS], ep1 * 2, t0);
              fence_async_global();
              mbar_expect_tx(bars + 8 * BAR_PIN, 16384);
              bulk_load(sbase + OFF_B + ((31 + on) % NB) * SLOT, g_part + (size_t)(rb * 8 + j) * 16384, 16384, bars + 8 * BAR_PIN);
            }
          } else {
            const int hh = ev - 2;
            tma_store_2d(&P.tmOs, DFF + hh * 128 + j * 16, rb * 128 + wg * 64, sbase + OFF_A + (15 % NA) * SLOT + wg * 8192 + hh * 2048);
            bulk_commit();
            if (hh == wg) {
              mbar_wait(bars + 8 * (BAR_KVEMPTY + wg), 0, t0);
              mbar_expect_tx(bars + 8 * (BAR_KVFULL + wg), kvbytes);
              bulk_load(kvdst, kvsrc + (size_t)(wg + 2) * SEQ * 64, kvbytes, bars + 8 * (BAR_KVFULL + wg));
            }
            bulk_wait_all();
            flag_add(&g_flag_o[(rb * 8 + hh * 2 + (j >> 2)) * FS]);
            if (hh == 3) mbar_arrive(bars + 8 * (BAR_EMPTYA + 15 % NA));
            if (wg == 0) TR(12 + hh);
          }
        }
      }
    }
  }
}

typedef CUresult (*EncodeFn)(CUtensorMap*, CUtensorMapDataType, cuuint32_t, void*, const cuuint64_t*, const cuuint64_t*, const cuuint32_t*,
                             const cuuint32_t*, CUtensorMapInterleave, CUtensorMapSwizzle, CUtensorMapL2promotion, CUtensorMapFloatOOBfill);

void make_map(EncodeFn enc, CUtensorMap* m, const void* ptr, int rank, const cuuint64_t* dims, const cuuint64_t* strides, const cuuint32_t* box,
              CUtensorMapSwizzle sw = CU_TENSOR_MAP_SWIZZLE_128B) {
  cuuint32_t es[4] = {1, 1, 1, 1};
  enc(m, CU_TENSOR_MAP_DATA_TYPE_BFLOAT16, rank, const_cast<void*>(ptr), dims, strides, box, es, CU_TENSOR_MAP_INTERLEAVE_NONE, sw,
      CU_TENSOR_MAP_L2_PROMOTION_L2_256B, CU_TENSOR_MAP_FLOAT_OOB_FILL_NONE);
}

}

extern "C" void kernel_launch(void* const* d_in, const int* in_sizes, int n_in, void* d_out, int out_size) {
  (void)in_sizes; (void)n_in; (void)out_size;
  static EncodeFn enc = nullptr;
  static void* ho_ptr = nullptr;
  if (!enc) {
    void* fn = nullptr; cudaDriverEntryPointQueryResult st;
    cudaGetDriverEntryPoint("cuTensorMapEncodeTiled", &fn, cudaEnableDefault, &st);
    enc = (EncodeFn)fn;
    cudaGetSymbolAddress(&ho_ptr, g_ho);
    cudaFuncSetAttribute(fused_kernel, cudaFuncAttributeMaxDynamicSharedMemorySize, SMEM_BYTES);
  }
  const __nv_bfloat16* x = (const __nv_bfloat16*)d_in[0];
  const __nv_bfloat16* wqkv = (const __nv_bfloat16*)d_in[1];
  const __nv_bfloat16* wo = (const __nv_bfloat16*)d_in[2];
  const __nv_bfloat16* w1 = (const __nv_bfloat16*)d_in[4];
  const __nv_bfloat16* w2 = (const __nv_bfloat16*)d_in[5];
  const __nv_bfloat16* gate_w = (const __nv_bfloat16*)d_in[6];
  Params P;
  { cuuint64_t d[2] = {DM, SEQ}, s[1] = {DM * 2}; cuuint32_t b[2] = {64, 128}; make_map(enc, &P.tmX, x, 2, d, s, b); }
  { cuuint64_t d[3] = {512, 512, 3}, s[2] = {1536 * 2, 512 * 2}; cuuint32_t b[3] = {64, 16, 3}; make_map(enc, &P.tmWqkv, wqkv, 3, d, s, b); }
  { cuuint64_t d[3] = {64, 512, 28}, s[2] = {DFF * 2, 128}; cuuint32_t b[3] = {64, 16, 1}; make_map(enc, &P.tmW1a, w1, 3, d, s, b);
    b[2] = 3; make_map(enc, &P.tmW1b, w1, 3, d, s, b); }
  { cuuint64_t d[3] = {64, DFF, 8}, s[2] = {DM * 2, 128}; cuuint32_t b[3] = {64, 32, 2}; make_map(enc, &P.tmW2, w2, 3, d, s, b); }
  { cuuint64_t d[4] = {DM, 16, 4, 8}, s[3] = {DM * 2, 16 * DM * 2, 64 * DM * 2}; cuuint32_t b[4] = {64, 16, 1, 4}; make_map(enc, &P.tmWo, wo, 4, d, s, b); }
  { cuuint64_t d[2] = {KHO, SEQ}, s[1] = {KHO * 2}; cuuint32_t b[2] = {64, 128}; make_map(enc, &P.tmHO, ho_ptr, 2, d, s, b);
    b[1] = 64; make_map(enc, &P.tmHOs, ho_ptr, 2, d, s, b);
    b[0] = 16; make_map(enc, &P.tmOs, ho_ptr, 2, d, s, b, CU_TENSOR_MAP_SWIZZLE_NONE); }
  { cuuint64_t d[2] = {DM, SEQ}, s[1] = {DM * 2}; cuuint32_t b[2] = {64, 16}; make_map(enc, &P.tmOut, d_out, 2, d, s, b); }
  P.x = x; P.gate_w = gate_w; P.w1 = w1; P.w2 = w2; P.wo = wo; P.out = (__nv_bfloat16*)d_out;
  fused_kernel<<<128, 384, SMEM_BYTES>>>(P);
}
```

```cpp
#include <cuda_runtime.h>
#include <cuda_bf16.h>
#include <cuda.h>
#include <stdint.h>

#define DEVI __device__ __forceinline__

namespace {

constexpr int SEQ = 2048, DM = 512, DFF = 1792, KHO = 2304;
constexpr int NA = 5, NB = 6, SLOT = 16384, KVBUF = 24576;
constexpr int NA2 = 8;
constexpr int OFF_B = 0, OFF_A = NB * SLOT, OFF_KV = OFF_A + NA * SLOT, OFF_BAR = OFF_KV + 2 * KVBUF;
constexpr int OFF_GST = OFF_BAR + 512;
constexpr int OFF_GIN = OFF_BAR + 1024;
constexpr int SMEM_BYTES = OFF_BAR + 1536 + 1024;
constexpr uint32_t TIMEOUT = 1u << 28;
#define WAIT_HINT_NS 20000u
#define PFAT 8
#define HK0 2
#define HK1 1
constexpr int FS = 8;

constexpr int BAR_FULLA = 0, BAR_EMPTYA = BAR_FULLA + NA2, BAR_FULLB = BAR_EMPTYA + NA2, BAR_EMPTYB = BAR_FULLB + NB,
              BAR_KVFULL = BAR_EMPTYB + NB, BAR_KVEMPTY = BAR_KVFULL + 2, BAR_STG = BAR_KVEMPTY + 2, BAR_PIN = BAR_STG + 2, BAR_GATE = BAR_PIN + 1, BAR_STE = BAR_GATE + 2, BAR_ATTDONE = BAR_STE + 2, BAR_GIN = BAR_ATTDONE + 1;

__device__ __align__(1024) uint8_t g_kv[32 * SEQ * 64];
__device__ __align__(1024) __nv_bfloat16 g_ho[SEQ * KHO];
__device__ __align__(1024) uint8_t g_part[128 * 16384];
__device__ __align__(128) float g_gate[SEQ];
__device__ unsigned g_flag_kv[128 * FS], g_flag_h[128 * FS], g_flag_o[128 * FS], g_flag_g[16 * FS], g_flag_p[128 * FS], g_flag_e[128 * FS];
__device__ unsigned g_epoch, g_done;
#define TR(i) do {} while (0)

struct Params {
  CUtensorMap tmX, tmWqkv, tmW1a, tmW1b, tmW2, tmWo, tmHO, tmHOs, tmOs, tmOut;
  const __nv_bfloat16* x;
  const __nv_bfloat16* gate_w;
  const __nv_bfloat16* w1;
  const __nv_bfloat16* w2;
  const __nv_bfloat16* wo;
  __nv_bfloat16* out;
};

DEVI uint32_t smem_u32(const void* p) { return (uint32_t)__cvta_generic_to_shared(p); }
DEVI uint32_t clk32() { uint32_t c; asm volatile("mov.u32 %0, %%clock;" : "=r"(c)); return c; }
DEVI void mbar_init(uint32_t bar, uint32_t cnt) { asm volatile("mbarrier.init.shared::cta.b64 [%0], %1;" ::"r"(bar), "r"(cnt)); }
DEVI void mbar_expect_tx(uint32_t bar, uint32_t bytes) { asm volatile("mbarrier.arrive.expect_tx.shared::cta.b64 _, [%0], %1;" ::"r"(bar), "r"(bytes) : "memory"); }
DEVI void mbar_arrive(uint32_t bar) { asm volatile("mbarrier.arrive.shared::cta.b64 _, [%0];" ::"r"(bar) : "memory"); }
DEVI void mbar_arrive_n(uint32_t bar, uint32_t n) { asm volatile("mbarrier.arrive.shared::cta.b64 _, [%0], %1;" ::"r"(bar), "r"(n) : "memory"); }
DEVI void mbar_arrive_cluster(uint32_t bar, uint32_t cta) {
  asm volatile("{ .reg .b32 ra; mapa.shared::cluster.u32 ra, %0, %1; mbarrier.arrive.shared::cluster.b64 _, [ra]; }" ::"r"(bar), "r"(cta) : "memory");
}
DEVI void mbar_wait(uint32_t bar, uint32_t parity, uint32_t t0) {
  asm volatile("{ .reg .pred p; .reg .u32 c;\n"
               "mbarrier.try_wait.parity.shared::cta.b64 p, [%0], %1;\n"
               "@p bra DONE_%=;\n"
               "WAIT_%=:\n"
               "mbarrier.try_wait.parity.shared::cta.b64 p, [%0], %1, %4;\n"
               "@p bra DONE_%=;\n"
               "mov.u32 c, %%clock; sub.u32 c, c, %2; setp.lt.u32 p, c, %3;\n"
               "@p bra WAIT_%=;\n"
               "DONE_%=: }" ::"r"(bar), "r"(parity), "r"(t0), "n"(TIMEOUT), "r"(WAIT_HINT_NS) : "memory");
}
DEVI unsigned ld_relaxed(const unsigned* p) { unsigned v; asm volatile("ld.relaxed.gpu.global.u32 %0, [%1];" : "=r"(v) : "l"(p) : "memory"); return v; }
DEVI void flag_wait(const unsigned* p, unsigned target, uint32_t t0) {
  while ((int)(ld_relaxed(p) - target) < 0) { if (clk32() - t0 > TIMEOUT) break; }
}
DEVI void flag_add(unsigned* p) { asm volatile("red.relaxed.gpu.global.add.u32 [%0], 1;" ::"l"(p) : "memory"); }
DEVI void fence_async_smem() { asm volatile("fence.proxy.async.shared::cta;" ::: "memory"); }
DEVI void fence_async_global() { asm volatile("fence.proxy.async.global;" ::: "memory"); }
DEVI void tma_load_2d(uint32_t dst, const CUtensorMap* m, int c0, int c1, uint32_t bar) {
  asm volatile("cp.async.bulk.tensor.2d.shared::cluster.global.mbarrier::complete_tx::bytes [%0], [%1, {%3, %4}], [%2];" ::"r"(dst), "l"(m), "r"(bar), "r"(c0), "r"(c1) : "memory");
}
DEVI void tma_load_3d(uint32_t dst, const CUtensorMap* m, int c0, int c1, int c2, uint32_t bar) {
  asm volatile("cp.async.bulk.tensor.3d.shared::cluster.global.mbarrier::complete_tx::bytes [%0], [%1, {%3, %4, %5}], [%2];"
               ::"r"(dst), "l"(m), "r"(bar), "r"(c0), "r"(c1), "r"(c2) : "memory");
}
DEVI void tma_load_3d_mc(uint32_t dst, const CUtensorMap* m, int c0, int c1, int c2, uint32_t bar) {
  asm volatile("cp.async.bulk.tensor.3d.shared::cluster.global.mbarrier::complete_tx::bytes.multicast::cluster [%0], [%1, {%3, %4, %5}], [%2], %6;"
               ::"r"(dst), "l"(m), "r"(bar), "r"(c0), "r"(c1), "r"(c2), "h"((uint16_t)3) : "memory");
}
DEVI void tma_load_4d_mc(uint32_t dst, const CUtensorMap* m, int c0, int c1, int c2, int c3, uint32_t bar) {
  asm volatile("cp.async.bulk.tensor.4d.shared::cluster.global.mbarrier::complete_tx::bytes.multicast::cluster [%0], [%1, {%3, %4, %5, %6}], [%2], %7;"
               ::"r"(dst), "l"(m), "r"(bar), "r"(c0), "r"(c1), "r"(c2), "r"(c3), "h"((uint16_t)3) : "memory");
}
DEVI void tma_store_2d(const CUtensorMap* m, int c0, int c1, uint32_t src) {
  asm volatile("cp.async.bulk.tensor.2d.global.shared::cta.bulk_group [%0, {%1, %2}], [%3];" ::"l"(m), "r"(c0), "r"(c1), "r"(src) : "memory");
}
DEVI void bulk_store(void* dst, uint32_t src, uint32_t bytes) {
  asm volatile("cp.async.bulk.global.shared::cta.bulk_group [%0], [%1], %2;" ::"l"(dst), "r"(src), "r"(bytes) : "memory");
}
DEVI void bulk_load(uint32_t dst, const void* src, uint32_t bytes, uint32_t bar) {
  asm volatile("cp.async.bulk.shared::cluster.global.mbarrier::complete_tx::bytes [%0], [%1], %2, [%3];" ::"r"(dst), "l"(src), "r"(bytes), "r"(bar) : "memory");
}
DEVI void bulk_commit() { asm volatile("cp.async.bulk.commit_group;" ::: "memory"); }
DEVI void bulk_wait_all() { asm volatile("cp.async.bulk.wait_group 0;" ::: "memory"); }
DEVI void l2_prefetch(const void* p, uint32_t bytes) { asm volatile("cp.async.bulk.prefetch.L2.global [%0], %1;" ::"l"(p), "r"(bytes) : "memory"); }
DEVI void cluster_arrive() { asm volatile("barrier.cluster.arrive.relaxed.aligned;" ::: "memory"); }
DEVI void cluster_wait() { asm volatile("barrier.cluster.wait.aligned;" ::: "memory"); }
template <int ID> DEVI void named_bar(int n) { asm volatile("bar.sync %0, %1;" ::"n"(ID), "r"(n) : "memory"); }
DEVI void wg_bar(int wg) { if (wg == 0) named_bar<1>(128); else named_bar<2>(128); }
DEVI void wgmma_fence() { asm volatile("wgmma.fence.sync.aligned;" ::: "memory"); }
DEVI void wgmma_commit() { asm volatile("wgmma.commit_group.sync.aligned;" ::: "memory"); }
template <int N> DEVI void wgmma_wait() { asm volatile("wgmma.wait_group.sync.aligned %0;" ::"n"(N) : "memory"); }
template <uint32_t LBO> DEVI uint64_t desc_sw128(uint32_t a16) {
  return ((uint64_t)(0x40000000u | (1024 >> 4)) << 32) | (a16 + ((LBO >> 4) << 16));
}
DEVI uint64_t desc_sw64(uint32_t a16) {
  return ((uint64_t)(0x80000000u | (512 >> 4)) << 32) | (a16 + ((512 >> 4) << 16));
}
DEVI uint32_t pack_bf16(float lo, float hi) { uint32_t r; asm("cvt.rn.bf16x2.f32 %0, %1, %2;" : "=r"(r) : "f"(hi), "f"(lo)); return r; }
DEVI void stsm_x4(uint32_t addr, uint32_t r0, uint32_t r1, uint32_t r2, uint32_t r3) {
  asm volatile("stmatrix.sync.aligned.m8n8.x4.shared.b16 [%0], {%1, %2, %3, %4};" ::"r"(addr), "r"(r0), "r"(r1), "r"(r2), "r"(r3) : "memory");
}
DEVI void sts128(uint32_t addr, uint32_t r0, uint32_t r1, uint32_t r2, uint32_t r3) {
  asm volatile("st.shared.v4.b32 [%0], {%1, %2, %3, %4};" ::"r"(addr), "r"(r0), "r"(r1), "r"(r2), "r"(r3) : "memory");
}
DEVI uint4 lds128(uint32_t addr) {
  uint4 v; asm volatile("ld.shared.v4.b32 {%0, %1, %2, %3}, [%4];" : "=r"(v.x), "=r"(v.y), "=r"(v.z), "=r"(v.w) : "r"(addr) : "memory"); return v;
}
DEVI float ex2(float x) { float y; asm("ex2.approx.ftz.f32 %0, %1;" : "=f"(y) : "f"(x)); return y; }

DEVI void wgmma_ss_n64(float (&d)[32], uint64_t da, uint64_t db) {
  asm volatile("wgmma.mma_async.sync.aligned.m64n64k16.f32.bf16.bf16 {%0, %1, %2, %3, %4, %5, %6, %7, %8, %9, %10, %11, %12, %13, %14, %15, %16, %17, %18, %19, %20, %21, %22, %23, %24, %25, %26, %27, %28, %29, %30, %31}, %32, %33, 1, 1, 1, 0, 1;"
    : "+f"(d[0]), "+f"(d[1]), "+f"(d[2]), "+f"(d[3]), "+f"(d[4]), "+f"(d[5]), "+f"(d[6]), "+f"(d[7]), "+f"(d[8]), "+f"(d[9]), "+f"(d[10]), "+f"(d[11]), "+f"(d[12]), "+f"(d[13]), "+f"(d[14]), "+f"(d[15]), "+f"(d[16]), "+f"(d[17]), "+f"(d[18]), "+f"(d[19]), "+f"(d[20]), "+f"(d[21]), "+f"(d[22]), "+f"(d[23]), "+f"(d[24]), "+f"(d[25]), "+f"(d[26]), "+f"(d[27]), "+f"(d[28]), "+f"(d[29]), "+f"(d[30]), "+f"(d[31])
    : "l"(da), "l"(db));
}
DEVI void wgmma_ss_n128(float (&d)[64], uint64_t da, uint64_t db) {
  asm volatile("wgmma.mma_async.sync.aligned.m64n128k16.f32.bf16.bf16 {%0, %1, %2, %3, %4, %5, %6, %7, %8, %9, %10, %11, %12, %13, %14, %15, %16, %17, %18, %19, %20, %21, %22, %23, %24, %25, %26, %27, %28, %29, %30, %31, %32, %33, %34, %35, %36, %37, %38, %39, %40, %41, %42, %43, %44, %45, %46, %47, %48, %49, %50, %51, %52, %53, %54, %55, %56, %57, %58, %59, %60, %61, %62, %63}, %64, %65, 1, 1, 1, 0, 1;"
    : "+f"(d[0]), "+f"(d[1]), "+f"(d[2]), "+f"(d[3]), "+f"(d[4]), "+f"(d[5]), "+f"(d[6]), "+f"(d[7]), "+f"(d[8]), "+f"(d[9]), "+f"(d[10]), "+f"(d[11]), "+f"(d[12]), "+f"(d[13]), "+f"(d[14]), "+f"(d[15]), "+f"(d[16]), "+f"(d[17]), "+f"(d[18]), "+f"(d[19]), "+f"(d[20]), "+f"(d[21]), "+f"(d[22]), "+f"(d[23]), "+f"(d[24]), "+f"(d[25]), "+f"(d[26]), "+f"(d[27]), "+f"(d[28]), "+f"(d[29]), "+f"(d[30]), "+f"(d[31]), "+f"(d[32]), "+f"(d[33]), "+f"(d[34]), "+f"(d[35]), "+f"(d[36]), "+f"(d[37]), "+f"(d[38]), "+f"(d[39]), "+f"(d[40]), "+f"(d[41]), "+f"(d[42]), "+f"(d[43]), "+f"(d[44]), "+f"(d[45]), "+f"(d[46]), "+f"(d[47]), "+f"(d[48]), "+f"(d[49]), "+f"(d[50]), "+f"(d[51]), "+f"(d[52]), "+f"(d[53]), "+f"(d[54]), "+f"(d[55]), "+f"(d[56]), "+f"(d[57]), "+f"(d[58]), "+f"(d[59]), "+f"(d[60]), "+f"(d[61]), "+f"(d[62]), "+f"(d[63])
    : "l"(da), "l"(db));
}
DEVI void wgmma_ss_n192(float (&d)[96], uint64_t da, uint64_t db) {
  asm volatile("wgmma.mma_async.sync.aligned.m64n192k16.f32.bf16.bf16 {%0, %1, %2, %3, %4, %5, %6, %7, %8, %9, %10, %11, %12, %13, %14, %15, %16, %17, %18, %19, %20, %21, %22, %23, %24, %25, %26, %27, %28, %29, %30, %31, %32, %33, %34, %35, %36, %37, %38, %39, %40, %41, %42, %43, %44, %45, %46, %47, %48, %49, %50, %51, %52, %53, %54, %55, %56, %57, %58, %59, %60, %61, %62, %63, %64, %65, %66, %67, %68, %69, %70, %71, %72, %73, %74, %75, %76, %77, %78, %79, %80, %81, %82, %83, %84, %85, %86, %87, %88, %89, %90, %91, %92, %93, %94, %95}, %96, %97, 1, 1, 1, 0, 1;"
    : "+f"(d[0]), "+f"(d[1]), "+f"(d[2]), "+f"(d[3]), "+f"(d[4]), "+f"(d[5]), "+f"(d[6]), "+f"(d[7]), "+f"(d[8]), "+f"(d[9]), "+f"(d[10]), "+f"(d[11]), "+f"(d[12]), "+f"(d[13]), "+f"(d[14]), "+f"(d[15]), "+f"(d[16]), "+f"(d[17]), "+f"(d[18]), "+f"(d[19]), "+f"(d[20]), "+f"(d[21]), "+f"(d[22]), "+f"(d[23]), "+f"(d[24]), "+f"(d[25]), "+f"(d[26]), "+f"(d[27]), "+f"(d[28]), "+f"(d[29]), "+f"(d[30]), "+f"(d[31]), "+f"(d[32]), "+f"(d[33]), "+f"(d[34]), "+f"(d[35]), "+f"(d[36]), "+f"(d[37]), "+f"(d[38]), "+f"(d[39]), "+f"(d[40]), "+f"(d[41]), "+f"(d[42]), "+f"(d[43]), "+f"(d[44]), "+f"(d[45]), "+f"(d[46]), "+f"(d[47]), "+f"(d[48]), "+f"(d[49]), "+f"(d[50]), "+f"(d[51]), "+f"(d[52]), "+f"(d[53]), "+f"(d[54]), "+f"(d[55]), "+f"(d[56]), "+f"(d[57]), "+f"(d[58]), "+f"(d[59]), "+f"(d[60]), "+f"(d[61]), "+f"(d[62]), "+f"(d[63]), "+f"(d[64]), "+f"(d[65]), "+f"(d[66]), "+f"(d[67]), "+f"(d[68]), "+f"(d[69]), "+f"(d[70]), "+f"(d[71]), "+f"(d[72]), "+f"(d[73]), "+f"(d[74]), "+f"(d[75]), "+f"(d[76]), "+f"(d[77]), "+f"(d[78]), "+f"(d[79]), "+f"(d[80]), "+f"(d[81]), "+f"(d[82]), "+f"(d[83]), "+f"(d[84]), "+f"(d[85]), "+f"(d[86]), "+f"(d[87]), "+f"(d[88]), "+f"(d[89]), "+f"(d[90]), "+f"(d[91]), "+f"(d[92]), "+f"(d[93]), "+f"(d[94]), "+f"(d[95])
    : "l"(da), "l"(db));
}
DEVI void wgmma_ss_n256(float (&d)[128], uint64_t da, uint64_t db) {
  asm volatile("wgmma.mma_async.sync.aligned.m64n256k16.f32.bf16.bf16 {%0, %1, %2, %3, %4, %5, %6, %7, %8, %9, %10, %11, %12, %13, %14, %15, %16, %17, %18, %19, %20, %21, %22, %23, %24, %25, %26, %27, %28, %29, %30, %31, %32, %33, %34, %35, %36, %37, %38, %39, %40, %41, %42, %43, %44, %45, %46, %47, %48, %49, %50, %51, %52, %53, %54, %55, %56, %57, %58, %59, %60, %61, %62, %63, %64, %65, %66, %67, %68, %69, %70, %71, %72, %73, %74, %75, %76, %77, %78, %79, %80, %81, %82, %83, %84, %85, %86, %87, %88, %89, %90, %91, %92, %93, %94, %95, %96, %97, %98, %99, %100, %101, %102, %103, %104, %105, %106, %107, %108, %109, %110, %111, %112, %113, %114, %115, %116, %117, %118, %119, %120, %121, %122, %123, %124, %125, %126, %127}, %128, %129, 1, 1, 1, 0, 1;"
    : "+f"(d[0]), "+f"(d[1]), "+f"(d[2]), "+f"(d[3]), "+f"(d[4]), "+f"(d[5]), "+f"(d[6]), "+f"(d[7]), "+f"(d[8]), "+f"(d[9]), "+f"(d[10]), "+f"(d[11]), "+f"(d[12]), "+f"(d[13]), "+f"(d[14]), "+f"(d[15]), "+f"(d[16]), "+f"(d[17]), "+f"(d[18]), "+f"(d[19]), "+f"(d[20]), "+f"(d[21]), "+f"(d[22]), "+f"(d[23]), "+f"(d[24]), "+f"(d[25]), "+f"(d[26]), "+f"(d[27]), "+f"(d[28]), "+f"(d[29]), "+f"(d[30]), "+f"(d[31]), "+f"(d[32]), "+f"(d[33]), "+f"(d[34]), "+f"(d[35]), "+f"(d[36]), "+f"(d[37]), "+f"(d[38]), "+f"(d[39]), "+f"(d[40]), "+f"(d[41]), "+f"(d[42]), "+f"(d[43]), "+f"(d[44]), "+f"(d[45]), "+f"(d[46]), "+f"(d[47]), "+f"(d[48]), "+f"(d[49]), "+f"(d[50]), "+f"(d[51]), "+f"(d[52]), "+f"(d[53]), "+f"(d[54]), "+f"(d[55]), "+f"(d[56]), "+f"(d[57]), "+f"(d[58]), "+f"(d[59]), "+f"(d[60]), "+f"(d[61]), "+f"(d[62]), "+f"(d[63]), "+f"(d[64]), "+f"(d[65]), "+f"(d[66]), "+f"(d[67]), "+f"(d[68]), "+f"(d[69]), "+f"(d[70]), "+f"(d[71]), "+f"(d[72]), "+f"(d[73]), "+f"(d[74]), "+f"(d[75]), "+f"(d[76]), "+f"(d[77]), "+f"(d[78]), "+f"(d[79]), "+f"(d[80]), "+f"(d[81]), "+f"(d[82]), "+f"(d[83]), "+f"(d[84]), "+f"(d[85]), "+f"(d[86]), "+f"(d[87]), "+f"(d[88]), "+f"(d[89]), "+f"(d[90]), "+f"(d[91]), "+f"(d[92]), "+f"(d[93]), "+f"(d[94]), "+f"(d[95]), "+f"(d[96]), "+f"(d[97]), "+f"(d[98]), "+f"(d[99]), "+f"(d[100]), "+f"(d[101]), "+f"(d[102]), "+f"(d[103]), "+f"(d[104]), "+f"(d[105]), "+f"(d[106]), "+f"(d[107]), "+f"(d[108]), "+f"(d[109]), "+f"(d[110]), "+f"(d[111]), "+f"(d[112]), "+f"(d[113]), "+f"(d[114]), "+f"(d[115]), "+f"(d[116]), "+f"(d[117]), "+f"(d[118]), "+f"(d[119]), "+f"(d[120]), "+f"(d[121]), "+f"(d[122]), "+f"(d[123]), "+f"(d[124]), "+f"(d[125]), "+f"(d[126]), "+f"(d[127])
    : "l"(da), "l"(db));
}
DEVI void wgmma_qk64(float (&d)[32], uint32_t a0, uint32_t a1, uint32_t a2, uint32_t a3, uint64_t db) {
  asm volatile("wgmma.mma_async.sync.aligned.m64n64k16.f32.bf16.bf16 {%0, %1, %2, %3, %4, %5, %6, %7, %8, %9, %10, %11, %12, %13, %14, %15, %16, %17, %18, %19, %20, %21, %22, %23, %24, %25, %26, %27, %28, %29, %30, %31}, {%32, %33, %34, %35}, %36, 0, 1, 1, 0;"
    : "=f"(d[0]), "=f"(d[1]), "=f"(d[2]), "=f"(d[3]), "=f"(d[4]), "=f"(d[5]), "=f"(d[6]), "=f"(d[7]), "=f"(d[8]), "=f"(d[9]), "=f"(d[10]), "=f"(d[11]), "=f"(d[12]), "=f"(d[13]), "=f"(d[14]), "=f"(d[15]), "=f"(d[16]), "=f"(d[17]), "=f"(d[18]), "=f"(d[19]), "=f"(d[20]), "=f"(d[21]), "=f"(d[22]), "=f"(d[23]), "=f"(d[24]), "=f"(d[25]), "=f"(d[26]), "=f"(d[27]), "=f"(d[28]), "=f"(d[29]), "=f"(d[30]), "=f"(d[31])
    : "r"(a0), "r"(a1), "r"(a2), "r"(a3), "l"(db));
}
DEVI void wgmma_qk128(float (&d)[64], uint32_t a0, uint32_t a1, uint32_t a2, uint32_t a3, uint64_t db) {
  asm volatile("wgmma.mma_async.sync.aligned.m64n128k16.f32.bf16.bf16 {%0, %1, %2, %3, %4, %5, %6, %7, %8, %9, %10, %11, %12, %13, %14, %15, %16, %17, %18, %19, %20, %21, %22, %23, %24, %25, %26, %27, %28, %29, %30, %31, %32, %33, %34, %35, %36, %37, %38, %39, %40, %41, %42, %43, %44, %45, %46, %47, %48, %49, %50, %51, %52, %53, %54, %55, %56, %57, %58, %59, %60, %61, %62, %63}, {%64, %65, %66, %67}, %68, 0, 1, 1, 0;"
    : "=f"(d[0]), "=f"(d[1]), "=f"(d[2]), "=f"(d[3]), "=f"(d[4]), "=f"(d[5]), "=f"(d[6]), "=f"(d[7]), "=f"(d[8]), "=f"(d[9]), "=f"(d[10]), "=f"(d[11]), "=f"(d[12]), "=f"(d[13]), "=f"(d[14]), "=f"(d[15]), "=f"(d[16]), "=f"(d[17]), "=f"(d[18]), "=f"(d[19]), "=f"(d[20]), "=f"(d[21]), "=f"(d[22]), "=f"(d[23]), "=f"(d[24]), "=f"(d[25]), "=f"(d[26]), "=f"(d[27]), "=f"(d[28]), "=f"(d[29]), "=f"(d[30]), "=f"(d[31]), "=f"(d[32]), "=f"(d[33]), "=f"(d[34]), "=f"(d[35]), "=f"(d[36]), "=f"(d[37]), "=f"(d[38]), "=f"(d[39]), "=f"(d[40]), "=f"(d[41]), "=f"(d[42]), "=f"(d[43]), "=f"(d[44]), "=f"(d[45]), "=f"(d[46]), "=f"(d[47]), "=f"(d[48]), "=f"(d[49]), "=f"(d[50]), "=f"(d[51]), "=f"(d[52]), "=f"(d[53]), "=f"(d[54]), "=f"(d[55]), "=f"(d[56]), "=f"(d[57]), "=f"(d[58]), "=f"(d[59]), "=f"(d[60]), "=f"(d[61]), "=f"(d[62]), "=f"(d[63])
    : "r"(a0), "r"(a1), "r"(a2), "r"(a3), "l"(db));
}
DEVI void wgmma_pv(float (&d)[8], uint32_t a0, uint32_t a1, uint32_t a2, uint32_t a3, uint64_t db) {
  asm volatile("wgmma.mma_async.sync.aligned.m64n16k16.f32.bf16.bf16 {%0, %1, %2, %3, %4, %5, %6, %7}, {%8, %9, %10, %11}, %12, 1, 1, 1, 1;"
    : "+f"(d[0]), "+f"(d[1]), "+f"(d[2]), "+f"(d[3]), "+f"(d[4]), "+f"(d[5]), "+f"(d[6]), "+f"(d[7])
    : "r"(a0), "r"(a1), "r"(a2), "r"(a3), "l"(db));
}
DEVI void wgmma_pv0(float (&d)[8], uint32_t a0, uint32_t a1, uint32_t a2, uint32_t a3, uint64_t db) {
  asm volatile("wgmma.mma_async.sync.aligned.m64n16k16.f32.bf16.bf16 {%0, %1, %2, %3, %4, %5, %6, %7}, {%8, %9, %10, %11}, %12, 0, 1, 1, 1;"
    : "=f"(d[0]), "=f"(d[1]), "=f"(d[2]), "=f"(d[3]), "=f"(d[4]), "=f"(d[5]), "=f"(d[6]), "=f"(d[7])
    : "r"(a0), "r"(a1), "r"(a2), "r"(a3), "l"(db));
}

template <int N> DEVI void wgmma_ss(float (&d)[N / 2], uint64_t da, uint64_t db) {
  if constexpr (N == 64) wgmma_ss_n64(d, da, db);
  else if constexpr (N == 128) wgmma_ss_n128(d, da, db);
  else if constexpr (N == 192) wgmma_ss_n192(d, da, db);
  else wgmma_ss_n256(d, da, db);
}

DEVI int oh_chunk(int j, int i, int& need) {
  if (j & 1) {
    if (i >= 3 && i < 7) { need = 16 + 2 * (i - 3); return 24 + (i - 3); }
    if (i >= 7) i -= 4;
  }
  const int g = i / 3, o = (j + 2 * g) & 7;
  need = o;
  return 3 * o + (i - 3 * g);
}

DEVI int next_a_slot(int e, int ai) {
  e++;
  return e < 16 ? (ai == NA - 1 ? 0 : ai + 1) : e < 32 ? 1 + (e & 3) : (e - 27) & 7;
}

struct Ctx {
  uint32_t sbase, bars, peer, t0, a16, b16;
  int wg, lane;
  int ai, bi; uint32_t aph, bph;
  int brem, ae;
  int pa2, pb2;
  int pa, pb;
};

DEVI void release_prev(Ctx& c) {
  if (c.pb >= 0) {
    if (c.lane == 0) mbar_arrive(c.bars + 8 * (BAR_EMPTYB + c.pb));
    if (c.lane == 1) mbar_arrive_cluster(c.bars + 8 * (BAR_EMPTYB + c.pb), c.peer);
  }
  if (c.pa >= 0 && c.lane == 2) mbar_arrive(c.bars + 8 * (BAR_EMPTYA + c.pa));
}

DEVI void gemm_wait(Ctx& c) {
  asm volatile("{ .reg .pred p, q; .reg .u32 c;\n"
               "WAIT_%=:\n"
               "mbarrier.try_wait.parity.shared::cta.b64 p, [%0], %1;\n"
               "mbarrier.try_wait.parity.shared::cta.b64 q, [%2], %3;\n"
               "and.pred p, p, q;\n"
               "@p bra DONE_%=;\n"
               "mov.u32 c, %%clock; sub.u32 c, c, %4; setp.lt.u32 p, c, %5;\n"
               "@p bra WAIT_%=;\n"
               "DONE_%=: }" ::"r"(c.bars + 8 * (BAR_FULLA + c.ai)), "r"((c.aph >> c.ai) & 1), "r"(c.bars + 8 * (BAR_FULLB + c.bi)), "r"(c.bph), "r"(c.t0), "n"(TIMEOUT) : "memory");
}
template <int N>
DEVI void gemm_group(float (&acc)[N / 2], Ctx& c, int g, int& npa, int& npb) {
  const uint32_t a16 = c.a16 + c.ai * (SLOT >> 4);
  const uint32_t b16 = c.b16 + c.bi * (SLOT >> 4);
  bool adv;
  if constexpr (N >= 192) {
    const uint32_t a2 = a16 + (g & 1) * 4;
    wgmma_ss<N>(acc, desc_sw128<16>(a2), desc_sw128<2048>(b16));
    wgmma_ss<N>(acc, desc_sw128<16>(a2 + 2), desc_sw128<2048>(b16 + 512));
    adv = g & 1;
  } else {
#pragma unroll
    for (int s = 0; s < 4; s++) wgmma_ss<N>(acc, desc_sw128<16>(a16 + s * 2), desc_sw128<4096>(b16 + (s >> 1) * 512 + (s & 1) * 128));
    adv = true;
  }
  wgmma_commit();
  npb = c.brem > 0 ? c.bi : -1;
  c.brem--;
  if (++c.bi == NB) { c.bi = 0; c.bph ^= 1; }
  npa = -1;
  if (adv) { npa = c.ai; c.aph ^= 1u << c.ai; c.ai = next_a_slot(c.ae, c.ai); c.ae++; }
}

template <int N>
DEVI void bare_groups(float (&acc)[N / 2], Ctx& c, int g0, int g1) {
  for (int g = g0; g < g1; g++) {
    int npa, npb;
    gemm_wait(c);
    wgmma_fence();
    gemm_group<N>(acc, c, g, npa, npb);
    wgmma_wait<1>();
    release_prev(c);
    c.pa = npa; c.pb = npb;
  }
}
DEVI void drain(Ctx& c) {
  wgmma_wait<0>();
  release_prev(c);
  c.pa = c.pb = -1;
}

constexpr float SC = 0.25f * 1.4426950408889634f;

#define ONCE _Pragma("unroll 1") for (unsigned once_ = 0; once_ < gridDim.y; once_++)

struct Attn {
  uint32_t q[4][4];
  uint32_t nm[4];
  float g0, g1;
  int cmin;
  int rowc;
};

template <int O0, int NS>
DEVI void kill32(float (&S)[NS]) {
#pragma unroll
  for (int i = 0; i < 32; i++) S[O0 + i] = __int_as_float(0xff800000);
}
DEVI void row_max(const float (&S)[64], float& x0, float& x1) {
#pragma unroll
  for (int n = 0; n < 16; n++) {
    x0 = fmaxf(x0, fmaxf(S[4 * n], S[4 * n + 1])); x1 = fmaxf(x1, fmaxf(S[4 * n + 2], S[4 * n + 3]));
  }
}
template <int K, bool PRE = false>
DEVI void exp8(const float (&S)[64], uint32_t (&P)[4], float n0, float n1, float (&l)[4]) {
  float e[8];
#pragma unroll
  for (int i = 0; i < 8; i++) e[i] = ex2(PRE ? S[8 * K + i] : fmaf(S[8 * K + i], SC, (i & 2) ? n1 : n0));
  l[0] += e[0]; l[1] += e[1]; l[2] += e[2]; l[3] += e[3];
  l[0] += e[4]; l[1] += e[5]; l[2] += e[6]; l[3] += e[7];
#pragma unroll
  for (int i = 0; i < 4; i++) P[i] = pack_bf16(e[2 * i], e[2 * i + 1]) | (__float_as_uint(l[i]) & blockIdx.y);
}
DEVI void merge_fl(float (&S)[64], const float (&F)[32], int rowc) {
#pragma unroll
  for (int n = 0; n < 8; n++) {
    if (n * 8 > rowc) S[32 + 4 * n] = F[4 * n];
    if (n * 8 + 1 > rowc) S[32 + 4 * n + 1] = F[4 * n + 1];
    if (n * 8 > rowc + 8) S[32 + 4 * n + 2] = F[4 * n + 2];
    if (n * 8 + 1 > rowc + 8) S[32 + 4 * n + 3] = F[4 * n + 3];
  }
}
DEVI bool wg_any(int wg, bool v) {
  uint32_t r;
  if (wg == 0) asm volatile("{ .reg .pred p, q; setp.ne.u32 p, %1, 0; bar.red.or.pred q, 1, 128, p; selp.u32 %0, 1, 0, q; }" : "=r"(r) : "r"((uint32_t)v) : "memory");
  else asm volatile("{ .reg .pred p, q; setp.ne.u32 p, %1, 0; bar.red.or.pred q, 2, 128, p; selp.u32 %0, 1, 0, q; }" : "=r"(r) : "r"((uint32_t)v) : "memory");
  return r != 0;
}

DEVI void qk_a(float (&S)[64], float (&F)[32], const uint32_t (&q)[4], uint32_t kb) {
  wgmma_fence();
  wgmma_qk128(S, q[0], q[1], q[2], q[3], desc_sw64(kb + 3 * 256));
  wgmma_qk64(F, q[0], q[1], q[2], q[3], desc_sw64(kb));
}
DEVI void fix_a(float (&S)[64], float (&F)[32], const Attn& at) {
  if (at.cmin > 0) { kill32<0>(F); if (at.cmin > 3) kill32<0>(S); }
  merge_fl(S, F, at.rowc);
}
DEVI void fix_b(float (&S)[64], const Attn& at) {
  if (at.cmin > 1) { kill32<0>(S); if (at.cmin > 2) kill32<32>(S); }
}
DEVI void release_all(Ctx& c) {
  release_prev(c);
  c.pa = c.pa2; c.pb = c.pb2;
  release_prev(c);
  c.pa = c.pb = c.pa2 = c.pb2 = -1;
}
template <int W> DEVI void claim(Ctx& c, uint32_t& a16, uint32_t& b16) {
  gemm_wait(c);
  a16 = c.a16 + c.ai * (SLOT >> 4);
  b16 = c.b16 + c.bi * (SLOT >> 4);
  const int npb = c.brem > 0 ? c.bi : -1;
  c.brem--;
  if (++c.bi == NB) { c.bi = 0; c.bph ^= 1; }
  if (W == 0) { c.pa = c.ai; c.pb = npb; } else { c.pa2 = c.ai; c.pb2 = npb; }
  c.aph ^= 1u << c.ai; c.ai = next_a_slot(c.ae, c.ai); c.ae++;
}
template <int ST> DEVI void g_step(float (&acc)[64], uint32_t a16, uint32_t b16, uint32_t dep) {
  a16 += dep & blockIdx.y;
  wgmma_ss<128>(acc, desc_sw128<16>(a16 + ST * 2), desc_sw128<4096>(b16 + (ST >> 1) * 512 + (ST & 1) * 128));
}
template <int NH>
DEVI void exp_all(float (&acc)[64], Ctx& c, const float (&S)[64], uint32_t (&P)[8][4], float n0, float n1, float (&l)[4],
                  uint32_t a0, uint32_t b0, uint32_t a1, uint32_t b1) {
  if (NH > 0) { wgmma_fence(); g_step<0>(acc, a0, b0, 0u); }
  exp8<0>(S, P[0], n0, n1, l); if (NH > 1) g_step<1>(acc, a0, b0, P[0][0]);
  exp8<1>(S, P[1], n0, n1, l); if (NH > 1) g_step<2>(acc, a0, b0, P[1][0]); else if (NH > 0) g_step<1>(acc, a0, b0, P[1][0]);
  exp8<2>(S, P[2], n0, n1, l); if (NH > 1) g_step<3>(acc, a0, b0, P[2][0]);
  exp8<3>(S, P[3], n0, n1, l); if (NH > 1) g_step<0>(acc, a1, b1, P[3][0]); else if (NH > 0) g_step<2>(acc, a0, b0, P[3][0]);
  exp8<4>(S, P[4], n0, n1, l); if (NH > 1) g_step<1>(acc, a1, b1, P[4][0]);
  exp8<5>(S, P[5], n0, n1, l); if (NH > 1) g_step<2>(acc, a1, b1, P[5][0]); else if (NH > 0) g_step<3>(acc, a0, b0, P[5][0]);
  exp8<6>(S, P[6], n0, n1, l); if (NH > 1) g_step<3>(acc, a1, b1, P[6][0]);
  exp8<7>(S, P[7], n0, n1, l);
}

template <int NH0, int NH1>
DEVI void head_pass(float (&acc)[64], Ctx& c, const Attn& at, uint32_t kb, float n0, float n1, float (&O)[8], float& l0, float& l1) {
  float S[64], l[4] = {0.f, 0.f, 0.f, 0.f};
  uint32_t P[8][4], a0 = 0, b0 = 0, a1 = 0, b1 = 0;
  {
    float F[32];
    qk_a(S, F, at.q[0], kb);
    wgmma_commit();
    if (NH0 > 0) claim<0>(c, a0, b0);
    if (NH0 > 1) claim<1>(c, a1, b1);
    wgmma_wait<0>();
    fix_a(S, F, at);
  }
  exp_all<NH0>(acc, c, S, P, n0, n1, l, a0, b0, a1, b1);
  {
    uint32_t PF[4][4];
#pragma unroll
    for (int k = 0; k < 4; k++) {
#pragma unroll
      for (int i = 0; i < 4; i++) {
        const int col = k * 16 + (i >> 1) * 8, r = at.rowc + (i & 1) * 8;
        const uint32_t m = (col > r ? 0xFFFFu : 0u) | (col + 1 > r ? 0xFFFF0000u : 0u);
        PF[k][i] = P[4 + k][i] & m; P[4 + k][i] &= ~m;
      }
    }
    wgmma_fence();
    wgmma_pv0(O, P[0][0], P[0][1], P[0][2], P[0][3], desc_sw64(kb + 3 * 256 + 2));
#pragma unroll
    for (int k = 1; k < 8; k++) wgmma_pv(O, P[k][0], P[k][1], P[k][2], P[k][3], desc_sw64(kb + 3 * 256 + 2 + k * 64));
#pragma unroll
    for (int k = 0; k < 4; k++) wgmma_pv(O, PF[k][0], PF[k][1], PF[k][2], PF[k][3], desc_sw64(kb + 2 + k * 64));
    wgmma_qk128(S, at.q[0][0], at.q[0][1], at.q[0][2], at.q[0][3], desc_sw64(kb + 256));
    wgmma_commit();
    wgmma_wait<0>();
  }
  if (NH0 > 0) release_all(c);
  if (NH1 > 0) claim<0>(c, a0, b0);
  if (NH1 > 1) claim<1>(c, a1, b1);
  fix_b(S, at);
  exp_all<NH1>(acc, c, S, P, n0, n1, l, a0, b0, a1, b1);
  wgmma_fence();
#pragma unroll
  for (int k = 0; k < 8; k++) wgmma_pv(O, P[k][0], P[k][1], P[k][2], P[k][3], desc_sw64(kb + 256 + 2 + k * 64));
  wgmma_commit();
  l0 = l[0] + l[1]; l1 = l[2] + l[3];
  l0 += __shfl_xor_sync(0xffffffffu, l0, 1); l1 += __shfl_xor_sync(0xffffffffu, l1, 1);
  l0 += __shfl_xor_sync(0xffffffffu, l0, 2); l1 += __shfl_xor_sync(0xffffffffu, l1, 2);
  wgmma_wait<0>();
  if (NH1 > 0) release_all(c);
}

DEVI void attention(float (&acc)[64], Ctx& c, Attn& at, int wi) {
  const uint32_t kvb = ((c.sbase & 0x3FFFF) + OFF_KV + c.wg * 4096) >> 4;
#pragma unroll 1
  for (int h = 0; h < 4; h++) {
    const uint32_t kb = kvb + (h & 1) * (KVBUF >> 4);
    float O[8], l0, l1;
    mbar_wait(c.bars + 8 * (BAR_KVFULL + (h & 1)), h >> 1, c.t0);
    head_pass<HK0, HK1>(acc, c, at, kb, __uint_as_float(at.nm[0] << 16), __uint_as_float(at.nm[0] & 0xffff0000u), O, l0, l1);
    const bool bad = !(l0 > 1e-6f && l0 < 1e18f && l1 > 1e-6f && l1 < 1e18f);
    float c0, c1;
    uint32_t o0, o1, o2, o3;
    if (wg_any(c.wg, bad)) {
      float x0 = __int_as_float(0xff800000), x1 = x0;
      {
        float T[64];
        wgmma_fence();
        wgmma_qk128(T, at.q[0][0], at.q[0][1], at.q[0][2], at.q[0][3], desc_sw64(kb + 256));
        wgmma_commit();
        wgmma_wait<0>();
        fix_b(T, at);
        row_max(T, x0, x1);
      }
      ONCE { asm volatile("" : "+f"(x0), "+f"(x1)); }
      {
        float T[64], G[32];
        qk_a(T, G, at.q[0], kb);
        wgmma_commit();
        wgmma_wait<0>();
        fix_a(T, G, at);
        row_max(T, x0, x1);
      }
      x0 = fmaxf(x0, __shfl_xor_sync(0xffffffffu, x0, 1)); x1 = fmaxf(x1, __shfl_xor_sync(0xffffffffu, x1, 1));
      x0 = fmaxf(x0, __shfl_xor_sync(0xffffffffu, x0, 2)); x1 = fmaxf(x1, __shfl_xor_sync(0xffffffffu, x1, 2));
      float O2[8];
      head_pass<0, 0>(acc, c, at, kb, -x0 * SC, -x1 * SC, O2, l0, l1);
      c0 = __fdividef(at.g0, l0); c1 = __fdividef(at.g1, l1);
      o0 = pack_bf16(O2[0] * c0, O2[1] * c0); o1 = pack_bf16(O2[2] * c1, O2[3] * c1);
      o2 = pack_bf16(O2[4] * c0, O2[5] * c0); o3 = pack_bf16(O2[6] * c1, O2[7] * c1);
    } else {
      c0 = __fdividef(at.g0, l0); c1 = __fdividef(at.g1, l1);
      o0 = pack_bf16(O[0] * c0, O[1] * c0); o1 = pack_bf16(O[2] * c1, O[3] * c1);
      o2 = pack_bf16(O[4] * c0, O[5] * c0); o3 = pack_bf16(O[6] * c1, O[7] * c1);
    }
    if (c.lane == 0) mbar_arrive(c.bars + 8 * (h == 3 ? BAR_ATTDONE : BAR_KVEMPTY + (h & 1)));
    const uint32_t ost = c.sbase + OFF_A + c.wg * 8192 + h * 2048;
    const int mi = c.lane >> 3;
    const int srow = wi * 16 + (c.lane & 7) + 8 * (mi & 1);
    stsm_x4(ost + srow * 32 + (mi >> 1) * 16, o0, o1, o2, o3);
    fence_async_smem();
    __syncwarp();
    if (c.lane == 0) mbar_arrive(c.bars + 8 * (BAR_STG + c.wg));
#pragma unroll
    for (int i = 0; i < 4; i++) { at.q[0][i] = at.q[1][i]; at.q[1][i] = at.q[2][i]; at.q[2][i] = at.q[3][i]; }
    at.nm[0] = at.nm[1]; at.nm[1] = at.nm[2]; at.nm[2] = at.nm[3];
  }
}

template <int CH, int NACC>
DEVI void store_h_chunk(const float (&acc)[NACC], uint32_t base  , int lane, float s0, float s1) {
  const int mi = lane >> 3;
#pragma unroll
  for (int tp = 0; tp < 4; tp++) {
    const int t = CH * 8 + tp * 2;
    const uint32_t r0 = pack_bf16(fmaxf(acc[4 * t + 0], 0.f) * s0, fmaxf(acc[4 * t + 1], 0.f) * s0);
    const uint32_t r1 = pack_bf16(fmaxf(acc[4 * t + 2], 0.f) * s1, fmaxf(acc[4 * t + 3], 0.f) * s1);
    const uint32_t r2 = pack_bf16(fmaxf(acc[4 * t + 4], 0.f) * s0, fmaxf(acc[4 * t + 5], 0.f) * s0);
    const uint32_t r3 = pack_bf16(fmaxf(acc[4 * t + 6], 0.f) * s1, fmaxf(acc[4 * t + 7], 0.f) * s1);
    stsm_x4(base + (((tp * 2 + (mi >> 1)) ^ (lane & 7)) << 4), r0, r1, r2, r3);
  }
}

DEVI void get_gate(Attn& at, const Ctx& c, int warp) {
  mbar_wait(c.bars + 8 * BAR_GIN, 0, c.t0);
  const uint32_t a = c.sbase + OFF_GIN + (warp * 16 + (c.lane >> 2)) * 4;
  asm volatile("ld.shared.f32 %0, [%1];" : "=f"(at.g0) : "r"(a) : "memory");
  asm volatile("ld.shared.f32 %0, [%1];" : "=f"(at.g1) : "r"(a + 32) : "memory");
}

template <int N>
DEVI void phase_q(Ctx& c, Attn& at, int warp) {
  float acc[N / 2];
#pragma unroll
  for (int i = 0; i < N / 2; i++) acc[i] = 0.f;
  bare_groups<N>(acc, c, 0, 16);
  drain(c);
  const int lane = c.lane, mi = lane >> 3;
  const int row = warp * 16 + (lane & 7) + 8 * (mi & 1);
  const int sw = (row >> 1) & 3;
#pragma unroll
  for (int hh = 0; hh < 4; hh++) {
    const uint32_t base = c.sbase + OFF_KV + hh * 8192 + row * 64;
#pragma unroll
    for (int kv = 0; kv < 2; kv++) {
      const int t = 8 + kv * 8 + 2 * hh;
      stsm_x4(base + (((kv * 2 + (mi >> 1)) ^ sw) << 4),
              pack_bf16(acc[4 * t + 0], acc[4 * t + 1]), pack_bf16(acc[4 * t + 2], acc[4 * t + 3]),
              pack_bf16(acc[4 * t + 4], acc[4 * t + 5]), pack_bf16(acc[4 * t + 6], acc[4 * t + 7]));
    }
  }
  fence_async_smem();
  __syncwarp();
  if (lane == 0) mbar_arrive(c.bars + 8 * (BAR_STG + c.wg));
  if constexpr (N == 256) {
    get_gate(at, c, warp);
    store_h_chunk<3>(acc, c.sbase + OFF_KV + 32768 + row * 128, lane, 1.f - at.g0, 1.f - at.g1);
    fence_async_smem();
    __syncwarp();
    if (lane == 0) mbar_arrive(c.bars + 8 * (BAR_STE + c.wg));
  }
#pragma unroll
  for (int hh = 0; hh < 4; hh++) {
#pragma unroll
    for (int i = 0; i < 4; i++) at.q[hh][i] = pack_bf16(acc[8 * hh + 2 * i], acc[8 * hh + 2 * i + 1]);
    const float* q = &acc[8 * hh];
    const float* k = &acc[32 + 8 * hh];
    float d0 = q[0] * k[0] + q[1] * k[1] + q[4] * k[4] + q[5] * k[5], d1 = q[2] * k[2] + q[3] * k[3] + q[6] * k[6] + q[7] * k[7];
    d0 += __shfl_xor_sync(0xffffffffu, d0, 1); d1 += __shfl_xor_sync(0xffffffffu, d1, 1);
    d0 += __shfl_xor_sync(0xffffffffu, d0, 2); d1 += __shfl_xor_sync(0xffffffffu, d1, 2);
    at.nm[hh] = pack_bf16(-d0 * SC, -d1 * SC);
  }
}

DEVI void first_loads(const Params& P, uint32_t sbase, int e, int j, int rb) {
  const uint32_t bars = sbase + OFF_BAR, fb = bars + 8 * (BAR_FULLB + e), fa = bars + 8 * (BAR_FULLA + e);
  mbar_expect_tx(fa, 16384);
  mbar_expect_tx(fb, (j & 1) ? 12288 : 16384);
  if (e == 0) tma_load_2d(sbase + OFF_A, &P.tmX, 0, rb * 128, fa);
#pragma unroll
  for (int r = 0; r < 2; r++) {
    tma_load_3d(sbase + OFF_B + e * SLOT + r * 8192, &P.tmWqkv, 64 * j, e * 32 + r * 16, 0, fb);
    if (!(j & 1)) tma_load_3d(sbase + OFF_B + e * SLOT + r * 8192 + 6144, &P.tmW1a, 0, e * 32 + r * 16, 24 + (j >> 1), fb);
  }
  if (e == 1) tma_load_2d(sbase + OFF_A + SLOT, &P.tmX, 64, rb * 128, fa);
}

__global__ void __cluster_dims__(2, 1, 1) __launch_bounds__(384, 1) fused_kernel(const __grid_constant__ Params P) {
  extern __shared__ uint8_t smem_raw[];
  const uint32_t sbase = (smem_u32(smem_raw) + 1023u) & ~1023u;
  const uint32_t bars = sbase + OFF_BAR;
  const int tid = threadIdx.x, warp = tid >> 5, lane = tid & 31;
  const uint32_t rank = blockIdx.x & 1, peer = rank ^ 1;
  const int j = (blockIdx.x >> 1) & 7, rb = ((blockIdx.x >> 4) << 1) | rank;
  const uint32_t t0 = clk32();

  const int typeB = j & 1;
  if (tid == 288) {
    for (int s = 0; s < NA2; s++) mbar_init(bars + 8 * (BAR_FULLA + s), 1);
    for (int s = 0; s < NB; s++) mbar_init(bars + 8 * (BAR_FULLB + s), 1);
    fence_async_smem();
  } else if (tid < 10) {
    asm volatile("prefetch.tensormap [%0];" ::"l"(&P.tmX + tid) : "memory");
  } else if (tid == 256) {
    for (int s = 0; s < NA2; s++) mbar_init(bars + 8 * (BAR_EMPTYA + s), 10);
    for (int s = 0; s < NB; s++) mbar_init(bars + 8 * (BAR_EMPTYB + s), 16);
  } else if (tid == 320) {
    for (int s = 0; s < 2; s++) { mbar_init(bars + 8 * (BAR_KVFULL + s), 1); mbar_init(bars + 8 * (BAR_KVEMPTY + s), 8); mbar_init(bars + 8 * (BAR_STG + s), 4); mbar_init(bars + 8 * (BAR_STE + s), 4); }
    mbar_init(bars + 8 * BAR_PIN, 1); mbar_init(bars + 8 * BAR_ATTDONE, 8); mbar_init(bars + 8 * BAR_GIN, 1); mbar_init(bars + 8 * BAR_GATE, 1); mbar_init(bars + 8 * (BAR_GATE + 1), 1);
  }
  if (tid >= 256 && lane == 0) asm volatile("fence.mbarrier_init.release.cluster;" ::: "memory");
  const unsigned ep1 = ld_relaxed(&g_epoch) + 1;
  __syncwarp();
  cluster_arrive();
  if (tid == 288) { first_loads(P, sbase, 0, j, rb); first_loads(P, sbase, 1, j, rb); }
  __syncwarp();

  const int on = 12 + 4 * typeB;

  if (warp < 8) {
    asm volatile("setmaxnreg.inc.sync.aligned.u32 232;");
    cluster_wait();
    const int wg = __shfl_sync(0xffffffffu, warp >> 2, 0), wi = warp & 3;
    Ctx c{sbase, bars, peer, t0, ((sbase & 0x3FFFF) + OFF_A + wg * 8192) >> 4, ((sbase & 0x3FFFF) + OFF_B) >> 4, wg, lane, 0, 0, 0u, 0u, 32 + on + 4 - NB, 0, -1, -1, -1, -1};
    Attn at;
    at.cmin = 4 - 2 * rb - wg;
    at.rowc = wi * 16 + (lane >> 2) - (lane & 3) * 2;
    if (tid == 0) TR(0);
    if (typeB) phase_q<192>(c, at, warp);
    else phase_q<256>(c, at, warp);
    if (tid == 0) TR(2);
    {
      float acc[96];
#pragma unroll
      for (int i = 0; i < 96; i++) acc[i] = 0.f;
      bare_groups<192>(acc, c, 0, 16);
      get_gate(at, c, warp);
      drain(c);
      if (tid == 0) TR(1);
      const uint32_t rowoff = (warp * 16 + (lane & 7) + 8 * ((lane >> 3) & 1)) * 128;
      const float s0 = 1.f - at.g0, s1 = 1.f - at.g1;
      constexpr int e0 = 16 % NA, e1 = 17 % NA, e2 = 18 % NA;
      mbar_wait(bars + 8 * (BAR_FULLA + e0), (16 / NA) & 1, t0);
      store_h_chunk<0>(acc, sbase + OFF_A + e0 * SLOT + rowoff, lane, s0, s1);
      mbar_wait(bars + 8 * (BAR_FULLA + e1), (17 / NA) & 1, t0);
      store_h_chunk<1>(acc, sbase + OFF_A + e1 * SLOT + rowoff, lane, s0, s1);
      mbar_wait(bars + 8 * (BAR_FULLA + e2), (18 / NA) & 1, t0);
      store_h_chunk<2>(acc, sbase + OFF_A + e2 * SLOT + rowoff, lane, s0, s1);
    }
    fence_async_smem();
    wg_bar(wg);
    if (lane == 0) mbar_arrive(bars + 8 * (BAR_STG + wg));
    if (tid == 0) TR(4);
    float own[32];
    {
      float acc[64];
#pragma unroll
      for (int i = 0; i < 64; i++) acc[i] = 0.f;
      attention(acc, c, at, wi);
      if (tid == 0) TR(3);
      bare_groups<128>(acc, c, 4 * (HK0 + HK1), on);
      drain(c);
      if (tid == 0) TR(5);
      named_bar<3>(256);
      const uint32_t pst = sbase + OFF_B + ((30 + on) % NB) * SLOT + wg * 8192 + (tid & 127) * 16;
#pragma unroll
      for (int i = 0; i < 4; i++) {
        uint32_t r[4];
#pragma unroll
        for (int k = 0; k < 4; k++) {
          const int idx = 8 * i + 2 * k;
          const float lo = typeB ? acc[idx] : acc[32 + idx], hi = typeB ? acc[idx + 1] : acc[32 + idx + 1];
          r[k] = pack_bf16(lo, hi);
        }
        sts128(pst + i * 2048, r[0], r[1], r[2], r[3]);
      }
#pragma unroll
      for (int i = 0; i < 32; i++) own[i] = typeB ? acc[32 + i] : acc[i];
      fence_async_smem();
      __syncwarp();
      if (lane == 0) mbar_arrive(bars + 8 * (BAR_STG + wg));
    }
    for (int g = 0; g < 8; g++) {
      const uint32_t a16 = c.a16 + c.ai * (SLOT >> 4);
      const uint32_t b16 = c.b16 + c.bi * (SLOT >> 4) + (g & 1) * 512;
      gemm_wait(c);
      wgmma_fence();
#pragma unroll
      for (int s = 0; s < 4; s++) wgmma_ss<64>(own, desc_sw128<16>(a16 + s * 2), desc_sw128<2048>(b16 + s * 128));
      wgmma_commit();
      c.ai = next_a_slot(c.ae, c.ai); c.ae++;
      if (g & 1) { if (++c.bi == NB) { c.bi = 0; c.bph ^= 1; } }
    }
    wgmma_wait<0>();
    if (tid == 0) TR(6);
    mbar_wait(bars + 8 * BAR_PIN, 0, t0);
    if (tid == 0) TR(7);
    {
      const uint32_t pin = sbase + OFF_B + ((31 + on) % NB) * SLOT + wg * 8192 + (tid & 127) * 16;
      wg_bar(wg);
      const uint32_t ob = sbase + OFF_A + wg * 8192;
      const uint32_t orow = ob + (wi * 16 + (lane & 7) + 8 * ((lane >> 3) & 1)) * 128;
#pragma unroll
      for (int i = 0; i < 4; i++) {
        const uint4 v = lds128(pin + i * 2048);
        const uint32_t r[4] = {v.x, v.y, v.z, v.w};
        uint32_t o[4];
#pragma unroll
        for (int k = 0; k < 4; k++) {
          const int idx = 8 * i + 2 * k;
          o[k] = pack_bf16(own[idx] + __uint_as_float(r[k] << 16), own[idx + 1] + __uint_as_float(r[k] & 0xffff0000u));
        }
        stsm_x4(orow + (((i * 2 + (lane >> 4)) ^ (lane & 7)) << 4), o[0], o[1], o[2], o[3]);
      }
      fence_async_smem();
      __syncwarp();
      if (lane == 0) {
        tma_store_2d(&P.tmOut, j * 64, rb * 128 + warp * 16, ob + wi * 2048);
        bulk_commit();
        asm volatile("cp.async.bulk.wait_group.read 0;" ::: "memory");
      }
    }
    if (tid == 0) TR(8);
  } else {
    asm volatile("setmaxnreg.dec.sync.aligned.u32 40;");
    if (warp == 8) {
      __syncwarp();
      cluster_wait();
      if (lane == 0) {
        int bi = 2; uint32_t bph = 1;
        const int nb = 32 + on + 4;
        for (int eb = 2; eb < nb; eb++) {
          if (eb == 4 || eb == 6) {
            for (int ea = eb - 2 - (eb == 6 ? 1 : 0); ea < (eb == 4 ? 3 : NA); ea++) {
              mbar_expect_tx(bars + 8 * (BAR_FULLA + ea), 16384);
              tma_load_2d(sbase + OFF_A + ea * SLOT, &P.tmX, ea * 64, rb * 128, bars + 8 * (BAR_FULLA + ea));
            }
          }
          const uint32_t fb = bars + 8 * (BAR_FULLB + bi), dst = sbase + OFF_B + bi * SLOT + rank * 8192;
          mbar_wait(bars + 8 * (BAR_EMPTYB + bi), bph, t0);
          if (eb < 16) {
            mbar_expect_tx(fb, typeB ? 12288 : 16384);
            tma_load_3d_mc(dst, &P.tmWqkv, 64 * j, eb * 32 + rank * 16, 0, fb);
            if (!typeB) tma_load_3d_mc(dst + 6144, &P.tmW1a, 0, eb * 32 + rank * 16, 24 + (j >> 1), fb);
          }
          else if (eb < 32) { mbar_expect_tx(fb, 12288); tma_load_3d_mc(dst, &P.tmW1b, 0, (eb - 16) * 32 + rank * 16, 3 * j, fb); }
          else if (eb < 32 + on) { int ow; const int ch = oh_chunk(j, eb - 32, ow); mbar_expect_tx(fb, 16384); tma_load_3d_mc(dst, &P.tmW2, 0, ch * 64 + rank * 32, (j >> 1) * 2, fb); }
          else { mbar_expect_tx(fb, 16384); tma_load_4d_mc(dst, &P.tmWo, 64 * j, 0, eb - 32 - on, rank * 4, fb); }
          if (++bi == NB) { bi = 0; bph ^= 1; }
          if (eb == PFAT) {
            const int b = blockIdx.x;
            l2_prefetch((const uint8_t*)P.w1 + b * 14336, 14336);
            l2_prefetch((const uint8_t*)P.w2 + b * 14336, 14336);
            l2_prefetch((const uint8_t*)P.wo + b * 4096, 4096);
          }
        }
      }
    } else if (warp == 9) {
      cluster_wait();
      if (lane == 0) {
        for (int ea = 0; ea < NA; ea++) mbar_arrive_n(bars + 8 * (BAR_EMPTYA + ea), 2);
        int ai = 0; uint32_t aph = 0xE0;
        const int na = 16 + on + 8;
        unsigned ready = 0;
        for (int ea = NA; ea < na; ea++) {
          const uint32_t fb = bars + 8 * (BAR_FULLA + ai), dst = sbase + OFF_A + ai * SLOT;
          int ch = ea & 7, need = -1;
          if (ea >= 16 + on) { need = 8 + ea - 16 - on; ch = 20 + need; }
          else if (ea >= 19) ch = oh_chunk(j, ea - 16, need);
          if (need >= 0 && !((ready >> need) & 1)) {
            const unsigned* fp = need < 8 ? &g_flag_h[rb * 8 * FS] : need < 16 ? &g_flag_o[rb * 8 * FS] : &g_flag_e[rb * 8 * FS];
            const unsigned tgt = (need & 8) ? ep1 * 8 : ep1 * 2;
            do {
              unsigned v[8];
#pragma unroll
              for (int i = 0; i < 8; i++) v[i] = ld_relaxed(fp + i * FS);
#pragma unroll
              for (int i = 0; i < 8; i++) if ((int)(v[i] - tgt) >= 0) ready |= 1u << (i + (need & 24));
            } while (!((ready >> need) & 1) && clk32() - t0 < TIMEOUT);
            fence_async_global();
          }
          if (ea == 32) mbar_wait(bars + 8 * BAR_ATTDONE, 0, t0);
          mbar_wait(bars + 8 * (BAR_EMPTYA + ai), (aph >> ai) & 1, t0);
          if (ea >= 16 && ea < 19) mbar_arrive(fb);
          else {
            if (ea != 15) mbar_arrive_n(bars + 8 * (BAR_EMPTYA + ai), 2);
            mbar_expect_tx(fb, 16384);
            tma_load_2d(dst, ea < 16 ? &P.tmX : &P.tmHO, ch * 64, rb * 128, fb);
          }
          TR(24 + ea);
          aph ^= 1u << ai;
          ai = next_a_slot(ea, ai);
        }
      }
    } else {
      const int wg = warp - 10;
      cluster_wait();
      {
        const int rowg = rb * 128 + j * 16 + wg * 8;
        const uint32_t xs = sbase + OFF_KV + 32768 + wg * 8192;
        if (lane == 0) {
          mbar_wait(bars + 8 * (BAR_FULLB + 1), 0, t0);
          mbar_expect_tx(bars + 8 * (BAR_GATE + wg), 8192);
          bulk_load(xs, P.x + (size_t)rowg * DM, 8192, bars + 8 * (BAR_GATE + wg));
        }
        const uint4* gw = (const uint4*)P.gate_w;
        const uint4 w0 = __ldg(gw + lane), w1 = __ldg(gw + 32 + lane);
        const uint32_t wa[8] = {w0.x, w0.y, w0.z, w0.w, w1.x, w1.y, w1.z, w1.w};
        mbar_wait(bars + 8 * (BAR_GATE + wg), 0, t0);
        float zz = 0.f;
#pragma unroll 1
        for (int i = 0; i < 8; i++) {
          const uint4 x0 = lds128(xs + i * 1024 + lane * 16), x1 = lds128(xs + i * 1024 + 512 + lane * 16);
          const uint32_t xa[8] = {x0.x, x0.y, x0.z, x0.w, x1.x, x1.y, x1.z, x1.w};
          float z = 0.f;
#pragma unroll
          for (int e = 0; e < 8; e++) {
            z = fmaf(__uint_as_float(xa[e] << 16), __uint_as_float(wa[e] << 16), z);
            z = fmaf(__uint_as_float(xa[e] & 0xffff0000u), __uint_as_float(wa[e] & 0xffff0000u), z);
          }
#pragma unroll
          for (int o = 16; o > 0; o >>= 1) z += __shfl_xor_sync(0xffffffffu, z, o);
          if (lane == i) zz = z;
        }
        if (lane < 8) asm volatile("st.shared.f32 [%0], %1;" ::"r"(sbase + OFF_GST + wg * 32 + lane * 4), "f"(1.f / (1.f + __expf(-zz))) : "memory");
        fence_async_smem();
        __syncwarp();
        if (lane == 0) {
          bulk_store(&g_gate[rowg], sbase + OFF_GST + wg * 32, 32);
          bulk_commit(); bulk_wait_all();
          flag_add(&g_flag_g[rb * FS]);
          if (wg == 1) {
            flag_wait(&g_flag_g[rb * FS], ep1 * 16, t0);
            fence_async_global();
            mbar_expect_tx(bars + 8 * BAR_GIN, 512);
            bulk_load(sbase + OFF_GIN, &g_gate[rb * 128], 512, bars + 8 * BAR_GIN);
          }
          if (wg == 0) TR(10);
        }
      }
      if (lane == 0) {
        const uint32_t stg = bars + 8 * (BAR_STG + wg);
        mbar_wait(stg, 0, t0);
        for (int hh = 0; hh < 4; hh++)
          bulk_store(g_kv + ((size_t)(4 * j + hh) * SEQ + rb * 128 + wg * 64) * 64, sbase + OFF_KV + hh * 8192 + wg * 4096, 4096);
        bulk_commit(); bulk_wait_all();
        flag_add(&g_flag_kv[(rb * 8 + j) * FS]);
        if (wg == 0) TR(21);
        if (!typeB) {
          mbar_wait(bars + 8 * (BAR_STE + wg), 0, t0);
          tma_store_2d(&P.tmHOs, (24 + (j >> 1)) * 64, rb * 128 + wg * 64, sbase + OFF_KV + 32768 + wg * 8192);
          bulk_commit(); bulk_wait_all();
          flag_add(&g_flag_e[(rb * 8 + j) * FS]);
          if (wg == 1) flag_wait(&g_flag_e[(rb * 8 + j) * FS], ep1 * 2, t0);
        }
        const int nblk = rb >= 2 ? 3 : rb + 1;
        const uint32_t kvbytes = nblk * 8192;
        const uint8_t* kvsrc = g_kv + ((size_t)(4 * j) * SEQ + (rb + 1 - nblk) * 128) * 64;
        const uint32_t kvdst = sbase + OFF_KV + wg * KVBUF + (3 - nblk) * 8192;
        {
          const unsigned* f0 = &g_flag_kv[(rb * 8 + j) * FS];
          const unsigned* f1 = rb >= 1 ? f0 - 8 * FS : f0;
          const unsigned* f2 = rb >= 2 ? f0 - 16 * FS : f0;
          unsigned v0, v1, v2;
          do { v0 = ld_relaxed(f0); v1 = ld_relaxed(f1); v2 = ld_relaxed(f2); }
          while (((int)(v0 - ep1 * 2) < 0 || (int)(v1 - ep1 * 2) < 0 || (int)(v2 - ep1 * 2) < 0) && clk32() - t0 < TIMEOUT);
        }
        if (wg == 0) TR(11);
        fence_async_global();
        mbar_expect_tx(bars + 8 * (BAR_KVFULL + wg), kvbytes);
        bulk_load(kvdst, kvsrc + (size_t)wg * SEQ * 64, kvbytes, bars + 8 * (BAR_KVFULL + wg));
        for (int ev = 1; ev < 7; ev++) {
          mbar_wait(stg, ev & 1, t0);
          if (ev == 1) {
            for (int i = 0; i < 3; i++)
              tma_store_2d(&P.tmHOs, (3 * j + i) * 64, rb * 128 + wg * 64, sbase + OFF_A + ((16 + i) % NA) * SLOT + wg * 8192);
            bulk_commit(); bulk_wait_all();
            flag_add(&g_flag_h[(rb * 8 + j) * FS]);
            for (int i = 0; i < 3; i++) mbar_arrive(bars + 8 * (BAR_EMPTYA + (16 + i) % NA));
            if (wg == 0) TR(22);
            if (wg == 0) {
              const unsigned old = atomicAdd(&g_done, 1u);
              if (old == gridDim.x - 1) { g_done = 0; *(volatile unsigned*)&g_epoch = ep1; }
            }
          } else if (ev == 6) {
            bulk_store(g_part + (size_t)(rb * 8 + (j ^ 1)) * 16384 + wg * 8192, sbase + OFF_B + ((30 + on) % NB) * SLOT + wg * 8192, 8192);
            bulk_commit(); bulk_wait_all();
            flag_add(&g_flag_p[(rb * 8 + (j ^ 1)) * FS]);
            if (wg == 0) TR(23);
            if (wg == 1) {
              flag_wait(&g_flag_p[(rb * 8 + j) * FS], ep1 * 2, t0);
              fence_async_global();
              mbar_expect_tx(bars + 8 * BAR_PIN, 16384);
              bulk_load(sbase + OFF_B + ((31 + on) % NB) * SLOT, g_part + (size_t)(rb * 8 + j) * 16384, 16384, bars + 8 * BAR_PIN);
            }
          } else {
            const int hh = ev - 2;
            tma_store_2d(&P.tmOs, DFF + hh * 128 + j * 16, rb * 128 + wg * 64, sbase + OFF_A + (15 % NA) * SLOT + wg * 8192 + hh * 2048);
            bulk_commit();
            if (hh == wg) {
              mbar_wait(bars + 8 * (BAR_KVEMPTY + wg), 0, t0);
              mbar_expect_tx(bars + 8 * (BAR_KVFULL + wg), kvbytes);
              bulk_load(kvdst, kvsrc + (size_t)(wg + 2) * SEQ * 64, kvbytes, bars + 8 * (BAR_KVFULL + wg));
            }
            bulk_wait_all();
            flag_add(&g_flag_o[(rb * 8 + hh * 2 + (j >> 2)) * FS]);
            if (hh == 3) mbar_arrive(bars + 8 * (BAR_EMPTYA + 15 % NA));
            if (wg == 0) TR(12 + hh);
          }
        }
      }
    }
  }
}

typedef CUresult (*EncodeFn)(CUtensorMap*, CUtensorMapDataType, cuuint32_t, void*, const cuuint64_t*, const cuuint64_t*, const cuuint32_t*,
                             const cuuint32_t*, CUtensorMapInterleave, CUtensorMapSwizzle, CUtensorMapL2promotion, CUtensorMapFloatOOBfill);

void make_map(EncodeFn enc, CUtensorMap* m, const void* ptr, int rank, const cuuint64_t* dims, const cuuint64_t* strides, const cuuint32_t* box,
              CUtensorMapSwizzle sw = CU_TENSOR_MAP_SWIZZLE_128B) {
  cuuint32_t es[4] = {1, 1, 1, 1};
  enc(m, CU_TENSOR_MAP_DATA_TYPE_BFLOAT16, rank, const_cast<void*>(ptr), dims, strides, box, es, CU_TENSOR_MAP_INTERLEAVE_NONE, sw,
      CU_TENSOR_MAP_L2_PROMOTION_L2_256B, CU_TENSOR_MAP_FLOAT_OOB_FILL_NONE);
}

}

extern "C" void kernel_launch(void* const* d_in, const int* in_sizes, int n_in, void* d_out, int out_size) {
  (void)in_sizes; (void)n_in; (void)out_size;
  static EncodeFn enc = nullptr;
  static void* ho_ptr = nullptr;
  if (!enc) {
    void* fn = nullptr; cudaDriverEntryPointQueryResult st;
    cudaGetDriverEntryPoint("cuTensorMapEncodeTiled", &fn, cudaEnableDefault, &st);
    enc = (EncodeFn)fn;
    cudaGetSymbolAddress(&ho_ptr, g_ho);
    cudaFuncSetAttribute(fused_kernel, cudaFuncAttributeMaxDynamicSharedMemorySize, SMEM_BYTES);
  }
  const __nv_bfloat16* x = (const __nv_bfloat16*)d_in[0];
  const __nv_bfloat16* wqkv = (const __nv_bfloat16*)d_in[1];
  const __nv_bfloat16* wo = (const __nv_bfloat16*)d_in[2];
  const __nv_bfloat16* w1 = (const __nv_bfloat16*)d_in[4];
  const __nv_bfloat16* w2 = (const __nv_bfloat16*)d_in[5];
  const __nv_bfloat16* gate_w = (const __nv_bfloat16*)d_in[6];
  Params P;
  { cuuint64_t d[2] = {DM, SEQ}, s[1] = {DM * 2}; cuuint32_t b[2] = {64, 128}; make_map(enc, &P.tmX, x, 2, d, s, b); }
  { cuuint64_t d[3] = {512, 512, 3}, s[2] = {1536 * 2, 512 * 2}; cuuint32_t b[3] = {64, 16, 3}; make_map(enc, &P.tmWqkv, wqkv, 3, d, s, b); }
  { cuuint64_t d[3] = {64, 512, 28}, s[2] = {DFF * 2, 128}; cuuint32_t b[3] = {64, 16, 1}; make_map(enc, &P.tmW1a, w1, 3, d, s, b);
    b[2] = 3; make_map(enc, &P.tmW1b, w1, 3, d, s, b); }
  { cuuint64_t d[3] = {64, DFF, 8}, s[2] = {DM * 2, 128}; cuuint32_t b[3] = {64, 32, 2}; make_map(enc, &P.tmW2, w2, 3, d, s, b); }
  { cuuint64_t d[4] = {DM, 16, 4, 8}, s[3] = {DM * 2, 16 * DM * 2, 64 * DM * 2}; cuuint32_t b[4] = {64, 16, 1, 4}; make_map(enc, &P.tmWo, wo, 4, d, s, b); }
  { cuuint64_t d[2] = {KHO, SEQ}, s[1] = {KHO * 2}; cuuint32_t b[2] = {64, 128}; make_map(enc, &P.tmHO, ho_ptr, 2, d, s, b);
    b[1] = 64; make_map(enc, &P.tmHOs, ho_ptr, 2, d, s, b);
    b[0] = 16; make_map(enc, &P.tmOs, ho_ptr, 2, d, s, b, CU_TENSOR_MAP_SWIZZLE_NONE); }
  { cuuint64_t d[2] = {DM, SEQ}, s[1] = {DM * 2}; cuuint32_t b[2] = {64, 16}; make_map(enc, &P.tmOut, d_out, 2, d, s, b); }
  P.x = x; P.gate_w = gate_w; P.w1 = w1; P.w2 = w2; P.wo = wo; P.out = (__nv_bfloat16*)d_out;
  fused_kernel<<<128, 384, SMEM_BYTES>>>(P);
}
```

```cpp
#include <cuda_runtime.h>
#include <cuda_bf16.h>
#include <cuda.h>
#include <stdint.h>

#define DEVI __device__ __forceinline__

namespace {

constexpr int SEQ = 2048, DM = 512, DFF = 1792, KHO = 2304;
constexpr int NA = 5, NB = 6, SLOT = 16384, KVBUF = 24576;
constexpr int NA2 = 8;
constexpr int OFF_B = 0, OFF_A = NB * SLOT, OFF_KV = OFF_A + NA * SLOT, OFF_BAR = OFF_KV + 2 * KVBUF;
constexpr int OFF_GST = OFF_BAR + 512;
constexpr int OFF_GIN = OFF_BAR + 1024;
constexpr int SMEM_BYTES = OFF_BAR + 1536 + 1024;
constexpr uint32_t TIMEOUT = 1u << 28;
#define WAIT_HINT_NS 20000u
#define PFAT 8
constexpr int FS = 8;

constexpr int BAR_FULLA = 0, BAR_EMPTYA = BAR_FULLA + NA2, BAR_FULLB = BAR_EMPTYA + NA2, BAR_EMPTYB = BAR_FULLB + NB,
              BAR_KVFULL = BAR_EMPTYB + NB, BAR_KVEMPTY = BAR_KVFULL + 2, BAR_STG = BAR_KVEMPTY + 2, BAR_PIN = BAR_STG + 2, BAR_GATE = BAR_PIN + 1, BAR_STE = BAR_GATE + 2, BAR_ATTDONE = BAR_STE + 2, BAR_GIN = BAR_ATTDONE + 1;

__device__ __align__(1024) uint8_t g_kv[32 * SEQ * 64];
__device__ __align__(1024) __nv_bfloat16 g_ho[SEQ * KHO];
__device__ __align__(1024) uint8_t g_part[128 * 16384];
__device__ __align__(128) float g_gate[SEQ];
__device__ unsigned g_flag_kv[128 * FS], g_flag_h[128 * FS], g_flag_o[128 * FS], g_flag_g[16 * FS], g_flag_p[128 * FS], g_flag_e[128 * FS];
__device__ unsigned g_epoch, g_done;
#define TR(i) do {} while (0)

struct Params {
  CUtensorMap tmX, tmWqkv, tmW1a, tmW1b, tmW2, tmWo, tmHO, tmHOs, tmOs, tmOut;
  const __nv_bfloat16* x;
  const __nv_bfloat16* gate_w;
  const __nv_bfloat16* w1;
  const __nv_bfloat16* w2;
  const __nv_bfloat16* wo;
  __nv_bfloat16* out;
};

DEVI uint32_t smem_u32(const void* p) { return (uint32_t)__cvta_generic_to_shared(p); }
DEVI uint32_t clk32() { uint32_t c; asm volatile("mov.u32 %0, %%clock;" : "=r"(c)); return c; }
DEVI void mbar_init(uint32_t bar, uint32_t cnt) { asm volatile("mbarrier.init.shared::cta.b64 [%0], %1;" ::"r"(bar), "r"(cnt)); }
DEVI void mbar_expect_tx(uint32_t bar, uint32_t bytes) { asm volatile("mbarrier.arrive.expect_tx.shared::cta.b64 _, [%0], %1;" ::"r"(bar), "r"(bytes) : "memory"); }
DEVI void mbar_arrive(uint32_t bar) { asm volatile("mbarrier.arrive.shared::cta.b64 _, [%0];" ::"r"(bar) : "memory"); }
DEVI void mbar_arrive_n(uint32_t bar, uint32_t n) { asm volatile("mbarrier.arrive.shared::cta.b64 _, [%0], %1;" ::"r"(bar), "r"(n) : "memory"); }
DEVI void mbar_arrive_cluster(uint32_t bar, uint32_t cta) {
  asm volatile("{ .reg .b32 ra; mapa.shared::cluster.u32 ra, %0, %1; mbarrier.arrive.shared::cluster.b64 _, [ra]; }" ::"r"(bar), "r"(cta) : "memory");
}
DEVI void mbar_wait(uint32_t bar, uint32_t parity, uint32_t t0) {
  asm volatile("{ .reg .pred p; .reg .u32 c;\n"
               "mbarrier.try_wait.parity.shared::cta.b64 p, [%0], %1;\n"
               "@p bra DONE_%=;\n"
               "WAIT_%=:\n"
               "mbarrier.try_wait.parity.shared::cta.b64 p, [%0], %1, %4;\n"
               "@p bra DONE_%=;\n"
               "mov.u32 c, %%clock; sub.u32 c, c, %2; setp.lt.u32 p, c, %3;\n"
               "@p bra WAIT_%=;\n"
               "DONE_%=: }" ::"r"(bar), "r"(parity), "r"(t0), "n"(TIMEOUT), "r"(WAIT_HINT_NS) : "memory");
}
DEVI unsigned ld_relaxed(const unsigned* p) { unsigned v; asm volatile("ld.relaxed.gpu.global.u32 %0, [%1];" : "=r"(v) : "l"(p) : "memory"); return v; }
DEVI void flag_wait(const unsigned* p, unsigned target, uint32_t t0) {
  while ((int)(ld_relaxed(p) - target) < 0) { if (clk32() - t0 > TIMEOUT) break; }
}
DEVI void flag_add(unsigned* p) { asm volatile("red.relaxed.gpu.global.add.u32 [%0], 1;" ::"l"(p) : "memory"); }
DEVI void fence_async_smem() { asm volatile("fence.proxy.async.shared::cta;" ::: "memory"); }
DEVI void fence_async_global() { asm volatile("fence.proxy.async.global;" ::: "memory"); }
DEVI void tma_load_2d(uint32_t dst, const CUtensorMap* m, int c0, int c1, uint32_t bar) {
  asm volatile("cp.async.bulk.tensor.2d.shared::cluster.global.mbarrier::complete_tx::bytes [%0], [%1, {%3, %4}], [%2];" ::"r"(dst), "l"(m), "r"(bar), "r"(c0), "r"(c1) : "memory");
}
DEVI void tma_load_3d(uint32_t dst, const CUtensorMap* m, int c0, int c1, int c2, uint32_t bar) {
  asm volatile("cp.async.bulk.tensor.3d.shared::cluster.global.mbarrier::complete_tx::bytes [%0], [%1, {%3, %4, %5}], [%2];"
               ::"r"(dst), "l"(m), "r"(bar), "r"(c0), "r"(c1), "r"(c2) : "memory");
}
DEVI void tma_load_3d_mc(uint32_t dst, const CUtensorMap* m, int c0, int c1, int c2, uint32_t bar) {
  asm volatile("cp.async.bulk.tensor.3d.shared::cluster.global.mbarrier::complete_tx::bytes.multicast::cluster [%0], [%1, {%3, %4, %5}], [%2], %6;"
               ::"r"(dst), "l"(m), "r"(bar), "r"(c0), "r"(c1), "r"(c2), "h"((uint16_t)3) : "memory");
}
DEVI void tma_load_4d_mc(uint32_t dst, const CUtensorMap* m, int c0, int c1, int c2, int c3, uint32_t bar) {
  asm volatile("cp.async.bulk.tensor.4d.shared::cluster.global.mbarrier::complete_tx::bytes.multicast::cluster [%0], [%1, {%3, %4, %5, %6}], [%2], %7;"
               ::"r"(dst), "l"(m), "r"(bar), "r"(c0), "r"(c1), "r"(c2), "r"(c3), "h"((uint16_t)3) : "memory");
}
DEVI void tma_store_2d(const CUtensorMap* m, int c0, int c1, uint32_t src) {
  asm volatile("cp.async.bulk.tensor.2d.global.shared::cta.bulk_group [%0, {%1, %2}], [%3];" ::"l"(m), "r"(c0), "r"(c1), "r"(src) : "memory");
}
DEVI void bulk_store(void* dst, uint32_t src, uint32_t bytes) {
  asm volatile("cp.async.bulk.global.shared::cta.bulk_group [%0], [%1], %2;" ::"l"(dst), "r"(src), "r"(bytes) : "memory");
}
DEVI void bulk_load(uint32_t dst, const void* src, uint32_t bytes, uint32_t bar) {
  asm volatile("cp.async.bulk.shared::cluster.global.mbarrier::complete_tx::bytes [%0], [%1], %2, [%3];" ::"r"(dst), "l"(src), "r"(bytes), "r"(bar) : "memory");
}
DEVI void bulk_commit() { asm volatile("cp.async.bulk.commit_group;" ::: "memory"); }
DEVI void bulk_wait_all() { asm volatile("cp.async.bulk.wait_group 0;" ::: "memory"); }
DEVI void l2_prefetch(const void* p, uint32_t bytes) { asm volatile("cp.async.bulk.prefetch.L2.global [%0], %1;" ::"l"(p), "r"(bytes) : "memory"); }
DEVI void cluster_arrive() { asm volatile("barrier.cluster.arrive.relaxed.aligned;" ::: "memory"); }
DEVI void cluster_wait() { asm volatile("barrier.cluster.wait.aligned;" ::: "memory"); }
template <int ID> DEVI void named_bar(int n) { asm volatile("bar.sync %0, %1;" ::"n"(ID), "r"(n) : "memory"); }
DEVI void wg_bar(int wg) { if (wg == 0) named_bar<1>(128); else named_bar<2>(128); }
DEVI void wgmma_fence() { asm volatile("wgmma.fence.sync.aligned;" ::: "memory"); }
DEVI void wgmma_commit() { asm volatile("wgmma.commit_group.sync.aligned;" ::: "memory"); }
template <int N> DEVI void wgmma_wait() { asm volatile("wgmma.wait_group.sync.aligned %0;" ::"n"(N) : "memory"); }
template <uint32_t LBO> DEVI uint64_t desc_sw128(uint32_t a16) {
  return ((uint64_t)(0x40000000u | (1024 >> 4)) << 32) | (a16 + ((LBO >> 4) << 16));
}
DEVI uint64_t desc_sw64(uint32_t a16) {
  return ((uint64_t)(0x80000000u | (512 >> 4)) << 32) | (a16 + ((512 >> 4) << 16));
}
DEVI uint32_t pack_bf16(float lo, float hi) { uint32_t r; asm("cvt.rn.bf16x2.f32 %0, %1, %2;" : "=r"(r) : "f"(hi), "f"(lo)); return r; }
DEVI void stsm_x4(uint32_t addr, uint32_t r0, uint32_t r1, uint32_t r2, uint32_t r3) {
  asm volatile("stmatrix.sync.aligned.m8n8.x4.shared.b16 [%0], {%1, %2, %3, %4};" ::"r"(addr), "r"(r0), "r"(r1), "r"(r2), "r"(r3) : "memory");
}
DEVI void sts128(uint32_t addr, uint32_t r0, uint32_t r1, uint32_t r2, uint32_t r3) {
  asm volatile("st.shared.v4.b32 [%0], {%1, %2, %3, %4};" ::"r"(addr), "r"(r0), "r"(r1), "r"(r2), "r"(r3) : "memory");
}
DEVI uint4 lds128(uint32_t addr) {
  uint4 v; asm volatile("ld.shared.v4.b32 {%0, %1, %2, %3}, [%4];" : "=r"(v.x), "=r"(v.y), "=r"(v.z), "=r"(v.w) : "r"(addr) : "memory"); return v;
}
DEVI float ex2(float x) { float y; asm("ex2.approx.ftz.f32 %0, %1;" : "=f"(y) : "f"(x)); return y; }

DEVI void wgmma_ss_n64(float (&d)[32], uint64_t da, uint64_t db) {
  asm volatile("wgmma.mma_async.sync.aligned.m64n64k16.f32.bf16.bf16 {%0, %1, %2, %3, %4, %5, %6, %7, %8, %9, %10, %11, %12, %13, %14, %15, %16, %17, %18, %19, %20, %21, %22, %23, %24, %25, %26, %27, %28, %29, %30, %31}, %32, %33, 1, 1, 1, 0, 1;"
    : "+f"(d[0]), "+f"(d[1]), "+f"(d[2]), "+f"(d[3]), "+f"(d[4]), "+f"(d[5]), "+f"(d[6]), "+f"(d[7]), "+f"(d[8]), "+f"(d[9]), "+f"(d[10]), "+f"(d[11]), "+f"(d[12]), "+f"(d[13]), "+f"(d[14]), "+f"(d[15]), "+f"(d[16]), "+f"(d[17]), "+f"(d[18]), "+f"(d[19]), "+f"(d[20]), "+f"(d[21]), "+f"(d[22]), "+f"(d[23]), "+f"(d[24]), "+f"(d[25]), "+f"(d[26]), "+f"(d[27]), "+f"(d[28]), "+f"(d[29]), "+f"(d[30]), "+f"(d[31])
    : "l"(da), "l"(db));
}
DEVI void wgmma_ss_n128(float (&d)[64], uint64_t da, uint64_t db) {
  asm volatile("wgmma.mma_async.sync.aligned.m64n128k16.f32.bf16.bf16 {%0, %1, %2, %3, %4, %5, %6, %7, %8, %9, %10, %11, %12, %13, %14, %15, %16, %17, %18, %19, %20, %21, %22, %23, %24, %25, %26, %27, %28, %29, %30, %31, %32, %33, %34, %35, %36, %37, %38, %39, %40, %41, %42, %43, %44, %45, %46, %47, %48, %49, %50, %51, %52, %53, %54, %55, %56, %57, %58, %59, %60, %61, %62, %63}, %64, %65, 1, 1, 1, 0, 1;"
    : "+f"(d[0]), "+f"(d[1]), "+f"(d[2]), "+f"(d[3]), "+f"(d[4]), "+f"(d[5]), "+f"(d[6]), "+f"(d[7]), "+f"(d[8]), "+f"(d[9]), "+f"(d[10]), "+f"(d[11]), "+f"(d[12]), "+f"(d[13]), "+f"(d[14]), "+f"(d[15]), "+f"(d[16]), "+f"(d[17]), "+f"(d[18]), "+f"(d[19]), "+f"(d[20]), "+f"(d[21]), "+f"(d[22]), "+f"(d[23]), "+f"(d[24]), "+f"(d[25]), "+f"(d[26]), "+f"(d[27]), "+f"(d[28]), "+f"(d[29]), "+f"(d[30]), "+f"(d[31]), "+f"(d[32]), "+f"(d[33]), "+f"(d[34]), "+f"(d[35]), "+f"(d[36]), "+f"(d[37]), "+f"(d[38]), "+f"(d[39]), "+f"(d[40]), "+f"(d[41]), "+f"(d[42]), "+f"(d[43]), "+f"(d[44]), "+f"(d[45]), "+f"(d[46]), "+f"(d[47]), "+f"(d[48]), "+f"(d[49]), "+f"(d[50]), "+f"(d[51]), "+f"(d[52]), "+f"(d[53]), "+f"(d[54]), "+f"(d[55]), "+f"(d[56]), "+f"(d[57]), "+f"(d[58]), "+f"(d[59]), "+f"(d[60]), "+f"(d[61]), "+f"(d[62]), "+f"(d[63])
    : "l"(da), "l"(db));
}
DEVI void wgmma_ss_n192(float (&d)[96], uint64_t da, uint64_t db) {
  asm volatile("wgmma.mma_async.sync.aligned.m64n192k16.f32.bf16.bf16 {%0, %1, %2, %3, %4, %5, %6, %7, %8, %9, %10, %11, %12, %13, %14, %15, %16, %17, %18, %19, %20, %21, %22, %23, %24, %25, %26, %27, %28, %29, %30, %31, %32, %33, %34, %35, %36, %37, %38, %39, %40, %41, %42, %43, %44, %45, %46, %47, %48, %49, %50, %51, %52, %53, %54, %55, %56, %57, %58, %59, %60, %61, %62, %63, %64, %65, %66, %67, %68, %69, %70, %71, %72, %73, %74, %75, %76, %77, %78, %79, %80, %81, %82, %83, %84, %85, %86, %87, %88, %89, %90, %91, %92, %93, %94, %95}, %96, %97, 1, 1, 1, 0, 1;"
    : "+f"(d[0]), "+f"(d[1]), "+f"(d[2]), "+f"(d[3]), "+f"(d[4]), "+f"(d[5]), "+f"(d[6]), "+f"(d[7]), "+f"(d[8]), "+f"(d[9]), "+f"(d[10]), "+f"(d[11]), "+f"(d[12]), "+f"(d[13]), "+f"(d[14]), "+f"(d[15]), "+f"(d[16]), "+f"(d[17]), "+f"(d[18]), "+f"(d[19]), "+f"(d[20]), "+f"(d[21]), "+f"(d[22]), "+f"(d[23]), "+f"(d[24]), "+f"(d[25]), "+f"(d[26]), "+f"(d[27]), "+f"(d[28]), "+f"(d[29]), "+f"(d[30]), "+f"(d[31]), "+f"(d[32]), "+f"(d[33]), "+f"(d[34]), "+f"(d[35]), "+f"(d[36]), "+f"(d[37]), "+f"(d[38]), "+f"(d[39]), "+f"(d[40]), "+f"(d[41]), "+f"(d[42]), "+f"(d[43]), "+f"(d[44]), "+f"(d[45]), "+f"(d[46]), "+f"(d[47]), "+f"(d[48]), "+f"(d[49]), "+f"(d[50]), "+f"(d[51]), "+f"(d[52]), "+f"(d[53]), "+f"(d[54]), "+f"(d[55]), "+f"(d[56]), "+f"(d[57]), "+f"(d[58]), "+f"(d[59]), "+f"(d[60]), "+f"(d[61]), "+f"(d[62]), "+f"(d[63]), "+f"(d[64]), "+f"(d[65]), "+f"(d[66]), "+f"(d[67]), "+f"(d[68]), "+f"(d[69]), "+f"(d[70]), "+f"(d[71]), "+f"(d[72]), "+f"(d[73]), "+f"(d[74]), "+f"(d[75]), "+f"(d[76]), "+f"(d[77]), "+f"(d[78]), "+f"(d[79]), "+f"(d[80]), "+f"(d[81]), "+f"(d[82]), "+f"(d[83]), "+f"(d[84]), "+f"(d[85]), "+f"(d[86]), "+f"(d[87]), "+f"(d[88]), "+f"(d[89]), "+f"(d[90]), "+f"(d[91]), "+f"(d[92]), "+f"(d[93]), "+f"(d[94]), "+f"(d[95])
    : "l"(da), "l"(db));
}
DEVI void wgmma_ss_n256(float (&d)[128], uint64_t da, uint64_t db) {
  asm volatile("wgmma.mma_async.sync.aligned.m64n256k16.f32.bf16.bf16 {%0, %1, %2, %3, %4, %5, %6, %7, %8, %9, %10, %11, %12, %13, %14, %15, %16, %17, %18, %19, %20, %21, %22, %23, %24, %25, %26, %27, %28, %29, %30, %31, %32, %33, %34, %35, %36, %37, %38, %39, %40, %41, %42, %43, %44, %45, %46, %47, %48, %49, %50, %51, %52, %53, %54, %55, %56, %57, %58, %59, %60, %61, %62, %63, %64, %65, %66, %67, %68, %69, %70, %71, %72, %73, %74, %75, %76, %77, %78, %79, %80, %81, %82, %83, %84, %85, %86, %87, %88, %89, %90, %91, %92, %93, %94, %95, %96, %97, %98, %99, %100, %101, %102, %103, %104, %105, %106, %107, %108, %109, %110, %111, %112, %113, %114, %115, %116, %117, %118, %119, %120, %121, %122, %123, %124, %125, %126, %127}, %128, %129, 1, 1, 1, 0, 1;"
    : "+f"(d[0]), "+f"(d[1]), "+f"(d[2]), "+f"(d[3]), "+f"(d[4]), "+f"(d[5]), "+f"(d[6]), "+f"(d[7]), "+f"(d[8]), "+f"(d[9]), "+f"(d[10]), "+f"(d[11]), "+f"(d[12]), "+f"(d[13]), "+f"(d[14]), "+f"(d[15]), "+f"(d[16]), "+f"(d[17]), "+f"(d[18]), "+f"(d[19]), "+f"(d[20]), "+f"(d[21]), "+f"(d[22]), "+f"(d[23]), "+f"(d[24]), "+f"(d[25]), "+f"(d[26]), "+f"(d[27]), "+f"(d[28]), "+f"(d[29]), "+f"(d[30]), "+f"(d[31]), "+f"(d[32]), "+f"(d[33]), "+f"(d[34]), "+f"(d[35]), "+f"(d[36]), "+f"(d[37]), "+f"(d[38]), "+f"(d[39]), "+f"(d[40]), "+f"(d[41]), "+f"(d[42]), "+f"(d[43]), "+f"(d[44]), "+f"(d[45]), "+f"(d[46]), "+f"(d[47]), "+f"(d[48]), "+f"(d[49]), "+f"(d[50]), "+f"(d[51]), "+f"(d[52]), "+f"(d[53]), "+f"(d[54]), "+f"(d[55]), "+f"(d[56]), "+f"(d[57]), "+f"(d[58]), "+f"(d[59]), "+f"(d[60]), "+f"(d[61]), "+f"(d[62]), "+f"(d[63]), "+f"(d[64]), "+f"(d[65]), "+f"(d[66]), "+f"(d[67]), "+f"(d[68]), "+f"(d[69]), "+f"(d[70]), "+f"(d[71]), "+f"(d[72]), "+f"(d[73]), "+f"(d[74]), "+f"(d[75]), "+f"(d[76]), "+f"(d[77]), "+f"(d[78]), "+f"(d[79]), "+f"(d[80]), "+f"(d[81]), "+f"(d[82]), "+f"(d[83]), "+f"(d[84]), "+f"(d[85]), "+f"(d[86]), "+f"(d[87]), "+f"(d[88]), "+f"(d[89]), "+f"(d[90]), "+f"(d[91]), "+f"(d[92]), "+f"(d[93]), "+f"(d[94]), "+f"(d[95]), "+f"(d[96]), "+f"(d[97]), "+f"(d[98]), "+f"(d[99]), "+f"(d[100]), "+f"(d[101]), "+f"(d[102]), "+f"(d[103]), "+f"(d[104]), "+f"(d[105]), "+f"(d[106]), "+f"(d[107]), "+f"(d[108]), "+f"(d[109]), "+f"(d[110]), "+f"(d[111]), "+f"(d[112]), "+f"(d[113]), "+f"(d[114]), "+f"(d[115]), "+f"(d[116]), "+f"(d[117]), "+f"(d[118]), "+f"(d[119]), "+f"(d[120]), "+f"(d[121]), "+f"(d[122]), "+f"(d[123]), "+f"(d[124]), "+f"(d[125]), "+f"(d[126]), "+f"(d[127])
    : "l"(da), "l"(db));
}
DEVI void wgmma_qk64(float (&d)[32], uint32_t a0, uint32_t a1, uint32_t a2, uint32_t a3, uint64_t db) {
  asm volatile("wgmma.mma_async.sync.aligned.m64n64k16.f32.bf16.bf16 {%0, %1, %2, %3, %4, %5, %6, %7, %8, %9, %10, %11, %12, %13, %14, %15, %16, %17, %18, %19, %20, %21, %22, %23, %24, %25, %26, %27, %28, %29, %30, %31}, {%32, %33, %34, %35}, %36, 0, 1, 1, 0;"
    : "=f"(d[0]), "=f"(d[1]), "=f"(d[2]), "=f"(d[3]), "=f"(d[4]), "=f"(d[5]), "=f"(d[6]), "=f"(d[7]), "=f"(d[8]), "=f"(d[9]), "=f"(d[10]), "=f"(d[11]), "=f"(d[12]), "=f"(d[13]), "=f"(d[14]), "=f"(d[15]), "=f"(d[16]), "=f"(d[17]), "=f"(d[18]), "=f"(d[19]), "=f"(d[20]), "=f"(d[21]), "=f"(d[22]), "=f"(d[23]), "=f"(d[24]), "=f"(d[25]), "=f"(d[26]), "=f"(d[27]), "=f"(d[28]), "=f"(d[29]), "=f"(d[30]), "=f"(d[31])
    : "r"(a0), "r"(a1), "r"(a2), "r"(a3), "l"(db));
}
DEVI void wgmma_qk128(float (&d)[64], uint32_t a0, uint32_t a1, uint32_t a2, uint32_t a3, uint64_t db) {
  asm volatile("wgmma.mma_async.sync.aligned.m64n128k16.f32.bf16.bf16 {%0, %1, %2, %3, %4, %5, %6, %7, %8, %9, %10, %11, %12, %13, %14, %15, %16, %17, %18, %19, %20, %21, %22, %23, %24, %25, %26, %27, %28, %29, %30, %31, %32, %33, %34, %35, %36, %37, %38, %39, %40, %41, %42, %43, %44, %45, %46, %47, %48, %49, %50, %51, %52, %53, %54, %55, %56, %57, %58, %59, %60, %61, %62, %63}, {%64, %65, %66, %67}, %68, 0, 1, 1, 0;"
    : "=f"(d[0]), "=f"(d[1]), "=f"(d[2]), "=f"(d[3]), "=f"(d[4]), "=f"(d[5]), "=f"(d[6]), "=f"(d[7]), "=f"(d[8]), "=f"(d[9]), "=f"(d[10]), "=f"(d[11]), "=f"(d[12]), "=f"(d[13]), "=f"(d[14]), "=f"(d[15]), "=f"(d[16]), "=f"(d[17]), "=f"(d[18]), "=f"(d[19]), "=f"(d[20]), "=f"(d[21]), "=f"(d[22]), "=f"(d[23]), "=f"(d[24]), "=f"(d[25]), "=f"(d[26]), "=f"(d[27]), "=f"(d[28]), "=f"(d[29]), "=f"(d[30]), "=f"(d[31]), "=f"(d[32]), "=f"(d[33]), "=f"(d[34]), "=f"(d[35]), "=f"(d[36]), "=f"(d[37]), "=f"(d[38]), "=f"(d[39]), "=f"(d[40]), "=f"(d[41]), "=f"(d[42]), "=f"(d[43]), "=f"(d[44]), "=f"(d[45]), "=f"(d[46]), "=f"(d[47]), "=f"(d[48]), "=f"(d[49]), "=f"(d[50]), "=f"(d[51]), "=f"(d[52]), "=f"(d[53]), "=f"(d[54]), "=f"(d[55]), "=f"(d[56]), "=f"(d[57]), "=f"(d[58]), "=f"(d[59]), "=f"(d[60]), "=f"(d[61]), "=f"(d[62]), "=f"(d[63])
    : "r"(a0), "r"(a1), "r"(a2), "r"(a3), "l"(db));
}
DEVI void wgmma_pv(float (&d)[8], uint32_t a0, uint32_t a1, uint32_t a2, uint32_t a3, uint64_t db) {
  asm volatile("wgmma.mma_async.sync.aligned.m64n16k16.f32.bf16.bf16 {%0, %1, %2, %3, %4, %5, %6, %7}, {%8, %9, %10, %11}, %12, 1, 1, 1, 1;"
    : "+f"(d[0]), "+f"(d[1]), "+f"(d[2]), "+f"(d[3]), "+f"(d[4]), "+f"(d[5]), "+f"(d[6]), "+f"(d[7])
    : "r"(a0), "r"(a1), "r"(a2), "r"(a3), "l"(db));
}
DEVI void wgmma_pv0(float (&d)[8], uint32_t a0, uint32_t a1, uint32_t a2, uint32_t a3, uint64_t db) {
  asm volatile("wgmma.mma_async.sync.aligned.m64n16k16.f32.bf16.bf16 {%0, %1, %2, %3, %4, %5, %6, %7}, {%8, %9, %10, %11}, %12, 0, 1, 1, 1;"
    : "=f"(d[0]), "=f"(d[1]), "=f"(d[2]), "=f"(d[3]), "=f"(d[4]), "=f"(d[5]), "=f"(d[6]), "=f"(d[7])
    : "r"(a0), "r"(a1), "r"(a2), "r"(a3), "l"(db));
}

template <int N> DEVI void wgmma_ss(float (&d)[N / 2], uint64_t da, uint64_t db) {
  if constexpr (N == 64) wgmma_ss_n64(d, da, db);
  else if constexpr (N == 128) wgmma_ss_n128(d, da, db);
  else if constexpr (N == 192) wgmma_ss_n192(d, da, db);
  else wgmma_ss_n256(d, da, db);
}

DEVI int oh_chunk(int j, int i, int& need) {
  if (j & 1) {
    if (i >= 3 && i < 7) { need = 16 + 2 * (i - 3); return 24 + (i - 3); }
    if (i >= 7) i -= 4;
  }
  const int g = i / 3, o = (j + 2 * g) & 7;
  need = o;
  return 3 * o + (i - 3 * g);
}

DEVI int next_a_slot(int e, int ai) {
  e++;
  return e < 16 ? (ai == NA - 1 ? 0 : ai + 1) : e < 32 ? 1 + (e & 3) : (e - 27) & 7;
}

struct Ctx {
  uint32_t sbase, bars, peer, t0, a16, b16;
  int wg, lane;
  int ai, bi; uint32_t aph, bph;
  int brem, ae;
  int pa, pb;
};

DEVI void release_prev(Ctx& c) {
  if (c.pb >= 0) {
    if (c.lane == 0) mbar_arrive(c.bars + 8 * (BAR_EMPTYB + c.pb));
    if (c.lane == 1) mbar_arrive_cluster(c.bars + 8 * (BAR_EMPTYB + c.pb), c.peer);
  }
  if (c.pa >= 0 && c.lane == 2) mbar_arrive(c.bars + 8 * (BAR_EMPTYA + c.pa));
}

DEVI void gemm_wait(Ctx& c) {
  asm volatile("{ .reg .pred p, q; .reg .u32 c;\n"
               "WAIT_%=:\n"
               "mbarrier.try_wait.parity.shared::cta.b64 p, [%0], %1;\n"
               "mbarrier.try_wait.parity.shared::cta.b64 q, [%2], %3;\n"
               "and.pred p, p, q;\n"
               "@p bra DONE_%=;\n"
               "mov.u32 c, %%clock; sub.u32 c, c, %4; setp.lt.u32 p, c, %5;\n"
               "@p bra WAIT_%=;\n"
               "DONE_%=: }" ::"r"(c.bars + 8 * (BAR_FULLA + c.ai)), "r"((c.aph >> c.ai) & 1), "r"(c.bars + 8 * (BAR_FULLB + c.bi)), "r"(c.bph), "r"(c.t0), "n"(TIMEOUT) : "memory");
}
template <int N>
DEVI void gemm_group(float (&acc)[N / 2], Ctx& c, int g, int& npa, int& npb) {
  const uint32_t a16 = c.a16 + c.ai * (SLOT >> 4);
  const uint32_t b16 = c.b16 + c.bi * (SLOT >> 4);
  bool adv;
  if constexpr (N >= 192) {
    const uint32_t a2 = a16 + (g & 1) * 4;
    wgmma_ss<N>(acc, desc_sw128<16>(a2), desc_sw128<2048>(b16));
    wgmma_ss<N>(acc, desc_sw128<16>(a2 + 2), desc_sw128<2048>(b16 + 512));
    adv = g & 1;
  } else {
#pragma unroll
    for (int s = 0; s < 4; s++) wgmma_ss<N>(acc, desc_sw128<16>(a16 + s * 2), desc_sw128<4096>(b16 + (s >> 1) * 512 + (s & 1) * 128));
    adv = true;
  }
  wgmma_commit();
  npb = c.brem > 0 ? c.bi : -1;
  c.brem--;
  if (++c.bi == NB) { c.bi = 0; c.bph ^= 1; }
  npa = -1;
  if (adv) { npa = c.ai; c.aph ^= 1u << c.ai; c.ai = next_a_slot(c.ae, c.ai); c.ae++; }
}

template <int N>
DEVI void bare_groups(float (&acc)[N / 2], Ctx& c, int g0, int g1) {
  for (int g = g0; g < g1; g++) {
    int npa, npb;
    gemm_wait(c);
    wgmma_fence();
    gemm_group<N>(acc, c, g, npa, npb);
    wgmma_wait<1>();
    release_prev(c);
    c.pa = npa; c.pb = npb;
  }
}
DEVI void drain(Ctx& c) {
  wgmma_wait<0>();
  release_prev(c);
  c.pa = c.pb = -1;
}

constexpr float SC = 0.25f * 1.4426950408889634f;

#define ONCE _Pragma("unroll 1") for (unsigned once_ = 0; once_ < gridDim.y; once_++)

struct Attn {
  uint32_t q[4][4];
  uint32_t nm[4];
  float g0, g1;
  int cmin;
  int rowc;
};

template <int O0, int NS>
DEVI void kill32(float (&S)[NS]) {
#pragma unroll
  for (int i = 0; i < 32; i++) S[O0 + i] = __int_as_float(0xff800000);
}
DEVI void row_max(const float (&S)[64], float& x0, float& x1) {
#pragma unroll
  for (int n = 0; n < 16; n++) {
    x0 = fmaxf(x0, fmaxf(S[4 * n], S[4 * n + 1])); x1 = fmaxf(x1, fmaxf(S[4 * n + 2], S[4 * n + 3]));
  }
}
template <int K, bool PRE = false>
DEVI void exp8(const float (&S)[64], uint32_t (&P)[4], float n0, float n1, float (&l)[4]) {
  float e[8];
#pragma unroll
  for (int i = 0; i < 8; i++) e[i] = ex2(PRE ? S[8 * K + i] : fmaf(S[8 * K + i], SC, (i & 2) ? n1 : n0));
  l[0] += e[0]; l[1] += e[1]; l[2] += e[2]; l[3] += e[3];
  l[0] += e[4]; l[1] += e[5]; l[2] += e[6]; l[3] += e[7];
#pragma unroll
  for (int i = 0; i < 4; i++) P[i] = pack_bf16(e[2 * i], e[2 * i + 1]) | (__float_as_uint(l[i]) & blockIdx.y);
}
DEVI void merge_fl(float (&S)[64], const float (&F)[32], int rowc) {
#pragma unroll
  for (int n = 0; n < 8; n++) {
    if (n * 8 > rowc) S[32 + 4 * n] = F[4 * n];
    if (n * 8 + 1 > rowc) S[32 + 4 * n + 1] = F[4 * n + 1];
    if (n * 8 > rowc + 8) S[32 + 4 * n + 2] = F[4 * n + 2];
    if (n * 8 + 1 > rowc + 8) S[32 + 4 * n + 3] = F[4 * n + 3];
  }
}
DEVI bool wg_any(int wg, bool v) {
  uint32_t r;
  if (wg == 0) asm volatile("{ .reg .pred p, q; setp.ne.u32 p, %1, 0; bar.red.or.pred q, 1, 128, p; selp.u32 %0, 1, 0, q; }" : "=r"(r) : "r"((uint32_t)v) : "memory");
  else asm volatile("{ .reg .pred p, q; setp.ne.u32 p, %1, 0; bar.red.or.pred q, 2, 128, p; selp.u32 %0, 1, 0, q; }" : "=r"(r) : "r"((uint32_t)v) : "memory");
  return r != 0;
}

DEVI void qk_a(float (&S)[64], float (&F)[32], const uint32_t (&q)[4], uint32_t kb) {
  wgmma_fence();
  wgmma_qk128(S, q[0], q[1], q[2], q[3], desc_sw64(kb + 3 * 256));
  wgmma_qk64(F, q[0], q[1], q[2], q[3], desc_sw64(kb));
}
DEVI void fix_a(float (&S)[64], float (&F)[32], const Attn& at) {
  if (at.cmin > 0) { kill32<0>(F); if (at.cmin > 3) kill32<0>(S); }
  merge_fl(S, F, at.rowc);
}
DEVI void fix_b(float (&S)[64], const Attn& at) {
  if (at.cmin > 1) { kill32<0>(S); if (at.cmin > 2) kill32<32>(S); }
}
struct GSlot { uint32_t a16, b16, fa, fb, ea, eb, pa, pb; bool relb; };
DEVI GSlot g_slot(const Ctx& c, int gi) {
  GSlot g;
  const int as = 1 + (gi & 3), e = 32 + gi, q = (e * 43) >> 8, bs = e - 6 * q;
  g.a16 = c.a16 + as * (SLOT >> 4); g.b16 = c.b16 + bs * (SLOT >> 4);
  g.fa = c.bars + 8 * (BAR_FULLA + as); g.fb = c.bars + 8 * (BAR_FULLB + bs);
  g.ea = c.bars + 8 * (BAR_EMPTYA + as); g.eb = c.bars + 8 * (BAR_EMPTYB + bs);
  g.pa = (1 + (gi >> 2)) & 1; g.pb = q & 1;
  g.relb = gi < c.brem;
  return g;
}
DEVI void g_wait(const Ctx& c, const GSlot& g) {
  asm volatile("{ .reg .pred p, q; .reg .u32 c;\n"
               "WAIT_%=:\n"
               "mbarrier.try_wait.parity.shared::cta.b64 p, [%0], %1;\n"
               "mbarrier.try_wait.parity.shared::cta.b64 q, [%2], %3;\n"
               "and.pred p, p, q;\n"
               "@p bra DONE_%=;\n"
               "mov.u32 c, %%clock; sub.u32 c, c, %4; setp.lt.u32 p, c, %5;\n"
               "@p bra WAIT_%=;\n"
               "DONE_%=: }" ::"r"(g.fa), "r"(g.pa), "r"(g.fb), "r"(g.pb), "r"(c.t0), "n"(TIMEOUT) : "memory");
}
DEVI void g_release(const Ctx& c, const GSlot& g) {
  if (c.lane == 2) mbar_arrive(g.ea);
  if (c.lane == 0 && g.relb) mbar_arrive(g.eb);
  if (c.lane == 1 && g.relb) mbar_arrive_cluster(g.eb, c.peer);
}
template <int ST> DEVI void g_step(float (&acc)[64], uint32_t a16, uint32_t b16, uint32_t dep) {
  a16 += dep & blockIdx.y;
  wgmma_ss<128>(acc, desc_sw128<16>(a16 + ST * 2), desc_sw128<4096>(b16 + (ST >> 1) * 512 + (ST & 1) * 128));
}
template <int NH>
DEVI void exp_all(float (&acc)[64], Ctx& c, const float (&S)[64], uint32_t (&P)[8][4], float n0, float n1, float (&l)[4],
                  uint32_t a0, uint32_t b0, uint32_t a1, uint32_t b1) {
  if (NH > 0) { wgmma_fence(); g_step<0>(acc, a0, b0, 0u); }
  exp8<0>(S, P[0], n0, n1, l); if (NH > 1) g_step<1>(acc, a0, b0, P[0][0]);
  exp8<1>(S, P[1], n0, n1, l); if (NH > 1) g_step<2>(acc, a0, b0, P[1][0]); else if (NH > 0) g_step<1>(acc, a0, b0, P[1][0]);
  exp8<2>(S, P[2], n0, n1, l); if (NH > 1) g_step<3>(acc, a0, b0, P[2][0]);
  exp8<3>(S, P[3], n0, n1, l); if (NH > 1) g_step<0>(acc, a1, b1, P[3][0]); else if (NH > 0) g_step<2>(acc, a0, b0, P[3][0]);
  exp8<4>(S, P[4], n0, n1, l); if (NH > 1) g_step<1>(acc, a1, b1, P[4][0]);
  exp8<5>(S, P[5], n0, n1, l); if (NH > 1) g_step<2>(acc, a1, b1, P[5][0]); else if (NH > 0) g_step<3>(acc, a0, b0, P[5][0]);
  exp8<6>(S, P[6], n0, n1, l); if (NH > 1) g_step<3>(acc, a1, b1, P[6][0]);
  exp8<7>(S, P[7], n0, n1, l);
}

template <bool FUSE>
DEVI void head_pass(float (&acc)[64], Ctx& c, const Attn& at, int h, uint32_t kb, float n0, float n1, float (&O)[8], float& l0, float& l1) {
  float S[64], l[4] = {0.f, 0.f, 0.f, 0.f};
  uint32_t P[8][4];
  const GSlot g0 = g_slot(c, 3 * h), g1 = g_slot(c, 3 * h + 1), g2 = g_slot(c, 3 * h + 2);
  {
    float F[32];
    qk_a(S, F, at.q[0], kb);
    wgmma_commit();
    if (FUSE) { g_wait(c, g0); g_wait(c, g1); }
    wgmma_wait<0>();
    fix_a(S, F, at);
  }
  exp_all<FUSE ? 2 : 0>(acc, c, S, P, n0, n1, l, g0.a16, g0.b16, g1.a16, g1.b16);
  {
    uint32_t PF[4][4];
#pragma unroll
    for (int k = 0; k < 4; k++) {
#pragma unroll
      for (int i = 0; i < 4; i++) {
        const int col = k * 16 + (i >> 1) * 8, r = at.rowc + (i & 1) * 8;
        const uint32_t m = (col > r ? 0xFFFFu : 0u) | (col + 1 > r ? 0xFFFF0000u : 0u);
        PF[k][i] = P[4 + k][i] & m; P[4 + k][i] &= ~m;
      }
    }
    wgmma_fence();
    wgmma_pv0(O, P[0][0], P[0][1], P[0][2], P[0][3], desc_sw64(kb + 3 * 256 + 2));
#pragma unroll
    for (int k = 1; k < 8; k++) wgmma_pv(O, P[k][0], P[k][1], P[k][2], P[k][3], desc_sw64(kb + 3 * 256 + 2 + k * 64));
#pragma unroll
    for (int k = 0; k < 4; k++) wgmma_pv(O, PF[k][0], PF[k][1], PF[k][2], PF[k][3], desc_sw64(kb + 2 + k * 64));
    wgmma_qk128(S, at.q[0][0], at.q[0][1], at.q[0][2], at.q[0][3], desc_sw64(kb + 256));
    wgmma_commit();
    if (FUSE) g_wait(c, g2);
    wgmma_wait<0>();
  }
  if (FUSE) { g_release(c, g0); g_release(c, g1); }
  fix_b(S, at);
  exp_all<FUSE ? 1 : 0>(acc, c, S, P, n0, n1, l, g2.a16, g2.b16, 0u, 0u);
  wgmma_fence();
#pragma unroll
  for (int k = 0; k < 8; k++) wgmma_pv(O, P[k][0], P[k][1], P[k][2], P[k][3], desc_sw64(kb + 256 + 2 + k * 64));
  wgmma_commit();
  l0 = l[0] + l[1]; l1 = l[2] + l[3];
  l0 += __shfl_xor_sync(0xffffffffu, l0, 1); l1 += __shfl_xor_sync(0xffffffffu, l1, 1);
  l0 += __shfl_xor_sync(0xffffffffu, l0, 2); l1 += __shfl_xor_sync(0xffffffffu, l1, 2);
  wgmma_wait<0>();
  if (FUSE) g_release(c, g2);
}

DEVI void attention(float (&acc)[64], Ctx& c, Attn& at, int wi) {
  const uint32_t kvb = ((c.sbase & 0x3FFFF) + OFF_KV + c.wg * 4096) >> 4;
#pragma unroll 1
  for (int h = 0; h < 4; h++) {
    const uint32_t kb = kvb + (h & 1) * (KVBUF >> 4);
    float O[8], l0, l1;
    mbar_wait(c.bars + 8 * (BAR_KVFULL + (h & 1)), h >> 1, c.t0);
    head_pass<true>(acc, c, at, h, kb, __uint_as_float(at.nm[0] << 16), __uint_as_float(at.nm[0] & 0xffff0000u), O, l0, l1);
    const bool bad = !(l0 > 1e-6f && l0 < 1e18f && l1 > 1e-6f && l1 < 1e18f);
    float c0, c1;
    uint32_t o0, o1, o2, o3;
    if (wg_any(c.wg, bad)) {
      float x0 = __int_as_float(0xff800000), x1 = x0;
      {
        float T[64];
        wgmma_fence();
        wgmma_qk128(T, at.q[0][0], at.q[0][1], at.q[0][2], at.q[0][3], desc_sw64(kb + 256));
        wgmma_commit();
        wgmma_wait<0>();
        fix_b(T, at);
        row_max(T, x0, x1);
      }
      ONCE { asm volatile("" : "+f"(x0), "+f"(x1)); }
      {
        float T[64], G[32];
        qk_a(T, G, at.q[0], kb);
        wgmma_commit();
        wgmma_wait<0>();
        fix_a(T, G, at);
        row_max(T, x0, x1);
      }
      x0 = fmaxf(x0, __shfl_xor_sync(0xffffffffu, x0, 1)); x1 = fmaxf(x1, __shfl_xor_sync(0xffffffffu, x1, 1));
      x0 = fmaxf(x0, __shfl_xor_sync(0xffffffffu, x0, 2)); x1 = fmaxf(x1, __shfl_xor_sync(0xffffffffu, x1, 2));
      float O2[8];
      head_pass<false>(acc, c, at, h, kb, -x0 * SC, -x1 * SC, O2, l0, l1);
      c0 = __fdividef(at.g0, l0); c1 = __fdividef(at.g1, l1);
      o0 = pack_bf16(O2[0] * c0, O2[1] * c0); o1 = pack_bf16(O2[2] * c1, O2[3] * c1);
      o2 = pack_bf16(O2[4] * c0, O2[5] * c0); o3 = pack_bf16(O2[6] * c1, O2[7] * c1);
    } else {
      c0 = __fdividef(at.g0, l0); c1 = __fdividef(at.g1, l1);
      o0 = pack_bf16(O[0] * c0, O[1] * c0); o1 = pack_bf16(O[2] * c1, O[3] * c1);
      o2 = pack_bf16(O[4] * c0, O[5] * c0); o3 = pack_bf16(O[6] * c1, O[7] * c1);
    }
    if (c.lane == 0) mbar_arrive(c.bars + 8 * (h == 3 ? BAR_ATTDONE : BAR_KVEMPTY + (h & 1)));
    const uint32_t ost = c.sbase + OFF_A + c.wg * 8192 + h * 2048;
    const int mi = c.lane >> 3;
    const int srow = wi * 16 + (c.lane & 7) + 8 * (mi & 1);
    stsm_x4(ost + srow * 32 + (mi >> 1) * 16, o0, o1, o2, o3);
    fence_async_smem();
    __syncwarp();
    if (c.lane == 0) mbar_arrive(c.bars + 8 * (BAR_STG + c.wg));
#pragma unroll
    for (int i = 0; i < 4; i++) { at.q[0][i] = at.q[1][i]; at.q[1][i] = at.q[2][i]; at.q[2][i] = at.q[3][i]; }
    at.nm[0] = at.nm[1]; at.nm[1] = at.nm[2]; at.nm[2] = at.nm[3];
  }
}

template <int CH, int NACC>
DEVI void store_h_chunk(const float (&acc)[NACC], uint32_t base  , int lane, float s0, float s1) {
  const int mi = lane >> 3;
#pragma unroll
  for (int tp = 0; tp < 4; tp++) {
    const int t = CH * 8 + tp * 2;
    const uint32_t r0 = pack_bf16(fmaxf(acc[4 * t + 0], 0.f) * s0, fmaxf(acc[4 * t + 1], 0.f) * s0);
    const uint32_t r1 = pack_bf16(fmaxf(acc[4 * t + 2], 0.f) * s1, fmaxf(acc[4 * t + 3], 0.f) * s1);
    const uint32_t r2 = pack_bf16(fmaxf(acc[4 * t + 4], 0.f) * s0, fmaxf(acc[4 * t + 5], 0.f) * s0);
    const uint32_t r3 = pack_bf16(fmaxf(acc[4 * t + 6], 0.f) * s1, fmaxf(acc[4 * t + 7], 0.f) * s1);
    stsm_x4(base + (((tp * 2 + (mi >> 1)) ^ (lane & 7)) << 4), r0, r1, r2, r3);
  }
}

DEVI void get_gate(Attn& at, const Ctx& c, int warp) {
  mbar_wait(c.bars + 8 * BAR_GIN, 0, c.t0);
  const uint32_t a = c.sbase + OFF_GIN + (warp * 16 + (c.lane >> 2)) * 4;
  asm volatile("ld.shared.f32 %0, [%1];" : "=f"(at.g0) : "r"(a) : "memory");
  asm volatile("ld.shared.f32 %0, [%1];" : "=f"(at.g1) : "r"(a + 32) : "memory");
}

template <int N>
DEVI void phase_q(Ctx& c, Attn& at, int warp) {
  float acc[N / 2];
#pragma unroll
  for (int i = 0; i < N / 2; i++) acc[i] = 0.f;
  bare_groups<N>(acc, c, 0, 16);
  drain(c);
  const int lane = c.lane, mi = lane >> 3;
  const int row = warp * 16 + (lane & 7) + 8 * (mi & 1);
  const int sw = (row >> 1) & 3;
#pragma unroll
  for (int hh = 0; hh < 4; hh++) {
    const uint32_t base = c.sbase + OFF_KV + hh * 8192 + row * 64;
#pragma unroll
    for (int kv = 0; kv < 2; kv++) {
      const int t = 8 + kv * 8 + 2 * hh;
      stsm_x4(base + (((kv * 2 + (mi >> 1)) ^ sw) << 4),
              pack_bf16(acc[4 * t + 0], acc[4 * t + 1]), pack_bf16(acc[4 * t + 2], acc[4 * t + 3]),
              pack_bf16(acc[4 * t + 4], acc[4 * t + 5]), pack_bf16(acc[4 * t + 6], acc[4 * t + 7]));
    }
  }
  fence_async_smem();
  __syncwarp();
  if (lane == 0) mbar_arrive(c.bars + 8 * (BAR_STG + c.wg));
  if constexpr (N == 256) {
    get_gate(at, c, warp);
    store_h_chunk<3>(acc, c.sbase + OFF_KV + 32768 + row * 128, lane, 1.f - at.g0, 1.f - at.g1);
    fence_async_smem();
    __syncwarp();
    if (lane == 0) mbar_arrive(c.bars + 8 * (BAR_STE + c.wg));
  }
#pragma unroll
  for (int hh = 0; hh < 4; hh++) {
#pragma unroll
    for (int i = 0; i < 4; i++) at.q[hh][i] = pack_bf16(acc[8 * hh + 2 * i], acc[8 * hh + 2 * i + 1]);
    const float* q = &acc[8 * hh];
    const float* k = &acc[32 + 8 * hh];
    float d0 = q[0] * k[0] + q[1] * k[1] + q[4] * k[4] + q[5] * k[5], d1 = q[2] * k[2] + q[3] * k[3] + q[6] * k[6] + q[7] * k[7];
    d0 += __shfl_xor_sync(0xffffffffu, d0, 1); d1 += __shfl_xor_sync(0xffffffffu, d1, 1);
    d0 += __shfl_xor_sync(0xffffffffu, d0, 2); d1 += __shfl_xor_sync(0xffffffffu, d1, 2);
    at.nm[hh] = pack_bf16(-d0 * SC, -d1 * SC);
  }
}

DEVI void first_loads(const Params& P, uint32_t sbase, int e, int j, int rb) {
  const uint32_t bars = sbase + OFF_BAR, fb = bars + 8 * (BAR_FULLB + e), fa = bars + 8 * (BAR_FULLA + e);
  mbar_expect_tx(fa, 16384);
  mbar_expect_tx(fb, (j & 1) ? 12288 : 16384);
  if (e == 0) tma_load_2d(sbase + OFF_A, &P.tmX, 0, rb * 128, fa);
#pragma unroll
  for (int r = 0; r < 2; r++) {
    tma_load_3d(sbase + OFF_B + e * SLOT + r * 8192, &P.tmWqkv, 64 * j, e * 32 + r * 16, 0, fb);
    if (!(j & 1)) tma_load_3d(sbase + OFF_B + e * SLOT + r * 8192 + 6144, &P.tmW1a, 0, e * 32 + r * 16, 24 + (j >> 1), fb);
  }
  if (e == 1) tma_load_2d(sbase + OFF_A + SLOT, &P.tmX, 64, rb * 128, fa);
}

__global__ void __cluster_dims__(2, 1, 1) __launch_bounds__(384, 1) fused_kernel(const __grid_constant__ Params P) {
  extern __shared__ uint8_t smem_raw[];
  const uint32_t sbase = (smem_u32(smem_raw) + 1023u) & ~1023u;
  const uint32_t bars = sbase + OFF_BAR;
  const int tid = threadIdx.x, warp = tid >> 5, lane = tid & 31;
  const uint32_t rank = blockIdx.x & 1, peer = rank ^ 1;
  const int j = (blockIdx.x >> 1) & 7, rb = ((blockIdx.x >> 4) << 1) | rank;
  const uint32_t t0 = clk32();

  const int typeB = j & 1;
  if (tid == 288) {
    for (int s = 0; s < NA2; s++) mbar_init(bars + 8 * (BAR_FULLA + s), 1);
    for (int s = 0; s < NB; s++) mbar_init(bars + 8 * (BAR_FULLB + s), 1);
    fence_async_smem();
  } else if (tid < 10) {
    asm volatile("prefetch.tensormap [%0];" ::"l"(&P.tmX + tid) : "memory");
  } else if (tid == 256) {
    for (int s = 0; s < NA2; s++) mbar_init(bars + 8 * (BAR_EMPTYA + s), 10);
    for (int s = 0; s < NB; s++) mbar_init(bars + 8 * (BAR_EMPTYB + s), 16);
  } else if (tid == 320) {
    for (int s = 0; s < 2; s++) { mbar_init(bars + 8 * (BAR_KVFULL + s), 1); mbar_init(bars + 8 * (BAR_KVEMPTY + s), 8); mbar_init(bars + 8 * (BAR_STG + s), 4); mbar_init(bars + 8 * (BAR_STE + s), 4); }
    mbar_init(bars + 8 * BAR_PIN, 1); mbar_init(bars + 8 * BAR_ATTDONE, 8); mbar_init(bars + 8 * BAR_GIN, 1); mbar_init(bars + 8 * BAR_GATE, 1); mbar_init(bars + 8 * (BAR_GATE + 1), 1);
  }
  if (tid >= 256 && lane == 0) asm volatile("fence.mbarrier_init.release.cluster;" ::: "memory");
  const unsigned ep1 = ld_relaxed(&g_epoch) + 1;
  __syncwarp();
  cluster_arrive();
  if (tid == 288) { first_loads(P, sbase, 0, j, rb); first_loads(P, sbase, 1, j, rb); }
  __syncwarp();

  const int on = 12 + 4 * typeB;

  if (warp < 8) {
    asm volatile("setmaxnreg.inc.sync.aligned.u32 232;");
    cluster_wait();
    const int wg = __shfl_sync(0xffffffffu, warp >> 2, 0), wi = warp & 3;
    Ctx c{sbase, bars, peer, t0, ((sbase & 0x3FFFF) + OFF_A + wg * 8192) >> 4, ((sbase & 0x3FFFF) + OFF_B) >> 4, wg, lane, 0, 0, 0u, 0u, 32 + on + 4 - NB, 0, -1, -1};
    Attn at;
    at.cmin = 4 - 2 * rb - wg;
    at.rowc = wi * 16 + (lane >> 2) - (lane & 3) * 2;
    if (tid == 0) TR(0);
    if (typeB) phase_q<192>(c, at, warp);
    else phase_q<256>(c, at, warp);
    if (tid == 0) TR(2);
    {
      float acc[96];
#pragma unroll
      for (int i = 0; i < 96; i++) acc[i] = 0.f;
      bare_groups<192>(acc, c, 0, 16);
      get_gate(at, c, warp);
      drain(c);
      if (tid == 0) TR(1);
      const uint32_t rowoff = (warp * 16 + (lane & 7) + 8 * ((lane >> 3) & 1)) * 128;
      const float s0 = 1.f - at.g0, s1 = 1.f - at.g1;
      constexpr int e0 = 16 % NA, e1 = 17 % NA, e2 = 18 % NA;
      mbar_wait(bars + 8 * (BAR_FULLA + e0), (16 / NA) & 1, t0);
      store_h_chunk<0>(acc, sbase + OFF_A + e0 * SLOT + rowoff, lane, s0, s1);
      mbar_wait(bars + 8 * (BAR_FULLA + e1), (17 / NA) & 1, t0);
      store_h_chunk<1>(acc, sbase + OFF_A + e1 * SLOT + rowoff, lane, s0, s1);
      mbar_wait(bars + 8 * (BAR_FULLA + e2), (18 / NA) & 1, t0);
      store_h_chunk<2>(acc, sbase + OFF_A + e2 * SLOT + rowoff, lane, s0, s1);
    }
    fence_async_smem();
    wg_bar(wg);
    if (lane == 0) mbar_arrive(bars + 8 * (BAR_STG + wg));
    if (tid == 0) TR(4);
    float own[32];
    {
      float acc[64];
#pragma unroll
      for (int i = 0; i < 64; i++) acc[i] = 0.f;
      attention(acc, c, at, wi);
      if (tid == 0) TR(3);
      c.ae = 28; c.aph ^= 0x1E; c.bi = 44 % NB; c.bph = (44 / NB) & 1; c.brem -= 12;
      bare_groups<128>(acc, c, 12, on);
      drain(c);
      if (tid == 0) TR(5);
      named_bar<3>(256);
      const uint32_t pst = sbase + OFF_B + ((30 + on) % NB) * SLOT + wg * 8192 + (tid & 127) * 16;
#pragma unroll
      for (int i = 0; i < 4; i++) {
        uint32_t r[4];
#pragma unroll
        for (int k = 0; k < 4; k++) {
          const int idx = 8 * i + 2 * k;
          const float lo = typeB ? acc[idx] : acc[32 + idx], hi = typeB ? acc[idx + 1] : acc[32 + idx + 1];
          r[k] = pack_bf16(lo, hi);
        }
        sts128(pst + i * 2048, r[0], r[1], r[2], r[3]);
      }
#pragma unroll
      for (int i = 0; i < 32; i++) own[i] = typeB ? acc[32 + i] : acc[i];
      fence_async_smem();
      __syncwarp();
      if (lane == 0) mbar_arrive(bars + 8 * (BAR_STG + wg));
    }
    for (int g = 0; g < 8; g++) {
      const uint32_t a16 = c.a16 + c.ai * (SLOT >> 4);
      const uint32_t b16 = c.b16 + c.bi * (SLOT >> 4) + (g & 1) * 512;
      gemm_wait(c);
      wgmma_fence();
#pragma unroll
      for (int s = 0; s < 4; s++) wgmma_ss<64>(own, desc_sw128<16>(a16 + s * 2), desc_sw128<2048>(b16 + s * 128));
      wgmma_commit();
      c.ai = next_a_slot(c.ae, c.ai); c.ae++;
      if (g & 1) { if (++c.bi == NB) { c.bi = 0; c.bph ^= 1; } }
    }
    wgmma_wait<0>();
    if (tid == 0) TR(6);
    mbar_wait(bars + 8 * BAR_PIN, 0, t0);
    if (tid == 0) TR(7);
    {
      const uint32_t pin = sbase + OFF_B + ((31 + on) % NB) * SLOT + wg * 8192 + (tid & 127) * 16;
      wg_bar(wg);
      const uint32_t ob = sbase + OFF_A + wg * 8192;
      const uint32_t orow = ob + (wi * 16 + (lane & 7) + 8 * ((lane >> 3) & 1)) * 128;
#pragma unroll
      for (int i = 0; i < 4; i++) {
        const uint4 v = lds128(pin + i * 2048);
        const uint32_t r[4] = {v.x, v.y, v.z, v.w};
        uint32_t o[4];
#pragma unroll
        for (int k = 0; k < 4; k++) {
          const int idx = 8 * i + 2 * k;
          o[k] = pack_bf16(own[idx] + __uint_as_float(r[k] << 16), own[idx + 1] + __uint_as_float(r[k] & 0xffff0000u));
        }
        stsm_x4(orow + (((i * 2 + (lane >> 4)) ^ (lane & 7)) << 4), o[0], o[1], o[2], o[3]);
      }
      fence_async_smem();
      __syncwarp();
      if (lane == 0) {
        tma_store_2d(&P.tmOut, j * 64, rb * 128 + warp * 16, ob + wi * 2048);
        bulk_commit();
        asm volatile("cp.async.bulk.wait_group.read 0;" ::: "memory");
      }
    }
    if (tid == 0) TR(8);
  } else {
    asm volatile("setmaxnreg.dec.sync.aligned.u32 40;");
    if (warp == 8) {
      __syncwarp();
      cluster_wait();
      if (lane == 0) {
        int bi = 2; uint32_t bph = 1;
        const int nb = 32 + on + 4;
        for (int eb = 2; eb < nb; eb++) {
          if (eb == 4 || eb == 6) {
            for (int ea = eb - 2 - (eb == 6 ? 1 : 0); ea < (eb == 4 ? 3 : NA); ea++) {
              mbar_expect_tx(bars + 8 * (BAR_FULLA + ea), 16384);
              tma_load_2d(sbase + OFF_A + ea * SLOT, &P.tmX, ea * 64, rb * 128, bars + 8 * (BAR_FULLA + ea));
            }
          }
          const uint32_t fb = bars + 8 * (BAR_FULLB + bi), dst = sbase + OFF_B + bi * SLOT + rank * 8192;
          mbar_wait(bars + 8 * (BAR_EMPTYB + bi), bph, t0);
          if (eb < 16) {
            mbar_expect_tx(fb, typeB ? 12288 : 16384);
            tma_load_3d_mc(dst, &P.tmWqkv, 64 * j, eb * 32 + rank * 16, 0, fb);
            if (!typeB) tma_load_3d_mc(dst + 6144, &P.tmW1a, 0, eb * 32 + rank * 16, 24 + (j >> 1), fb);
          }
          else if (eb < 32) { mbar_expect_tx(fb, 12288); tma_load_3d_mc(dst, &P.tmW1b, 0, (eb - 16) * 32 + rank * 16, 3 * j, fb); }
          else if (eb < 32 + on) { int ow; const int ch = oh_chunk(j, eb - 32, ow); mbar_expect_tx(fb, 16384); tma_load_3d_mc(dst, &P.tmW2, 0, ch * 64 + rank * 32, (j >> 1) * 2, fb); }
          else { mbar_expect_tx(fb, 16384); tma_load_4d_mc(dst, &P.tmWo, 64 * j, 0, eb - 32 - on, rank * 4, fb); }
          if (++bi == NB) { bi = 0; bph ^= 1; }
          if (eb == PFAT) {
            const int b = blockIdx.x;
            l2_prefetch((const uint8_t*)P.w1 + b * 14336, 14336);
            l2_prefetch((const uint8_t*)P.w2 + b * 14336, 14336);
            l2_prefetch((const uint8_t*)P.wo + b * 4096, 4096);
          }
        }
      }
    } else if (warp == 9) {
      cluster_wait();
      if (lane == 0) {
        for (int ea = 0; ea < NA; ea++) mbar_arrive_n(bars + 8 * (BAR_EMPTYA + ea), 2);
        int ai = 0; uint32_t aph = 0xE0;
        const int na = 16 + on + 8;
        unsigned ready = 0;
        for (int ea = NA; ea < na; ea++) {
          const uint32_t fb = bars + 8 * (BAR_FULLA + ai), dst = sbase + OFF_A + ai * SLOT;
          int ch = ea & 7, need = -1;
          if (ea >= 16 + on) { need = 8 + ea - 16 - on; ch = 20 + need; }
          else if (ea >= 19) ch = oh_chunk(j, ea - 16, need);
          if (need >= 0 && !((ready >> need) & 1)) {
            const unsigned* fp = need < 8 ? &g_flag_h[rb * 8 * FS] : need < 16 ? &g_flag_o[rb * 8 * FS] : &g_flag_e[rb * 8 * FS];
            const unsigned tgt = (need & 8) ? ep1 * 8 : ep1 * 2;
            do {
              unsigned v[8];
#pragma unroll
              for (int i = 0; i < 8; i++) v[i] = ld_relaxed(fp + i * FS);
#pragma unroll
              for (int i = 0; i < 8; i++) if ((int)(v[i] - tgt) >= 0) ready |= 1u << (i + (need & 24));
            } while (!((ready >> need) & 1) && clk32() - t0 < TIMEOUT);
            fence_async_global();
          }
          if (ea == 32) mbar_wait(bars + 8 * BAR_ATTDONE, 0, t0);
          mbar_wait(bars + 8 * (BAR_EMPTYA + ai), (aph >> ai) & 1, t0);
          if (ea >= 16 && ea < 19) mbar_arrive(fb);
          else {
            if (ea != 15) mbar_arrive_n(bars + 8 * (BAR_EMPTYA + ai), 2);
            mbar_expect_tx(fb, 16384);
            tma_load_2d(dst, ea < 16 ? &P.tmX : &P.tmHO, ch * 64, rb * 128, fb);
          }
          TR(24 + ea);
          aph ^= 1u << ai;
          ai = next_a_slot(ea, ai);
        }
      }
    } else {
      const int wg = warp - 10;
      cluster_wait();
      {
        const int rowg = rb * 128 + j * 16 + wg * 8;
        const uint32_t xs = sbase + OFF_KV + 32768 + wg * 8192;
        if (lane == 0) {
          mbar_wait(bars + 8 * (BAR_FULLB + 1), 0, t0);
          mbar_expect_tx(bars + 8 * (BAR_GATE + wg), 8192);
          bulk_load(xs, P.x + (size_t)rowg * DM, 8192, bars + 8 * (BAR_GATE + wg));
        }
        const uint4* gw = (const uint4*)P.gate_w;
        const uint4 w0 = __ldg(gw + lane), w1 = __ldg(gw + 32 + lane);
        const uint32_t wa[8] = {w0.x, w0.y, w0.z, w0.w, w1.x, w1.y, w1.z, w1.w};
        mbar_wait(bars + 8 * (BAR_GATE + wg), 0, t0);
        float zz = 0.f;
#pragma unroll 1
        for (int i = 0; i < 8; i++) {
          const uint4 x0 = lds128(xs + i * 1024 + lane * 16), x1 = lds128(xs + i * 1024 + 512 + lane * 16);
          const uint32_t xa[8] = {x0.x, x0.y, x0.z, x0.w, x1.x, x1.y, x1.z, x1.w};
          float z = 0.f;
#pragma unroll
          for (int e = 0; e < 8; e++) {
            z = fmaf(__uint_as_float(xa[e] << 16), __uint_as_float(wa[e] << 16), z);
            z = fmaf(__uint_as_float(xa[e] & 0xffff0000u), __uint_as_float(wa[e] & 0xffff0000u), z);
          }
#pragma unroll
          for (int o = 16; o > 0; o >>= 1) z += __shfl_xor_sync(0xffffffffu, z, o);
          if (lane == i) zz = z;
        }
        if (lane < 8) asm volatile("st.shared.f32 [%0], %1;" ::"r"(sbase + OFF_GST + wg * 32 + lane * 4), "f"(1.f / (1.f + __expf(-zz))) : "memory");
        fence_async_smem();
        __syncwarp();
        if (lane == 0) {
          bulk_store(&g_gate[rowg], sbase + OFF_GST + wg * 32, 32);
          bulk_commit(); bulk_wait_all();
          flag_add(&g_flag_g[rb * FS]);
          if (wg == 1) {
            flag_wait(&g_flag_g[rb * FS], ep1 * 16, t0);
            fence_async_global();
            mbar_expect_tx(bars + 8 * BAR_GIN, 512);
            bulk_load(sbase + OFF_GIN, &g_gate[rb * 128], 512, bars + 8 * BAR_GIN);
          }
          if (wg == 0) TR(10);
        }
      }
      if (lane == 0) {
        const uint32_t stg = bars + 8 * (BAR_STG + wg);
        mbar_wait(stg, 0, t0);
        for (int hh = 0; hh < 4; hh++)
          bulk_store(g_kv + ((size_t)(4 * j + hh) * SEQ + rb * 128 + wg * 64) * 64, sbase + OFF_KV + hh * 8192 + wg * 4096, 4096);
        bulk_commit(); bulk_wait_all();
        flag_add(&g_flag_kv[(rb * 8 + j) * FS]);
        if (wg == 0) TR(21);
        if (!typeB) {
          mbar_wait(bars + 8 * (BAR_STE + wg), 0, t0);
          tma_store_2d(&P.tmHOs, (24 + (j >> 1)) * 64, rb * 128 + wg * 64, sbase + OFF_KV + 32768 + wg * 8192);
          bulk_commit(); bulk_wait_all();
          flag_add(&g_flag_e[(rb * 8 + j) * FS]);
          if (wg == 1) flag_wait(&g_flag_e[(rb * 8 + j) * FS], ep1 * 2, t0);
        }
        const int nblk = rb >= 2 ? 3 : rb + 1;
        const uint32_t kvbytes = nblk * 8192;
        const uint8_t* kvsrc = g_kv + ((size_t)(4 * j) * SEQ + (rb + 1 - nblk) * 128) * 64;
        const uint32_t kvdst = sbase + OFF_KV + wg * KVBUF + (3 - nblk) * 8192;
        {
          const unsigned* f0 = &g_flag_kv[(rb * 8 + j) * FS];
          const unsigned* f1 = rb >= 1 ? f0 - 8 * FS : f0;
          const unsigned* f2 = rb >= 2 ? f0 - 16 * FS : f0;
          unsigned v0, v1, v2;
          do { v0 = ld_relaxed(f0); v1 = ld_relaxed(f1); v2 = ld_relaxed(f2); }
          while (((int)(v0 - ep1 * 2) < 0 || (int)(v1 - ep1 * 2) < 0 || (int)(v2 - ep1 * 2) < 0) && clk32() - t0 < TIMEOUT);
        }
        if (wg == 0) TR(11);
        fence_async_global();
        mbar_expect_tx(bars + 8 * (BAR_KVFULL + wg), kvbytes);
        bulk_load(kvdst, kvsrc + (size_t)wg * SEQ * 64, kvbytes, bars + 8 * (BAR_KVFULL + wg));
        for (int ev = 1; ev < 7; ev++) {
          mbar_wait(stg, ev & 1, t0);
          if (ev == 1) {
            for (int i = 0; i < 3; i++)
              tma_store_2d(&P.tmHOs, (3 * j + i) * 64, rb * 128 + wg * 64, sbase + OFF_A + ((16 + i) % NA) * SLOT + wg * 8192);
            bulk_commit(); bulk_wait_all();
            flag_add(&g_flag_h[(rb * 8 + j) * FS]);
            for (int i = 0; i < 3; i++) mbar_arrive(bars + 8 * (BAR_EMPTYA + (16 + i) % NA));
            if (wg == 0) TR(22);
            if (wg == 0) {
              const unsigned old = atomicAdd(&g_done, 1u);
              if (old == gridDim.x - 1) { g_done = 0; *(volatile unsigned*)&g_epoch = ep1; }
            }
          } else if (ev == 6) {
            bulk_store(g_part + (size_t)(rb * 8 + (j ^ 1)) * 16384 + wg * 8192, sbase + OFF_B + ((30 + on) % NB) * SLOT + wg * 8192, 8192);
            bulk_commit(); bulk_wait_all();
            flag_add(&g_flag_p[(rb * 8 + (j ^ 1)) * FS]);
            if (wg == 0) TR(23);
            if (wg == 1) {
              flag_wait(&g_flag_p[(rb * 8 + j) * FS], ep1 * 2, t0);
              fence_async_global();
              mbar_expect_tx(bars + 8 * BAR_PIN, 16384);
              bulk_load(sbase + OFF_B + ((31 + on) % NB) * SLOT, g_part + (size_t)(rb * 8 + j) * 16384, 16384, bars + 8 * BAR_PIN);
            }
          } else {
            const int hh = ev - 2;
            tma_store_2d(&P.tmOs, DFF + hh * 128 + j * 16, rb * 128 + wg * 64, sbase + OFF_A + (15 % NA) * SLOT + wg * 8192 + hh * 2048);
            bulk_commit();
            if (hh == wg) {
              mbar_wait(bars + 8 * (BAR_KVEMPTY + wg), 0, t0);
              mbar_expect_tx(bars + 8 * (BAR_KVFULL + wg), kvbytes);
              bulk_load(kvdst, kvsrc + (size_t)(wg + 2) * SEQ * 64, kvbytes, bars + 8 * (BAR_KVFULL + wg));
            }
            bulk_wait_all();
            flag_add(&g_flag_o[(rb * 8 + hh * 2 + (j >> 2)) * FS]);
            if (hh == 3) mbar_arrive(bars + 8 * (BAR_EMPTYA + 15 % NA));
            if (wg == 0) TR(12 + hh);
          }
        }
      }
    }
  }
}

typedef CUresult (*EncodeFn)(CUtensorMap*, CUtensorMapDataType, cuuint32_t, void*, const cuuint64_t*, const cuuint64_t*, const cuuint32_t*,
                             const cuuint32_t*, CUtensorMapInterleave, CUtensorMapSwizzle, CUtensorMapL2promotion, CUtensorMapFloatOOBfill);

void make_map(EncodeFn enc, CUtensorMap* m, const void* ptr, int rank, const cuuint64_t* dims, const cuuint64_t* strides, const cuuint32_t* box,
              CUtensorMapSwizzle sw = CU_TENSOR_MAP_SWIZZLE_128B) {
  cuuint32_t es[4] = {1, 1, 1, 1};
  enc(m, CU_TENSOR_MAP_DATA_TYPE_BFLOAT16, rank, const_cast<void*>(ptr), dims, strides, box, es, CU_TENSOR_MAP_INTERLEAVE_NONE, sw,
      CU_TENSOR_MAP_L2_PROMOTION_L2_256B, CU_TENSOR_MAP_FLOAT_OOB_FILL_NONE);
}

}

extern "C" void kernel_launch(void* const* d_in, const int* in_sizes, int n_in, void* d_out, int out_size) {
  (void)in_sizes; (void)n_in; (void)out_size;
  static EncodeFn enc = nullptr;
  static void* ho_ptr = nullptr;
  if (!enc) {
    void* fn = nullptr; cudaDriverEntryPointQueryResult st;
    cudaGetDriverEntryPoint("cuTensorMapEncodeTiled", &fn, cudaEnableDefault, &st);
    enc = (EncodeFn)fn;
    cudaGetSymbolAddress(&ho_ptr, g_ho);
    cudaFuncSetAttribute(fused_kernel, cudaFuncAttributeMaxDynamicSharedMemorySize, SMEM_BYTES);
  }
  const __nv_bfloat16* x = (const __nv_bfloat16*)d_in[0];
  const __nv_bfloat16* wqkv = (const __nv_bfloat16*)d_in[1];
  const __nv_bfloat16* wo = (const __nv_bfloat16*)d_in[2];
  const __nv_bfloat16* w1 = (const __nv_bfloat16*)d_in[4];
  const __nv_bfloat16* w2 = (const __nv_bfloat16*)d_in[5];
  const __nv_bfloat16* gate_w = (const __nv_bfloat16*)d_in[6];
  Params P;
  { cuuint64_t d[2] = {DM, SEQ}, s[1] = {DM * 2}; cuuint32_t b[2] = {64, 128}; make_map(enc, &P.tmX, x, 2, d, s, b); }
  { cuuint64_t d[3] = {512, 512, 3}, s[2] = {1536 * 2, 512 * 2}; cuuint32_t b[3] = {64, 16, 3}; make_map(enc, &P.tmWqkv, wqkv, 3, d, s, b); }
  { cuuint64_t d[3] = {64, 512, 28}, s[2] = {DFF * 2, 128}; cuuint32_t b[3] = {64, 16, 1}; make_map(enc, &P.tmW1a, w1, 3, d, s, b);
    b[2] = 3; make_map(enc, &P.tmW1b, w1, 3, d, s, b); }
  { cuuint64_t d[3] = {64, DFF, 8}, s[2] = {DM * 2, 128}; cuuint32_t b[3] = {64, 32, 2}; make_map(enc, &P.tmW2, w2, 3, d, s, b); }
  { cuuint64_t d[4] = {DM, 16, 4, 8}, s[3] = {DM * 2, 16 * DM * 2, 64 * DM * 2}; cuuint32_t b[4] = {64, 16, 1, 4}; make_map(enc, &P.tmWo, wo, 4, d, s, b); }
  { cuuint64_t d[2] = {KHO, SEQ}, s[1] = {KHO * 2}; cuuint32_t b[2] = {64, 128}; make_map(enc, &P.tmHO, ho_ptr, 2, d, s, b);
    b[1] = 64; make_map(enc, &P.tmHOs, ho_ptr, 2, d, s, b);
    b[0] = 16; make_map(enc, &P.tmOs, ho_ptr, 2, d, s, b, CU_TENSOR_MAP_SWIZZLE_NONE); }
  { cuuint64_t d[2] = {DM, SEQ}, s[1] = {DM * 2}; cuuint32_t b[2] = {64, 16}; make_map(enc, &P.tmOut, d_out, 2, d, s, b); }
  P.x = x; P.gate_w = gate_w; P.w1 = w1; P.w2 = w2; P.wo = wo; P.out = (__nv_bfloat16*)d_out;
  fused_kernel<<<128, 384, SMEM_BYTES>>>(P);
}
```

```cpp
#include <cuda_runtime.h>
#include <cuda_bf16.h>
#include <cuda.h>
#include <stdint.h>

#define DEVI __device__ __forceinline__

namespace {

constexpr int SEQ = 2048, DM = 512, DFF = 1792, KHO = 2304;
constexpr int NA = 5, NB = 6, SLOT = 16384, KVBUF = 24576;
constexpr int NA2 = 8;
constexpr int OFF_B = 0, OFF_A = NB * SLOT, OFF_KV = OFF_A + NA * SLOT, OFF_BAR = OFF_KV + 2 * KVBUF;
constexpr int OFF_GST = OFF_BAR + 512;
constexpr int OFF_GIN = OFF_BAR + 1024;
constexpr int SMEM_BYTES = OFF_BAR + 1536 + 1024;
constexpr uint32_t TIMEOUT = 1u << 28;
#define WAIT_HINT_NS 20000u
#define PFAT 8
constexpr int FS = 8;

constexpr int BAR_FULLA = 0, BAR_EMPTYA = BAR_FULLA + NA2, BAR_FULLB = BAR_EMPTYA + NA2, BAR_EMPTYB = BAR_FULLB + NB,
              BAR_KVFULL = BAR_EMPTYB + NB, BAR_KVEMPTY = BAR_KVFULL + 2, BAR_STG = BAR_KVEMPTY + 2, BAR_PIN = BAR_STG + 2, BAR_GATE = BAR_PIN + 1, BAR_STE = BAR_GATE + 2, BAR_ATTDONE = BAR_STE + 2, BAR_GIN = BAR_ATTDONE + 1, BAR_OST = BAR_GIN + 1, BAR_QRDY = BAR_OST + 2, BAR_KVOK = BAR_QRDY + 2;

__device__ __align__(1024) uint8_t g_kv[32 * SEQ * 64];
__device__ __align__(1024) __nv_bfloat16 g_ho[SEQ * KHO];
__device__ __align__(1024) uint8_t g_part[128 * 16384];
__device__ __align__(128) float g_gate[SEQ];
__device__ unsigned g_flag_kv[128 * FS], g_flag_h[128 * FS], g_flag_o[128 * FS], g_flag_g[16 * FS], g_flag_p[128 * FS], g_flag_e[128 * FS];
__device__ unsigned g_epoch, g_done;
#define TR(i) do {} while (0)

struct Params {
  CUtensorMap tmX, tmWqkv, tmW1a, tmW1b, tmW2, tmWo, tmHO, tmHOs, tmOs, tmOut;
  const __nv_bfloat16* x;
  const __nv_bfloat16* gate_w;
  const __nv_bfloat16* w1;
  const __nv_bfloat16* w2;
  const __nv_bfloat16* wo;
  __nv_bfloat16* out;
};

DEVI uint32_t smem_u32(const void* p) { return (uint32_t)__cvta_generic_to_shared(p); }
DEVI uint32_t clk32() { uint32_t c; asm volatile("mov.u32 %0, %%clock;" : "=r"(c)); return c; }
DEVI void mbar_init(uint32_t bar, uint32_t cnt) { asm volatile("mbarrier.init.shared::cta.b64 [%0], %1;" ::"r"(bar), "r"(cnt)); }
DEVI void mbar_expect_tx(uint32_t bar, uint32_t bytes) { asm volatile("mbarrier.arrive.expect_tx.shared::cta.b64 _, [%0], %1;" ::"r"(bar), "r"(bytes) : "memory"); }
DEVI void mbar_arrive(uint32_t bar) { asm volatile("mbarrier.arrive.shared::cta.b64 _, [%0];" ::"r"(bar) : "memory"); }
DEVI void mbar_arrive_cluster(uint32_t bar, uint32_t cta) {
  asm volatile("{ .reg .b32 ra; mapa.shared::cluster.u32 ra, %0, %1; mbarrier.arrive.shared::cluster.b64 _, [ra]; }" ::"r"(bar), "r"(cta) : "memory");
}
DEVI void mbar_wait(uint32_t bar, uint32_t parity, uint32_t t0) {
  asm volatile("{ .reg .pred p; .reg .u32 c;\n"
               "mbarrier.try_wait.parity.shared::cta.b64 p, [%0], %1;\n"
               "@p bra DONE_%=;\n"
               "WAIT_%=:\n"
               "mbarrier.try_wait.parity.shared::cta.b64 p, [%0], %1, %4;\n"
               "@p bra DONE_%=;\n"
               "mov.u32 c, %%clock; sub.u32 c, c, %2; setp.lt.u32 p, c, %3;\n"
               "@p bra WAIT_%=;\n"
               "DONE_%=: }" ::"r"(bar), "r"(parity), "r"(t0), "n"(TIMEOUT), "r"(WAIT_HINT_NS) : "memory");
}
DEVI unsigned ld_relaxed(const unsigned* p) { unsigned v; asm volatile("ld.relaxed.gpu.global.u32 %0, [%1];" : "=r"(v) : "l"(p) : "memory"); return v; }
DEVI void flag_wait(const unsigned* p, unsigned target, uint32_t t0) {
  while ((int)(ld_relaxed(p) - target) < 0) { if (clk32() - t0 > TIMEOUT) break; }
}
DEVI void flag_add(unsigned* p) { asm volatile("red.relaxed.gpu.global.add.u32 [%0], 1;" ::"l"(p) : "memory"); }
DEVI void fence_async_smem() { asm volatile("fence.proxy.async.shared::cta;" ::: "memory"); }
DEVI void fence_async_global() { asm volatile("fence.proxy.async.global;" ::: "memory"); }
DEVI void tma_load_2d(uint32_t dst, const CUtensorMap* m, int c0, int c1, uint32_t bar) {
  asm volatile("cp.async.bulk.tensor.2d.shared::cluster.global.mbarrier::complete_tx::bytes [%0], [%1, {%3, %4}], [%2];" ::"r"(dst), "l"(m), "r"(bar), "r"(c0), "r"(c1) : "memory");
}
DEVI void tma_load_3d(uint32_t dst, const CUtensorMap* m, int c0, int c1, int c2, uint32_t bar) {
  asm volatile("cp.async.bulk.tensor.3d.shared::cluster.global.mbarrier::complete_tx::bytes [%0], [%1, {%3, %4, %5}], [%2];"
               ::"r"(dst), "l"(m), "r"(bar), "r"(c0), "r"(c1), "r"(c2) : "memory");
}
DEVI void tma_load_3d_mc(uint32_t dst, const CUtensorMap* m, int c0, int c1, int c2, uint32_t bar) {
  asm volatile("cp.async.bulk.tensor.3d.shared::cluster.global.mbarrier::complete_tx::bytes.multicast::cluster [%0], [%1, {%3, %4, %5}], [%2], %6;"
               ::"r"(dst), "l"(m), "r"(bar), "r"(c0), "r"(c1), "r"(c2), "h"((uint16_t)3) : "memory");
}
DEVI void tma_load_4d_mc(uint32_t dst, const CUtensorMap* m, int c0, int c1, int c2, int c3, uint32_t bar) {
  asm volatile("cp.async.bulk.tensor.4d.shared::cluster.global.mbarrier::complete_tx::bytes.multicast::cluster [%0], [%1, {%3, %4, %5, %6}], [%2], %7;"
               ::"r"(dst), "l"(m), "r"(bar), "r"(c0), "r"(c1), "r"(c2), "r"(c3), "h"((uint16_t)3) : "memory");
}
DEVI void tma_store_2d(const CUtensorMap* m, int c0, int c1, uint32_t src) {
  asm volatile("cp.async.bulk.tensor.2d.global.shared::cta.bulk_group [%0, {%1, %2}], [%3];" ::"l"(m), "r"(c0), "r"(c1), "r"(src) : "memory");
}
DEVI void bulk_store(void* dst, uint32_t src, uint32_t bytes) {
  asm volatile("cp.async.bulk.global.shared::cta.bulk_group [%0], [%1], %2;" ::"l"(dst), "r"(src), "r"(bytes) : "memory");
}
DEVI void bulk_load(uint32_t dst, const void* src, uint32_t bytes, uint32_t bar) {
  asm volatile("cp.async.bulk.shared::cluster.global.mbarrier::complete_tx::bytes [%0], [%1], %2, [%3];" ::"r"(dst), "l"(src), "r"(bytes), "r"(bar) : "memory");
}
DEVI void bulk_commit() { asm volatile("cp.async.bulk.commit_group;" ::: "memory"); }
DEVI void bulk_wait_all() { asm volatile("cp.async.bulk.wait_group 0;" ::: "memory"); }
DEVI void l2_prefetch(const void* p, uint32_t bytes) { asm volatile("cp.async.bulk.prefetch.L2.global [%0], %1;" ::"l"(p), "r"(bytes) : "memory"); }
DEVI void cluster_arrive() { asm volatile("barrier.cluster.arrive.relaxed.aligned;" ::: "memory"); }
DEVI void cluster_wait() { asm volatile("barrier.cluster.wait.aligned;" ::: "memory"); }
template <int ID> DEVI void named_bar(int n) { asm volatile("bar.sync %0, %1;" ::"n"(ID), "r"(n) : "memory"); }
DEVI void wg_bar(int wg) { if (wg == 0) named_bar<1>(128); else named_bar<2>(128); }
DEVI void wgmma_fence() { asm volatile("wgmma.fence.sync.aligned;" ::: "memory"); }
DEVI void wgmma_commit() { asm volatile("wgmma.commit_group.sync.aligned;" ::: "memory"); }
template <int N> DEVI void wgmma_wait() { asm volatile("wgmma.wait_group.sync.aligned %0;" ::"n"(N) : "memory"); }
template <uint32_t LBO> DEVI uint64_t desc_sw128(uint32_t a16) {
  return ((uint64_t)(0x40000000u | (1024 >> 4)) << 32) | (a16 + ((LBO >> 4) << 16));
}
DEVI uint64_t desc_sw64(uint32_t a16) {
  return ((uint64_t)(0x80000000u | (512 >> 4)) << 32) | (a16 + ((512 >> 4) << 16));
}
DEVI uint32_t pack_bf16(float lo, float hi) { uint32_t r; asm("cvt.rn.bf16x2.f32 %0, %1, %2;" : "=r"(r) : "f"(hi), "f"(lo)); return r; }
DEVI void stsm_x4(uint32_t addr, uint32_t r0, uint32_t r1, uint32_t r2, uint32_t r3) {
  asm volatile("stmatrix.sync.aligned.m8n8.x4.shared.b16 [%0], {%1, %2, %3, %4};" ::"r"(addr), "r"(r0), "r"(r1), "r"(r2), "r"(r3) : "memory");
}
DEVI void sts128(uint32_t addr, uint32_t r0, uint32_t r1, uint32_t r2, uint32_t r3) {
  asm volatile("st.shared.v4.b32 [%0], {%1, %2, %3, %4};" ::"r"(addr), "r"(r0), "r"(r1), "r"(r2), "r"(r3) : "memory");
}
DEVI uint4 lds128(uint32_t addr) {
  uint4 v; asm volatile("ld.shared.v4.b32 {%0, %1, %2, %3}, [%4];" : "=r"(v.x), "=r"(v.y), "=r"(v.z), "=r"(v.w) : "r"(addr) : "memory"); return v;
}
DEVI float ex2(float x) { float y; asm("ex2.approx.ftz.f32 %0, %1;" : "=f"(y) : "f"(x)); return y; }

DEVI void wgmma_ss_n64(float (&d)[32], uint64_t da, uint64_t db) {
  asm volatile("wgmma.mma_async.sync.aligned.m64n64k16.f32.bf16.bf16 {%0, %1, %2, %3, %4, %5, %6, %7, %8, %9, %10, %11, %12, %13, %14, %15, %16, %17, %18, %19, %20, %21, %22, %23, %24, %25, %26, %27, %28, %29, %30, %31}, %32, %33, 1, 1, 1, 0, 1;"
    : "+f"(d[0]), "+f"(d[1]), "+f"(d[2]), "+f"(d[3]), "+f"(d[4]), "+f"(d[5]), "+f"(d[6]), "+f"(d[7]), "+f"(d[8]), "+f"(d[9]), "+f"(d[10]), "+f"(d[11]), "+f"(d[12]), "+f"(d[13]), "+f"(d[14]), "+f"(d[15]), "+f"(d[16]), "+f"(d[17]), "+f"(d[18]), "+f"(d[19]), "+f"(d[20]), "+f"(d[21]), "+f"(d[22]), "+f"(d[23]), "+f"(d[24]), "+f"(d[25]), "+f"(d[26]), "+f"(d[27]), "+f"(d[28]), "+f"(d[29]), "+f"(d[30]), "+f"(d[31])
    : "l"(da), "l"(db));
}
DEVI void wgmma_ss_n128(float (&d)[64], uint64_t da, uint64_t db) {
  asm volatile("wgmma.mma_async.sync.aligned.m64n128k16.f32.bf16.bf16 {%0, %1, %2, %3, %4, %5, %6, %7, %8, %9, %10, %11, %12, %13, %14, %15, %16, %17, %18, %19, %20, %21, %22, %23, %24, %25, %26, %27, %28, %29, %30, %31, %32, %33, %34, %35, %36, %37, %38, %39, %40, %41, %42, %43, %44, %45, %46, %47, %48, %49, %50, %51, %52, %53, %54, %55, %56, %57, %58, %59, %60, %61, %62, %63}, %64, %65, 1, 1, 1, 0, 1;"
    : "+f"(d[0]), "+f"(d[1]), "+f"(d[2]), "+f"(d[3]), "+f"(d[4]), "+f"(d[5]), "+f"(d[6]), "+f"(d[7]), "+f"(d[8]), "+f"(d[9]), "+f"(d[10]), "+f"(d[11]), "+f"(d[12]), "+f"(d[13]), "+f"(d[14]), "+f"(d[15]), "+f"(d[16]), "+f"(d[17]), "+f"(d[18]), "+f"(d[19]), "+f"(d[20]), "+f"(d[21]), "+f"(d[22]), "+f"(d[23]), "+f"(d[24]), "+f"(d[25]), "+f"(d[26]), "+f"(d[27]), "+f"(d[28]), "+f"(d[29]), "+f"(d[30]), "+f"(d[31]), "+f"(d[32]), "+f"(d[33]), "+f"(d[34]), "+f"(d[35]), "+f"(d[36]), "+f"(d[37]), "+f"(d[38]), "+f"(d[39]), "+f"(d[40]), "+f"(d[41]), "+f"(d[42]), "+f"(d[43]), "+f"(d[44]), "+f"(d[45]), "+f"(d[46]), "+f"(d[47]), "+f"(d[48]), "+f"(d[49]), "+f"(d[50]), "+f"(d[51]), "+f"(d[52]), "+f"(d[53]), "+f"(d[54]), "+f"(d[55]), "+f"(d[56]), "+f"(d[57]), "+f"(d[58]), "+f"(d[59]), "+f"(d[60]), "+f"(d[61]), "+f"(d[62]), "+f"(d[63])
    : "l"(da), "l"(db));
}
DEVI void wgmma_qk64(float (&d)[32], uint32_t a0, uint32_t a1, uint32_t a2, uint32_t a3, uint64_t db) {
  asm volatile("wgmma.mma_async.sync.aligned.m64n64k16.f32.bf16.bf16 {%0, %1, %2, %3, %4, %5, %6, %7, %8, %9, %10, %11, %12, %13, %14, %15, %16, %17, %18, %19, %20, %21, %22, %23, %24, %25, %26, %27, %28, %29, %30, %31}, {%32, %33, %34, %35}, %36, 0, 1, 1, 0;"
    : "=f"(d[0]), "=f"(d[1]), "=f"(d[2]), "=f"(d[3]), "=f"(d[4]), "=f"(d[5]), "=f"(d[6]), "=f"(d[7]), "=f"(d[8]), "=f"(d[9]), "=f"(d[10]), "=f"(d[11]), "=f"(d[12]), "=f"(d[13]), "=f"(d[14]), "=f"(d[15]), "=f"(d[16]), "=f"(d[17]), "=f"(d[18]), "=f"(d[19]), "=f"(d[20]), "=f"(d[21]), "=f"(d[22]), "=f"(d[23]), "=f"(d[24]), "=f"(d[25]), "=f"(d[26]), "=f"(d[27]), "=f"(d[28]), "=f"(d[29]), "=f"(d[30]), "=f"(d[31])
    : "r"(a0), "r"(a1), "r"(a2), "r"(a3), "l"(db));
}
DEVI void wgmma_pv(float (&d)[8], uint32_t a0, uint32_t a1, uint32_t a2, uint32_t a3, uint64_t db) {
  asm volatile("wgmma.mma_async.sync.aligned.m64n16k16.f32.bf16.bf16 {%0, %1, %2, %3, %4, %5, %6, %7}, {%8, %9, %10, %11}, %12, 1, 1, 1, 1;"
    : "+f"(d[0]), "+f"(d[1]), "+f"(d[2]), "+f"(d[3]), "+f"(d[4]), "+f"(d[5]), "+f"(d[6]), "+f"(d[7])
    : "r"(a0), "r"(a1), "r"(a2), "r"(a3), "l"(db));
}
DEVI void wgmma_pv0(float (&d)[8], uint32_t a0, uint32_t a1, uint32_t a2, uint32_t a3, uint64_t db) {
  asm volatile("wgmma.mma_async.sync.aligned.m64n16k16.f32.bf16.bf16 {%0, %1, %2, %3, %4, %5, %6, %7}, {%8, %9, %10, %11}, %12, 0, 1, 1, 1;"
    : "=f"(d[0]), "=f"(d[1]), "=f"(d[2]), "=f"(d[3]), "=f"(d[4]), "=f"(d[5]), "=f"(d[6]), "=f"(d[7])
    : "r"(a0), "r"(a1), "r"(a2), "r"(a3), "l"(db));
}

template <int N> struct Acc { float a[64]; float b[(N - 128) / 2]; DEVI float& operator[](int i) { return i < 64 ? a[i] : b[i - 64]; } };
template <> struct Acc<128> { float a[64]; DEVI float& operator[](int i) { return a[i]; } };
template <int N> DEVI void wgmma_ss(Acc<N>& d, uint64_t da, uint64_t db) {
  wgmma_ss_n128(d.a, da, db);
  if constexpr (N == 192) wgmma_ss_n64(d.b, da, db + 256);
  if constexpr (N == 256) wgmma_ss_n128(d.b, da, db + 256);
}

DEVI int oh_chunk(int j, int i, int& need) {
  if (j & 1) {
    if (i >= 3 && i < 7) { need = 16 + 2 * (i - 3); return 24 + (i - 3); }
    if (i >= 7) i -= 4;
  }
  const int g = i / 3, o = (j + 2 * g) & 7;
  need = o;
  return 3 * o + (i - 3 * g);
}

DEVI int a_slot(int e, int ebig) { return e < ebig ? 1 + (e & 3) : (e - ebig + 5) & 7; }

struct Ctx {
  uint32_t sbase, bars, peer, t0, a16, b16;
  int wg, lane;
  int ai, bi; uint32_t aph, bph;
  int brem, ae;
  int pa, pb;
};

DEVI void release_prev(Ctx& c) {
  if (c.pb >= 0) {
    if (c.lane == 0) mbar_arrive(c.bars + 8 * (BAR_EMPTYB + c.pb));
    if (c.lane == 1) mbar_arrive_cluster(c.bars + 8 * (BAR_EMPTYB + c.pb), c.peer);
  }
  if (c.pa >= 0 && c.lane == 2) mbar_arrive(c.bars + 8 * (BAR_EMPTYA + c.pa));
}

DEVI void gemm_wait(Ctx& c) {
  asm volatile("{ .reg .pred p, q; .reg .u32 c;\n"
               "WAIT_%=:\n"
               "mbarrier.try_wait.parity.shared::cta.b64 p, [%0], %1;\n"
               "mbarrier.try_wait.parity.shared::cta.b64 q, [%2], %3;\n"
               "and.pred p, p, q;\n"
               "@p bra DONE_%=;\n"
               "mov.u32 c, %%clock; sub.u32 c, c, %4; setp.lt.u32 p, c, %5;\n"
               "@p bra WAIT_%=;\n"
               "DONE_%=: }" ::"r"(c.bars + 8 * (BAR_FULLA + c.ai)), "r"((c.aph >> c.ai) & 1), "r"(c.bars + 8 * (BAR_FULLB + c.bi)), "r"(c.bph), "r"(c.t0), "n"(TIMEOUT) : "memory");
}
template <int N>
DEVI void gemm_group(Acc<N>& acc, Ctx& c, int g, int& npa, int& npb) {
  const uint32_t a16 = c.a16 + c.ai * (SLOT >> 4);
  const uint32_t b16 = c.b16 + c.bi * (SLOT >> 4);
  bool adv;
  if constexpr (N >= 192) {
    const uint32_t a2 = a16 + (g & 1) * 4;
    wgmma_ss<N>(acc, desc_sw128<16>(a2), desc_sw128<2048>(b16));
    wgmma_ss<N>(acc, desc_sw128<16>(a2 + 2), desc_sw128<2048>(b16 + 512));
    adv = g & 1;
  } else {
#pragma unroll
    for (int s = 0; s < 4; s++) wgmma_ss<N>(acc, desc_sw128<16>(a16 + s * 2), desc_sw128<4096>(b16 + (s >> 1) * 512 + (s & 1) * 128));
    adv = true;
  }
  wgmma_commit();
  npb = c.brem > 0 ? c.bi : -1;
  c.brem--;
  if (++c.bi == NB) { c.bi = 0; c.bph ^= 1; }
  npa = -1;
  if (adv) { npa = c.ai; c.aph ^= 1u << c.ai; c.ae++; c.ai = 1 + (c.ae & 3); }
}

template <int N>
DEVI void bare_groups(Acc<N>& acc, Ctx& c, int g0, int g1) {
  for (int g = g0; g < g1; g++) {
    int npa, npb;
    gemm_wait(c);
    wgmma_fence();
    gemm_group<N>(acc, c, g, npa, npb);
    wgmma_wait<1>();
    release_prev(c);
    c.pa = npa; c.pb = npb;
  }
}
DEVI void drain(Ctx& c) {
  wgmma_wait<0>();
  release_prev(c);
  c.pa = c.pb = -1;
}

constexpr float SC = 0.25f * 1.4426950408889634f;

#define ONCE _Pragma("unroll 1") for (unsigned once_ = 0; once_ < gridDim.y; once_++)

struct Gate { float g0, g1; };

DEVI void kill32(float (&S)[32]) {
#pragma unroll
  for (int i = 0; i < 32; i++) S[i] = __int_as_float(0xff800000);
}
DEVI void row_max(const float (&S)[32], float& x0, float& x1) {
  float y0 = S[1], y1 = S[3];
  x0 = fmaxf(x0, S[0]); x1 = fmaxf(x1, S[2]);
#pragma unroll
  for (int n = 1; n < 8; n++) {
    x0 = fmaxf(x0, S[4 * n]); y0 = fmaxf(y0, S[4 * n + 1]); x1 = fmaxf(x1, S[4 * n + 2]); y1 = fmaxf(y1, S[4 * n + 3]);
  }
  x0 = fmaxf(x0, y0); x1 = fmaxf(x1, y1);
}
DEVI void quad_max(float& x0, float& x1) {
  x0 = fmaxf(x0, __shfl_xor_sync(0xffffffffu, x0, 1)); x1 = fmaxf(x1, __shfl_xor_sync(0xffffffffu, x1, 1));
  x0 = fmaxf(x0, __shfl_xor_sync(0xffffffffu, x0, 2)); x1 = fmaxf(x1, __shfl_xor_sync(0xffffffffu, x1, 2));
}
DEVI void exp32(const float (&S)[32], float (&E)[32], float n0, float n1, float (&l)[4]) {
#pragma unroll
  for (int i = 0; i < 32; i++) { E[i] = ex2(fmaf(S[i], SC, (i & 2) ? n1 : n0)); l[i & 3] += E[i]; }
}
DEVI void pack32(const float (&E)[32], uint32_t (&P)[16]) {
#pragma unroll
  for (int i = 0; i < 16; i++) P[i] = pack_bf16(E[2 * i], E[2 * i + 1]);
}
template <bool FIRST> DEVI void pv4(float (&O)[8], const uint32_t (&P)[16], uint32_t v16) {
  if (FIRST) wgmma_pv0(O, P[0], P[1], P[2], P[3], desc_sw64(v16)); else wgmma_pv(O, P[0], P[1], P[2], P[3], desc_sw64(v16));
#pragma unroll
  for (int k = 1; k < 4; k++) wgmma_pv(O, P[4 * k], P[4 * k + 1], P[4 * k + 2], P[4 * k + 3], desc_sw64(v16 + k * 64));
}
DEVI bool wg_any(int wg, bool v) {
  uint32_t r;
  if (wg == 0) asm volatile("{ .reg .pred p, q; setp.ne.u32 p, %1, 0; bar.red.or.pred q, 4, 128, p; selp.u32 %0, 1, 0, q; }" : "=r"(r) : "r"((uint32_t)v) : "memory");
  else asm volatile("{ .reg .pred p, q; setp.ne.u32 p, %1, 0; bar.red.or.pred q, 5, 128, p; selp.u32 %0, 1, 0, q; }" : "=r"(r) : "r"((uint32_t)v) : "memory");
  return r != 0;
}
DEVI void get_gate(Gate& g, uint32_t sbase, int row16, int lane, uint32_t t0) {
  mbar_wait(sbase + OFF_BAR + 8 * BAR_GIN, 0, t0);
  const uint32_t a = sbase + OFF_GIN + (row16 * 16 + (lane >> 2)) * 4;
  asm volatile("ld.shared.f32 %0, [%1];" : "=f"(g.g0) : "r"(a) : "memory");
  asm volatile("ld.shared.f32 %0, [%1];" : "=f"(g.g1) : "r"(a + 32) : "memory");
}

DEVI void attention(uint32_t sbase, int aw, int wi, int lane, int rb, uint32_t t0) {
  const uint32_t bars = sbase + OFF_BAR;
  const uint32_t kvb = ((sbase & 0x3FFFF) + OFF_KV + aw * 4096) >> 4;
  const int cmin = 4 - 2 * rb - aw;
  const int rowc = wi * 16 + (lane >> 2) - (lane & 3) * 2;
  const uint32_t qst = sbase + OFF_A + aw * 8192;
  const float NINF = __int_as_float(0xff800000);
  float xt0 = NINF, xt1 = NINF;
  int h = 0;
  mbar_wait(bars + 8 * (BAR_QRDY + aw), 0, t0);
#pragma unroll 1
  while (h < 4) {
    const uint32_t kb = kvb + (h & 1) * (KVBUF >> 4);
    const uint4 q = lds128(qst + h * 2048 + (wi * 32 + lane) * 16);
    float O[8], l[4] = {0.f, 0.f, 0.f, 0.f}, n0, n1;
    uint32_t P[16];
    mbar_wait(bars + 8 * (BAR_KVFULL + (h & 1)), h >> 1, t0);
    {
      float S[32], F[32];
      wgmma_fence();
      wgmma_qk64(S, q.x, q.y, q.z, q.w, desc_sw64(kb + 4 * 256));
      wgmma_qk64(F, q.x, q.y, q.z, q.w, desc_sw64(kb));
      wgmma_commit();
      wgmma_wait<0>();
      if (cmin > 0) kill32(F);
      float M[32];
#pragma unroll
      for (int i = 0; i < 32; i++) M[i] = ((i >> 2) * 8 + (i & 1) > rowc + (i & 2) * 4) ? F[i] : S[i];
      float x0 = xt0, x1 = xt1;
      row_max(M, x0, x1);
      quad_max(x0, x1);
      n0 = -x0 * SC; n1 = -x1 * SC;
      exp32(M, M, n0, n1, l);
      pack32(M, P);
      uint32_t PF[16];
#pragma unroll
      for (int i = 0; i < 16; i++) {
        const int col = (i >> 1) * 8, r = rowc + (i & 1) * 8;
        const uint32_t m = (col > r ? 0xFFFFu : 0u) | (col + 1 > r ? 0xFFFF0000u : 0u);
        PF[i] = P[i] & m; P[i] &= ~m;
      }
      wgmma_fence();
      pv4<true>(O, PF, kb + 2);
      wgmma_commit();
      wgmma_wait<0>();
    }
#pragma unroll 1
    for (int t = 3; t >= 1; t--) {
      float S[32], E[32];
      wgmma_fence();
      wgmma_qk64(S, q.x, q.y, q.z, q.w, desc_sw64(kb + t * 256));
      wgmma_commit();
      pv4<false>(O, P, kb + (t + 1) * 256 + 2);
      wgmma_commit();
      wgmma_wait<1>();
      if (t < cmin) kill32(S);
      exp32(S, E, n0, n1, l);
      wgmma_wait<0>();
      pack32(E, P);
    }
    wgmma_fence();
    pv4<false>(O, P, kb + 256 + 2);
    wgmma_commit();
    float l0 = l[0] + l[1], l1 = l[2] + l[3];
    l0 += __shfl_xor_sync(0xffffffffu, l0, 1); l1 += __shfl_xor_sync(0xffffffffu, l1, 1);
    l0 += __shfl_xor_sync(0xffffffffu, l0, 2); l1 += __shfl_xor_sync(0xffffffffu, l1, 2);
    const bool exact = xt0 != NINF || cmin > 3;
    const bool redo = wg_any(aw, !exact && !(l0 < 1e18f && l1 < 1e18f));
    wgmma_wait<0>();
    if (redo) {
      xt0 = -3.0e38f; xt1 = -3.0e38f;
#pragma unroll 1
      for (int t = 3; t >= 1 && t >= cmin; t--) {
        float S[32];
        wgmma_fence();
        wgmma_qk64(S, q.x, q.y, q.z, q.w, desc_sw64(kb + t * 256));
        wgmma_commit();
        wgmma_wait<0>();
        row_max(S, xt0, xt1);
      }
      continue;
    }
    if (lane == 0) mbar_arrive(bars + 8 * (h == 3 ? BAR_ATTDONE : BAR_KVEMPTY + (h & 1)));
    Gate g;
    get_gate(g, sbase, aw * 4 + wi, lane, t0);
    const float c0 = __fdividef(g.g0, l0), c1 = __fdividef(g.g1, l1);
    const int mi = lane >> 3;
    const int srow = wi * 16 + (lane & 7) + 8 * (mi & 1);
    stsm_x4(qst + h * 2048 + srow * 32 + (mi >> 1) * 16, pack_bf16(O[0] * c0, O[1] * c0), pack_bf16(O[2] * c1, O[3] * c1),
            pack_bf16(O[4] * c0, O[5] * c0), pack_bf16(O[6] * c1, O[7] * c1));
    fence_async_smem();
    __syncwarp();
    if (lane == 0) mbar_arrive(bars + 8 * (BAR_OST + aw));
    xt0 = NINF; xt1 = NINF;
    h++;
  }
}

template <int CH, int N>
DEVI void store_h_chunk(Acc<N>& acc, uint32_t base  , int lane, float s0, float s1) {
  const int mi = lane >> 3;
#pragma unroll
  for (int tp = 0; tp < 4; tp++) {
    const int t = CH * 8 + tp * 2;
    const uint32_t r0 = pack_bf16(fmaxf(acc[4 * t + 0], 0.f) * s0, fmaxf(acc[4 * t + 1], 0.f) * s0);
    const uint32_t r1 = pack_bf16(fmaxf(acc[4 * t + 2], 0.f) * s1, fmaxf(acc[4 * t + 3], 0.f) * s1);
    const uint32_t r2 = pack_bf16(fmaxf(acc[4 * t + 4], 0.f) * s0, fmaxf(acc[4 * t + 5], 0.f) * s0);
    const uint32_t r3 = pack_bf16(fmaxf(acc[4 * t + 6], 0.f) * s1, fmaxf(acc[4 * t + 7], 0.f) * s1);
    stsm_x4(base + (((tp * 2 + (mi >> 1)) ^ (lane & 7)) << 4), r0, r1, r2, r3);
  }
}

template <int N>
DEVI void phase_q(Ctx& c, int warp) {
  Acc<N> acc;
#pragma unroll
  for (int i = 0; i < N / 2; i++) acc[i] = 0.f;
  bare_groups<N>(acc, c, 0, 16);
  drain(c);
  const int lane = c.lane, mi = lane >> 3;
  const int row = warp * 16 + (lane & 7) + 8 * (mi & 1);
  const int sw = (row >> 1) & 3;
#pragma unroll
  for (int hh = 0; hh < 4; hh++) {
    const uint32_t base = c.sbase + OFF_KV + hh * 8192 + row * 64;
#pragma unroll
    for (int kv = 0; kv < 2; kv++) {
      const int t = 8 + kv * 8 + 2 * hh;
      stsm_x4(base + (((kv * 2 + (mi >> 1)) ^ sw) << 4),
              pack_bf16(acc[4 * t + 0], acc[4 * t + 1]), pack_bf16(acc[4 * t + 2], acc[4 * t + 3]),
              pack_bf16(acc[4 * t + 4], acc[4 * t + 5]), pack_bf16(acc[4 * t + 6], acc[4 * t + 7]));
    }
  }
  fence_async_smem();
  __syncwarp();
  if (lane == 0) mbar_arrive(c.bars + 8 * BAR_STG);
#pragma unroll
  for (int hh = 0; hh < 4; hh++)
    sts128(c.sbase + OFF_A + c.wg * 8192 + hh * 2048 + ((warp & 3) * 32 + lane) * 16,
           pack_bf16(acc[8 * hh], acc[8 * hh + 1]), pack_bf16(acc[8 * hh + 2], acc[8 * hh + 3]),
           pack_bf16(acc[8 * hh + 4], acc[8 * hh + 5]), pack_bf16(acc[8 * hh + 6], acc[8 * hh + 7]));
  __syncwarp();
  if (lane == 0) mbar_arrive(c.bars + 8 * (BAR_QRDY + c.wg));
  if constexpr (N == 256) {
    Gate g;
    get_gate(g, c.sbase, warp, lane, c.t0);
    store_h_chunk<3>(acc, c.sbase + OFF_KV + 32768 + row * 128, lane, 1.f - g.g0, 1.f - g.g1);
    fence_async_smem();
    __syncwarp();
    if (lane == 0) mbar_arrive(c.bars + 8 * BAR_STE);
  }
}

DEVI void first_loads(const Params& P, uint32_t sbase, int e, int j, int rb) {
  const uint32_t bars = sbase + OFF_BAR, fb = bars + 8 * (BAR_FULLB + e), fa = bars + 8 * (BAR_FULLA + 1 + e);
  mbar_expect_tx(fa, 16384);
  mbar_expect_tx(fb, (j & 1) ? 12288 : 16384);
  if (e == 0) tma_load_2d(sbase + OFF_A + SLOT, &P.tmX, 0, rb * 128, fa);
#pragma unroll
  for (int r = 0; r < 2; r++) {
    tma_load_3d(sbase + OFF_B + e * SLOT + r * 8192, &P.tmWqkv, 64 * j, e * 32 + r * 16, 0, fb);
    if (!(j & 1)) tma_load_3d(sbase + OFF_B + e * SLOT + r * 8192 + 6144, &P.tmW1a, 0, e * 32 + r * 16, 24 + (j >> 1), fb);
  }
  if (e == 1) tma_load_2d(sbase + OFF_A + 2 * SLOT, &P.tmX, 64, rb * 128, fa);
}

__global__ void __cluster_dims__(2, 1, 1) __launch_bounds__(640, 1) fused_kernel(const __grid_constant__ Params P) {
  extern __shared__ uint8_t smem_raw[];
  const uint32_t sbase = (smem_u32(smem_raw) + 1023u) & ~1023u;
  const uint32_t bars = sbase + OFF_BAR;
  const int tid = threadIdx.x, warp = tid >> 5, lane = tid & 31;
  const uint32_t rank = blockIdx.x & 1, peer = rank ^ 1;
  const int j = (blockIdx.x >> 1) & 7, rb = ((blockIdx.x >> 4) << 1) | rank;
  const uint32_t t0 = clk32();

  const int typeB = j & 1;
  if (tid == 544) {
    for (int s = 0; s < NA2; s++) mbar_init(bars + 8 * (BAR_FULLA + s), 1);
    for (int s = 0; s < NB; s++) mbar_init(bars + 8 * (BAR_FULLB + s), 1);
    fence_async_smem();
  } else if (tid < 10) {
    asm volatile("prefetch.tensormap [%0];" ::"l"(&P.tmX + tid) : "memory");
  } else if (tid == 512) {
    for (int s = 0; s < NA2; s++) mbar_init(bars + 8 * (BAR_EMPTYA + s), 9);
    for (int s = 0; s < NB; s++) mbar_init(bars + 8 * (BAR_EMPTYB + s), 16);
  } else if (tid == 576) {
    for (int s = 0; s < 2; s++) { mbar_init(bars + 8 * (BAR_KVFULL + s), 1); mbar_init(bars + 8 * (BAR_KVEMPTY + s), 8); mbar_init(bars + 8 * (BAR_OST + s), 4); mbar_init(bars + 8 * (BAR_QRDY + s), 4); }
    mbar_init(bars + 8 * BAR_STG, 8); mbar_init(bars + 8 * BAR_STE, 8); mbar_init(bars + 8 * BAR_KVOK, 1);
    mbar_init(bars + 8 * BAR_PIN, 1); mbar_init(bars + 8 * BAR_ATTDONE, 8); mbar_init(bars + 8 * BAR_GIN, 1); mbar_init(bars + 8 * BAR_GATE, 1); mbar_init(bars + 8 * (BAR_GATE + 1), 1);
  }
  if (tid >= 512 && lane == 0) asm volatile("fence.mbarrier_init.release.cluster;" ::: "memory");
  const unsigned ep1 = ld_relaxed(&g_epoch) + 1;
  __syncwarp();
  cluster_arrive();
  if (tid == 544) { first_loads(P, sbase, 0, j, rb); first_loads(P, sbase, 1, j, rb); }
  __syncwarp();

  const int on = 12 + 4 * typeB;

  if (warp < 8) {
    asm volatile("setmaxnreg.inc.sync.aligned.u32 160;");
    cluster_wait();
    const int wg = __shfl_sync(0xffffffffu, warp >> 2, 0), wi = warp & 3;
    Ctx c{sbase, bars, peer, t0, ((sbase & 0x3FFFF) + OFF_A + wg * 8192) >> 4, ((sbase & 0x3FFFF) + OFF_B) >> 4, wg, lane, 1, 0, 0u, 0u, 32 + on + 4 - NB, 0, -1, -1};
    if (tid == 0) TR(0);
    if (typeB) phase_q<192>(c, warp);
    else phase_q<256>(c, warp);
    asm volatile("setmaxnreg.dec.sync.aligned.u32 128;");
    if (tid == 0) TR(2);
    {
      Acc<192> acc;
#pragma unroll
      for (int i = 0; i < 96; i++) acc[i] = 0.f;
      bare_groups<192>(acc, c, 0, 16);
      Gate at;
      get_gate(at, sbase, warp, lane, t0);
      drain(c);
      if (tid == 0) TR(1);
      const uint32_t rowoff = (warp * 16 + (lane & 7) + 8 * ((lane >> 3) & 1)) * 128;
      const float s0 = 1.f - at.g0, s1 = 1.f - at.g1;
      constexpr int e0 = 1, e1 = 2, e2 = 3;
      mbar_wait(bars + 8 * (BAR_FULLA + e0), 0, t0);
      store_h_chunk<0>(acc, sbase + OFF_A + e0 * SLOT + rowoff, lane, s0, s1);
      mbar_wait(bars + 8 * (BAR_FULLA + e1), 0, t0);
      store_h_chunk<1>(acc, sbase + OFF_A + e1 * SLOT + rowoff, lane, s0, s1);
      mbar_wait(bars + 8 * (BAR_FULLA + e2), 0, t0);
      store_h_chunk<2>(acc, sbase + OFF_A + e2 * SLOT + rowoff, lane, s0, s1);
    }
    fence_async_smem();
    wg_bar(wg);
    if (lane == 0) mbar_arrive(bars + 8 * BAR_STG);
    if (tid == 0) TR(4);
    float own[32];
    {
      Acc<128> acc;
#pragma unroll
      for (int i = 0; i < 64; i++) acc[i] = 0.f;
      bare_groups<128>(acc, c, 0, on);
      drain(c);
      if (tid == 0) TR(5);
      named_bar<3>(256);
      const uint32_t pst = sbase + OFF_B + ((30 + on) % NB) * SLOT + wg * 8192 + (tid & 127) * 16;
#pragma unroll
      for (int i = 0; i < 4; i++) {
        uint32_t r[4];
#pragma unroll
        for (int k = 0; k < 4; k++) {
          const int idx = 8 * i + 2 * k;
          const float lo = typeB ? acc[idx] : acc[32 + idx], hi = typeB ? acc[idx + 1] : acc[32 + idx + 1];
          r[k] = pack_bf16(lo, hi);
        }
        sts128(pst + i * 2048, r[0], r[1], r[2], r[3]);
      }
#pragma unroll
      for (int i = 0; i < 32; i++) own[i] = typeB ? acc[32 + i] : acc[i];
      fence_async_smem();
      __syncwarp();
      if (lane == 0) mbar_arrive(bars + 8 * BAR_STG);
    }
    for (int g = 0; g < 8; g++) {
      const uint32_t a16 = c.a16 + c.ai * (SLOT >> 4);
      const uint32_t b16 = c.b16 + c.bi * (SLOT >> 4) + (g & 1) * 512;
      gemm_wait(c);
      wgmma_fence();
#pragma unroll
      for (int s = 0; s < 4; s++) wgmma_ss_n64(own, desc_sw128<16>(a16 + s * 2), desc_sw128<2048>(b16 + s * 128));
      wgmma_commit();
      c.ae++; c.ai = a_slot(c.ae, 20 + on);
      if (g & 1) { if (++c.bi == NB) { c.bi = 0; c.bph ^= 1; } }
    }
    wgmma_wait<0>();
    if (tid == 0) TR(6);
    mbar_wait(bars + 8 * BAR_PIN, 0, t0);
    if (tid == 0) TR(7);
    {
      const uint32_t pin = sbase + OFF_B + ((31 + on) % NB) * SLOT + wg * 8192 + (tid & 127) * 16;
      wg_bar(wg);
      const uint32_t ob = sbase + OFF_A + SLOT + wg * 8192;
      const uint32_t orow = ob + (wi * 16 + (lane & 7) + 8 * ((lane >> 3) & 1)) * 128;
#pragma unroll
      for (int i = 0; i < 4; i++) {
        const uint4 v = lds128(pin + i * 2048);
        const uint32_t r[4] = {v.x, v.y, v.z, v.w};
        uint32_t o[4];
#pragma unroll
        for (int k = 0; k < 4; k++) {
          const int idx = 8 * i + 2 * k;
          o[k] = pack_bf16(own[idx] + __uint_as_float(r[k] << 16), own[idx + 1] + __uint_as_float(r[k] & 0xffff0000u));
        }
        stsm_x4(orow + (((i * 2 + (lane >> 4)) ^ (lane & 7)) << 4), o[0], o[1], o[2], o[3]);
      }
      fence_async_smem();
      __syncwarp();
      if (lane == 0) {
        tma_store_2d(&P.tmOut, j * 64, rb * 128 + warp * 16, ob + wi * 2048);
        bulk_commit();
        asm volatile("cp.async.bulk.wait_group.read 0;" ::: "memory");
      }
    }
    if (tid == 0) TR(8);
  } else if (warp < 16) {
    asm volatile("setmaxnreg.dec.sync.aligned.u32 56;");
    cluster_wait();
    const int aw = __shfl_sync(0xffffffffu, (warp >> 2) & 1, 0);
    mbar_wait(bars + 8 * (BAR_QRDY + aw), 0, t0);
    asm volatile("setmaxnreg.inc.sync.aligned.u32 96;");
    attention(sbase, aw, warp & 3, lane, rb, t0);
    if (tid == 256) TR(3);
  } else {
    asm volatile("setmaxnreg.dec.sync.aligned.u32 32;");
    if (warp == 16) {
      __syncwarp();
      cluster_wait();
      if (lane == 0) {
        int bi = 2; uint32_t bph = 1;
        const int nb = 32 + on + 4;
        for (int eb = 2; eb < nb; eb++) {
          if (eb == 4 || eb == 6) {
            const int ea = eb >> 1;
            mbar_expect_tx(bars + 8 * (BAR_FULLA + 1 + ea), 16384);
            tma_load_2d(sbase + OFF_A + (1 + ea) * SLOT, &P.tmX, ea * 64, rb * 128, bars + 8 * (BAR_FULLA + 1 + ea));
          }
          const uint32_t fb = bars + 8 * (BAR_FULLB + bi), dst = sbase + OFF_B + bi * SLOT + rank * 8192;
          mbar_wait(bars + 8 * (BAR_EMPTYB + bi), bph, t0);
          if (eb < 16) {
            mbar_expect_tx(fb, typeB ? 12288 : 16384);
            tma_load_3d_mc(dst, &P.tmWqkv, 64 * j, eb * 32 + rank * 16, 0, fb);
            if (!typeB) tma_load_3d_mc(dst + 6144, &P.tmW1a, 0, eb * 32 + rank * 16, 24 + (j >> 1), fb);
          }
          else if (eb < 32) { mbar_expect_tx(fb, 12288); tma_load_3d_mc(dst, &P.tmW1b, 0, (eb - 16) * 32 + rank * 16, 3 * j, fb); }
          else if (eb < 32 + on) { int ow; const int ch = oh_chunk(j, eb - 32, ow); mbar_expect_tx(fb, 16384); tma_load_3d_mc(dst, &P.tmW2, 0, ch * 64 + rank * 32, (j >> 1) * 2, fb); }
          else { mbar_expect_tx(fb, 16384); tma_load_4d_mc(dst, &P.tmWo, 64 * j, 0, eb - 32 - on, rank * 4, fb); }
          if (++bi == NB) { bi = 0; bph ^= 1; }
          if (eb == PFAT) {
            const int b = blockIdx.x;
            l2_prefetch((const uint8_t*)P.w1 + b * 14336, 14336);
            l2_prefetch((const uint8_t*)P.w2 + b * 14336, 14336);
            l2_prefetch((const uint8_t*)P.wo + b * 4096, 4096);
          }
        }
      }
    } else if (warp == 17) {
      cluster_wait();
      if (lane == 0) {
        for (int ea = 1; ea < 5; ea++) mbar_arrive(bars + 8 * (BAR_EMPTYA + ea));
        uint32_t aph = 0xE1;
        const int na = 16 + on + 8;
        unsigned ready = 0;
        for (int ea = 4; ea < na; ea++) {
          const int ai = a_slot(ea, 20 + on);
          const uint32_t fb = bars + 8 * (BAR_FULLA + ai), dst = sbase + OFF_A + ai * SLOT;
          int ch = ea & 7, need = -1;
          if (ea >= 16 + on) { need = 8 + ea - 16 - on; ch = 20 + need; }
          else if (ea >= 19) ch = oh_chunk(j, ea - 16, need);
          if (need >= 0 && !((ready >> need) & 1)) {
            const unsigned* fp = need < 8 ? &g_flag_h[rb * 8 * FS] : need < 16 ? &g_flag_o[rb * 8 * FS] : &g_flag_e[rb * 8 * FS];
            const unsigned tgt = (need & 8) ? ep1 * 4 : ep1;
            do {
              unsigned v[8];
#pragma unroll
              for (int i = 0; i < 8; i++) v[i] = ld_relaxed(fp + i * FS);
#pragma unroll
              for (int i = 0; i < 8; i++) if ((int)(v[i] - tgt) >= 0) ready |= 1u << (i + (need & 24));
            } while (!((ready >> need) & 1) && clk32() - t0 < TIMEOUT);
            fence_async_global();
          }
          if (ea == 20 + on) mbar_wait(bars + 8 * BAR_ATTDONE, 0, t0);
          mbar_wait(bars + 8 * (BAR_EMPTYA + ai), (aph >> ai) & 1, t0);
          if (ea >= 16 && ea < 19) mbar_arrive(fb);
          else {
            mbar_arrive(bars + 8 * (BAR_EMPTYA + ai));
            mbar_expect_tx(fb, 16384);
            tma_load_2d(dst, ea < 16 ? &P.tmX : &P.tmHO, ch * 64, rb * 128, fb);
          }
          TR(24 + ea);
          aph ^= 1u << ai;
        }
      }
    } else {
      const int wg = warp - 18;
      cluster_wait();
      {
        const int rowg = rb * 128 + j * 16 + wg * 8;
        const uint32_t xs = sbase + OFF_KV + 32768 + wg * 8192;
        if (lane == 0) {
          mbar_wait(bars + 8 * (BAR_FULLB + 1), 0, t0);
          mbar_expect_tx(bars + 8 * (BAR_GATE + wg), 8192);
          bulk_load(xs, P.x + (size_t)rowg * DM, 8192, bars + 8 * (BAR_GATE + wg));
        }
        const uint4* gw = (const uint4*)P.gate_w;
        const uint4 w0 = __ldg(gw + lane), w1 = __ldg(gw + 32 + lane);
        const uint32_t wa[8] = {w0.x, w0.y, w0.z, w0.w, w1.x, w1.y, w1.z, w1.w};
        mbar_wait(bars + 8 * (BAR_GATE + wg), 0, t0);
        float zz = 0.f;
#pragma unroll 1
        for (int i = 0; i < 8; i++) {
          const uint4 x0 = lds128(xs + i * 1024 + lane * 16), x1 = lds128(xs + i * 1024 + 512 + lane * 16);
          const uint32_t xa[8] = {x0.x, x0.y, x0.z, x0.w, x1.x, x1.y, x1.z, x1.w};
          float z = 0.f;
#pragma unroll
          for (int e = 0; e < 8; e++) {
            z = fmaf(__uint_as_float(xa[e] << 16), __uint_as_float(wa[e] << 16), z);
            z = fmaf(__uint_as_float(xa[e] & 0xffff0000u), __uint_as_float(wa[e] & 0xffff0000u), z);
          }
#pragma unroll
          for (int o = 16; o > 0; o >>= 1) z += __shfl_xor_sync(0xffffffffu, z, o);
          if (lane == i) zz = z;
        }
        if (lane < 8) asm volatile("st.shared.f32 [%0], %1;" ::"r"(sbase + OFF_GST + wg * 32 + lane * 4), "f"(1.f / (1.f + __expf(-zz))) : "memory");
        fence_async_smem();
        __syncwarp();
        if (lane == 0) {
          bulk_store(&g_gate[rowg], sbase + OFF_GST + wg * 32, 32);
          bulk_commit(); bulk_wait_all();
          flag_add(&g_flag_g[rb * FS]);
          if (wg == 1) {
            flag_wait(&g_flag_g[rb * FS], ep1 * 16, t0);
            fence_async_global();
            mbar_expect_tx(bars + 8 * BAR_GIN, 512);
            bulk_load(sbase + OFF_GIN, &g_gate[rb * 128], 512, bars + 8 * BAR_GIN);
          }
          if (wg == 0) TR(10);
        }
      }
      if (lane == 0 && wg == 0) {
        const uint32_t stg = bars + 8 * BAR_STG;
        mbar_wait(stg, 0, t0);
        for (int hh = 0; hh < 4; hh++) bulk_store(g_kv + ((size_t)(4 * j + hh) * SEQ + rb * 128) * 64, sbase + OFF_KV + hh * 8192, 8192);
        bulk_commit(); bulk_wait_all();
        flag_add(&g_flag_kv[(rb * 8 + j) * FS]);
        TR(21);
        if (!typeB) {
          mbar_wait(bars + 8 * BAR_STE, 0, t0);
          tma_store_2d(&P.tmHO, (24 + (j >> 1)) * 64, rb * 128, sbase + OFF_KV + 32768);
          bulk_commit(); bulk_wait_all();
          flag_add(&g_flag_e[(rb * 8 + j) * FS]);
        }
        mbar_arrive(bars + 8 * BAR_KVOK);
        mbar_wait(stg, 1, t0);
        for (int i = 0; i < 3; i++) tma_store_2d(&P.tmHO, (3 * j + i) * 64, rb * 128, sbase + OFF_A + (1 + i) * SLOT);
        bulk_commit(); bulk_wait_all();
        flag_add(&g_flag_h[(rb * 8 + j) * FS]);
        for (int i = 0; i < 3; i++) mbar_arrive(bars + 8 * (BAR_EMPTYA + 1 + i));
        TR(22);
        {
          const unsigned old = atomicAdd(&g_done, 1u);
          if (old == gridDim.x - 1) { g_done = 0; *(volatile unsigned*)&g_epoch = ep1; }
        }
        mbar_wait(stg, 0, t0);
        bulk_store(g_part + (size_t)(rb * 8 + (j ^ 1)) * 16384, sbase + OFF_B + ((30 + on) % NB) * SLOT, 16384);
        bulk_commit(); bulk_wait_all();
        flag_add(&g_flag_p[(rb * 8 + (j ^ 1)) * FS]);
        TR(23);
        flag_wait(&g_flag_p[(rb * 8 + j) * FS], ep1, t0);
        fence_async_global();
        mbar_expect_tx(bars + 8 * BAR_PIN, 16384);
        bulk_load(sbase + OFF_B + ((31 + on) % NB) * SLOT, g_part + (size_t)(rb * 8 + j) * 16384, 16384, bars + 8 * BAR_PIN);
      } else if (lane == 0) {
        const int nblk = rb >= 2 ? 3 : rb + 1;
        const uint32_t kvbytes = nblk * 8192;
        const uint8_t* kvsrc = g_kv + ((size_t)(4 * j) * SEQ + (rb + 1 - nblk) * 128) * 64;
        const uint32_t kvdst = sbase + OFF_KV + (3 - nblk) * 8192;
        {
          const unsigned* f0 = &g_flag_kv[(rb * 8 + j) * FS];
          const unsigned* f1 = rb >= 1 ? f0 - 8 * FS : f0;
          const unsigned* f2 = rb >= 2 ? f0 - 16 * FS : f0;
          unsigned v0, v1, v2;
          do { v0 = ld_relaxed(f0); v1 = ld_relaxed(f1); v2 = ld_relaxed(f2); }
          while (((int)(v0 - ep1) < 0 || (int)(v1 - ep1) < 0 || (int)(v2 - ep1) < 0) && clk32() - t0 < TIMEOUT);
        }
        TR(11);
        fence_async_global();
        mbar_expect_tx(bars + 8 * BAR_KVFULL, kvbytes);
        bulk_load(kvdst, kvsrc, kvbytes, bars + 8 * BAR_KVFULL);
        mbar_wait(bars + 8 * BAR_KVOK, 0, t0);
        mbar_expect_tx(bars + 8 * (BAR_KVFULL + 1), kvbytes);
        bulk_load(kvdst + KVBUF, kvsrc + (size_t)SEQ * 64, kvbytes, bars + 8 * (BAR_KVFULL + 1));
        for (int hh = 0; hh < 4; hh++) {
          for (int aw = 0; aw < 2; aw++) {
            mbar_wait(bars + 8 * (BAR_OST + aw), hh & 1, t0);
            tma_store_2d(&P.tmOs, DFF + hh * 128 + j * 16, rb * 128 + aw * 64, sbase + OFF_A + aw * 8192 + hh * 2048);
          }
          bulk_commit();
          if (hh < 2) {
            mbar_wait(bars + 8 * (BAR_KVEMPTY + hh), 0, t0);
            mbar_expect_tx(bars + 8 * (BAR_KVFULL + hh), kvbytes);
            bulk_load(kvdst + hh * KVBUF, kvsrc + (size_t)(hh + 2) * SEQ * 64, kvbytes, bars + 8 * (BAR_KVFULL + hh));
          }
          bulk_wait_all();
          flag_add(&g_flag_o[(rb * 8 + hh * 2 + (j >> 2)) * FS]);
          TR(12 + hh);
        }
      }
    }
  }
}

typedef CUresult (*EncodeFn)(CUtensorMap*, CUtensorMapDataType, cuuint32_t, void*, const cuuint64_t*, const cuuint64_t*, const cuuint32_t*,
                             const cuuint32_t*, CUtensorMapInterleave, CUtensorMapSwizzle, CUtensorMapL2promotion, CUtensorMapFloatOOBfill);

void make_map(EncodeFn enc, CUtensorMap* m, const void* ptr, int rank, const cuuint64_t* dims, const cuuint64_t* strides, const cuuint32_t* box,
              CUtensorMapSwizzle sw = CU_TENSOR_MAP_SWIZZLE_128B) {
  cuuint32_t es[4] = {1, 1, 1, 1};
  enc(m, CU_TENSOR_MAP_DATA_TYPE_BFLOAT16, rank, const_cast<void*>(ptr), dims, strides, box, es, CU_TENSOR_MAP_INTERLEAVE_NONE, sw,
      CU_TENSOR_MAP_L2_PROMOTION_L2_256B, CU_TENSOR_MAP_FLOAT_OOB_FILL_NONE);
}

}

extern "C" void kernel_launch(void* const* d_in, const int* in_sizes, int n_in, void* d_out, int out_size) {
  (void)in_sizes; (void)n_in; (void)out_size;
  static EncodeFn enc = nullptr;
  static void* ho_ptr = nullptr;
  if (!enc) {
    void* fn = nullptr; cudaDriverEntryPointQueryResult st;
    cudaGetDriverEntryPoint("cuTensorMapEncodeTiled", &fn, cudaEnableDefault, &st);
    enc = (EncodeFn)fn;
    cudaGetSymbolAddress(&ho_ptr, g_ho);
    cudaFuncSetAttribute(fused_kernel, cudaFuncAttributeMaxDynamicSharedMemorySize, SMEM_BYTES);
  }
  const __nv_bfloat16* x = (const __nv_bfloat16*)d_in[0];
  const __nv_bfloat16* wqkv = (const __nv_bfloat16*)d_in[1];
  const __nv_bfloat16* wo = (const __nv_bfloat16*)d_in[2];
  const __nv_bfloat16* w1 = (const __nv_bfloat16*)d_in[4];
  const __nv_bfloat16* w2 = (const __nv_bfloat16*)d_in[5];
  const __nv_bfloat16* gate_w = (const __nv_bfloat16*)d_in[6];
  Params P;
  { cuuint64_t d[2] = {DM, SEQ}, s[1] = {DM * 2}; cuuint32_t b[2] = {64, 128}; make_map(enc, &P.tmX, x, 2, d, s, b); }
  { cuuint64_t d[3] = {512, 512, 3}, s[2] = {1536 * 2, 512 * 2}; cuuint32_t b[3] = {64, 16, 3}; make_map(enc, &P.tmWqkv, wqkv, 3, d, s, b); }
  { cuuint64_t d[3] = {64, 512, 28}, s[2] = {DFF * 2, 128}; cuuint32_t b[3] = {64, 16, 1}; make_map(enc, &P.tmW1a, w1, 3, d, s, b);
    b[2] = 3; make_map(enc, &P.tmW1b, w1, 3, d, s, b); }
  { cuuint64_t d[3] = {64, DFF, 8}, s[2] = {DM * 2, 128}; cuuint32_t b[3] = {64, 32, 2}; make_map(enc, &P.tmW2, w2, 3, d, s, b); }
  { cuuint64_t d[4] = {DM, 16, 4, 8}, s[3] = {DM * 2, 16 * DM * 2, 64 * DM * 2}; cuuint32_t b[4] = {64, 16, 1, 4}; make_map(enc, &P.tmWo, wo, 4, d, s, b); }
  { cuuint64_t d[2] = {KHO, SEQ}, s[1] = {KHO * 2}; cuuint32_t b[2] = {64, 128}; make_map(enc, &P.tmHO, ho_ptr, 2, d, s, b);
    b[1] = 64; make_map(enc, &P.tmHOs, ho_ptr, 2, d, s, b);
    b[0] = 16; make_map(enc, &P.tmOs, ho_ptr, 2, d, s, b, CU_TENSOR_MAP_SWIZZLE_NONE); }
  { cuuint64_t d[2] = {DM, SEQ}, s[1] = {DM * 2}; cuuint32_t b[2] = {64, 16}; make_map(enc, &P.tmOut, d_out, 2, d, s, b); }
  P.x = x; P.gate_w = gate_w; P.w1 = w1; P.w2 = w2; P.wo = wo; P.out = (__nv_bfloat16*)d_out;
  fused_kernel<<<128, 640, SMEM_BYTES>>>(P);
}
```

```cpp
#include <cuda_runtime.h>
#include <cuda_bf16.h>
#include <cuda.h>
#include <stdint.h>

#define DEVI __device__ __forceinline__

namespace {

constexpr int SEQ = 2048, DM = 512, DFF = 1792, KHO = 2304;
constexpr int NA = 5, NB = 6, SLOT = 16384, KVBUF = 24576;
constexpr int NA2 = 8;
constexpr int OFF_B = 0, OFF_A = NB * SLOT, OFF_KV = OFF_A + NA * SLOT, OFF_BAR = OFF_KV + 2 * KVBUF;
constexpr int OFF_GST = OFF_BAR + 512;
constexpr int OFF_GIN = OFF_BAR + 1024;
constexpr int SMEM_BYTES = OFF_BAR + 1536 + 1024;
constexpr uint32_t TIMEOUT = 1u << 28;
#define WAIT_HINT_NS 20000u
#define PFAT 8
constexpr int FS = 8;

constexpr int BAR_FULLA = 0, BAR_EMPTYA = BAR_FULLA + NA2, BAR_FULLB = BAR_EMPTYA + NA2, BAR_EMPTYB = BAR_FULLB + NB,
              BAR_KVFULL = BAR_EMPTYB + NB, BAR_KVEMPTY = BAR_KVFULL + 2, BAR_STG = BAR_KVEMPTY + 2, BAR_PIN = BAR_STG + 2, BAR_GATE = BAR_PIN + 1, BAR_STE = BAR_GATE + 2, BAR_ATTDONE = BAR_STE + 2, BAR_GIN = BAR_ATTDONE + 1, BAR_OST = BAR_GIN + 1, BAR_QRDY = BAR_OST + 2, BAR_KVOK = BAR_QRDY + 2;

__device__ __align__(1024) uint8_t g_kv[32 * SEQ * 64];
__device__ __align__(1024) __nv_bfloat16 g_ho[SEQ * KHO];
__device__ __align__(1024) uint8_t g_part[128 * 16384];
__device__ __align__(128) float g_gate[SEQ];
__device__ unsigned g_flag_kv[128 * FS], g_flag_h[128 * FS], g_flag_o[128 * FS], g_flag_g[16 * FS], g_flag_p[128 * FS], g_flag_e[128 * FS];
__device__ unsigned g_epoch, g_done;
#define TR(i) do {} while (0)

struct Params {
  CUtensorMap tmX, tmWqkv, tmW1a, tmW1b, tmW2, tmWo, tmHO, tmHOs, tmOs, tmOut;
  const __nv_bfloat16* x;
  const __nv_bfloat16* gate_w;
  const __nv_bfloat16* w1;
  const __nv_bfloat16* w2;
  const __nv_bfloat16* wo;
  __nv_bfloat16* out;
};

DEVI uint32_t smem_u32(const void* p) { return (uint32_t)__cvta_generic_to_shared(p); }
DEVI uint32_t clk32() { uint32_t c; asm volatile("mov.u32 %0, %%clock;" : "=r"(c)); return c; }
DEVI void mbar_init(uint32_t bar, uint32_t cnt) { asm volatile("mbarrier.init.shared::cta.b64 [%0], %1;" ::"r"(bar), "r"(cnt)); }
DEVI void mbar_expect_tx(uint32_t bar, uint32_t bytes) { asm volatile("mbarrier.arrive.expect_tx.shared::cta.b64 _, [%0], %1;" ::"r"(bar), "r"(bytes) : "memory"); }
DEVI void mbar_arrive(uint32_t bar) { asm volatile("mbarrier.arrive.shared::cta.b64 _, [%0];" ::"r"(bar) : "memory"); }
DEVI void mbar_arrive_cluster(uint32_t bar, uint32_t cta) {
  asm volatile("{ .reg .b32 ra; mapa.shared::cluster.u32 ra, %0, %1; mbarrier.arrive.shared::cluster.b64 _, [ra]; }" ::"r"(bar), "r"(cta) : "memory");
}
DEVI void mbar_wait(uint32_t bar, uint32_t parity, uint32_t t0) {
  asm volatile("{ .reg .pred p; .reg .u32 c;\n"
               "mbarrier.try_wait.parity.shared::cta.b64 p, [%0], %1;\n"
               "@p bra DONE_%=;\n"
               "WAIT_%=:\n"
               "mbarrier.try_wait.parity.shared::cta.b64 p, [%0], %1, %4;\n"
               "@p bra DONE_%=;\n"
               "mov.u32 c, %%clock; sub.u32 c, c, %2; setp.lt.u32 p, c, %3;\n"
               "@p bra WAIT_%=;\n"
               "DONE_%=: }" ::"r"(bar), "r"(parity), "r"(t0), "n"(TIMEOUT), "r"(WAIT_HINT_NS) : "memory");
}
DEVI unsigned ld_relaxed(const unsigned* p) { unsigned v; asm volatile("ld.relaxed.gpu.global.u32 %0, [%1];" : "=r"(v) : "l"(p) : "memory"); return v; }
DEVI void flag_wait(const unsigned* p, unsigned target, uint32_t t0) {
  while ((int)(ld_relaxed(p) - target) < 0) { if (clk32() - t0 > TIMEOUT) break; }
}
DEVI void flag_add(unsigned* p) { asm volatile("red.relaxed.gpu.global.add.u32 [%0], 1;" ::"l"(p) : "memory"); }
DEVI void fence_async_smem() { asm volatile("fence.proxy.async.shared::cta;" ::: "memory"); }
DEVI void fence_async_global() { asm volatile("fence.proxy.async.global;" ::: "memory"); }
DEVI void tma_load_2d(uint32_t dst, const CUtensorMap* m, int c0, int c1, uint32_t bar) {
  asm volatile("cp.async.bulk.tensor.2d.shared::cluster.global.mbarrier::complete_tx::bytes [%0], [%1, {%3, %4}], [%2];" ::"r"(dst), "l"(m), "r"(bar), "r"(c0), "r"(c1) : "memory");
}
DEVI void tma_load_3d(uint32_t dst, const CUtensorMap* m, int c0, int c1, int c2, uint32_t bar) {
  asm volatile("cp.async.bulk.tensor.3d.shared::cluster.global.mbarrier::complete_tx::bytes [%0], [%1, {%3, %4, %5}], [%2];"
               ::"r"(dst), "l"(m), "r"(bar), "r"(c0), "r"(c1), "r"(c2) : "memory");
}
DEVI void tma_load_3d_mc(uint32_t dst, const CUtensorMap* m, int c0, int c1, int c2, uint32_t bar) {
  asm volatile("cp.async.bulk.tensor.3d.shared::cluster.global.mbarrier::complete_tx::bytes.multicast::cluster [%0], [%1, {%3, %4, %5}], [%2], %6;"
               ::"r"(dst), "l"(m), "r"(bar), "r"(c0), "r"(c1), "r"(c2), "h"((uint16_t)3) : "memory");
}
DEVI void tma_load_4d_mc(uint32_t dst, const CUtensorMap* m, int c0, int c1, int c2, int c3, uint32_t bar) {
  asm volatile("cp.async.bulk.tensor.4d.shared::cluster.global.mbarrier::complete_tx::bytes.multicast::cluster [%0], [%1, {%3, %4, %5, %6}], [%2], %7;"
               ::"r"(dst), "l"(m), "r"(bar), "r"(c0), "r"(c1), "r"(c2), "r"(c3), "h"((uint16_t)3) : "memory");
}
DEVI void tma_store_2d(const CUtensorMap* m, int c0, int c1, uint32_t src) {
  asm volatile("cp.async.bulk.tensor.2d.global.shared::cta.bulk_group [%0, {%1, %2}], [%3];" ::"l"(m), "r"(c0), "r"(c1), "r"(src) : "memory");
}
DEVI void bulk_store(void* dst, uint32_t src, uint32_t bytes) {
  asm volatile("cp.async.bulk.global.shared::cta.bulk_group [%0], [%1], %2;" ::"l"(dst), "r"(src), "r"(bytes) : "memory");
}
DEVI void bulk_load(uint32_t dst, const void* src, uint32_t bytes, uint32_t bar) {
  asm volatile("cp.async.bulk.shared::cluster.global.mbarrier::complete_tx::bytes [%0], [%1], %2, [%3];" ::"r"(dst), "l"(src), "r"(bytes), "r"(bar) : "memory");
}
DEVI void bulk_commit() { asm volatile("cp.async.bulk.commit_group;" ::: "memory"); }
DEVI void bulk_wait_all() { asm volatile("cp.async.bulk.wait_group 0;" ::: "memory"); }
DEVI void l2_prefetch(const void* p, uint32_t bytes) { asm volatile("cp.async.bulk.prefetch.L2.global [%0], %1;" ::"l"(p), "r"(bytes) : "memory"); }
DEVI void cluster_arrive() { asm volatile("barrier.cluster.arrive.relaxed.aligned;" ::: "memory"); }
DEVI void cluster_wait() { asm volatile("barrier.cluster.wait.aligned;" ::: "memory"); }
template <int ID> DEVI void named_bar(int n) { asm volatile("bar.sync %0, %1;" ::"n"(ID), "r"(n) : "memory"); }
DEVI void wg_bar(int wg) { if (wg == 0) named_bar<1>(128); else named_bar<2>(128); }
DEVI void wgmma_fence() { asm volatile("wgmma.fence.sync.aligned;" ::: "memory"); }
DEVI void wgmma_commit() { asm volatile("wgmma.commit_group.sync.aligned;" ::: "memory"); }
template <int N> DEVI void wgmma_wait() { asm volatile("wgmma.wait_group.sync.aligned %0;" ::"n"(N) : "memory"); }
template <uint32_t LBO> DEVI uint64_t desc_sw128(uint32_t a16) {
  return ((uint64_t)(0x40000000u | (1024 >> 4)) << 32) | (a16 + ((LBO >> 4) << 16));
}
DEVI uint64_t desc_sw64(uint32_t a16) {
  return ((uint64_t)(0x80000000u | (512 >> 4)) << 32) | (a16 + ((512 >> 4) << 16));
}
DEVI uint32_t pack_bf16(float lo, float hi) { uint32_t r; asm("cvt.rn.bf16x2.f32 %0, %1, %2;" : "=r"(r) : "f"(hi), "f"(lo)); return r; }
DEVI void stsm_x4(uint32_t addr, uint32_t r0, uint32_t r1, uint32_t r2, uint32_t r3) {
  asm volatile("stmatrix.sync.aligned.m8n8.x4.shared.b16 [%0], {%1, %2, %3, %4};" ::"r"(addr), "r"(r0), "r"(r1), "r"(r2), "r"(r3) : "memory");
}
DEVI void sts128(uint32_t addr, uint32_t r0, uint32_t r1, uint32_t r2, uint32_t r3) {
  asm volatile("st.shared.v4.b32 [%0], {%1, %2, %3, %4};" ::"r"(addr), "r"(r0), "r"(r1), "r"(r2), "r"(r3) : "memory");
}
DEVI uint4 lds128(uint32_t addr) {
  uint4 v; asm volatile("ld.shared.v4.b32 {%0, %1, %2, %3}, [%4];" : "=r"(v.x), "=r"(v.y), "=r"(v.z), "=r"(v.w) : "r"(addr) : "memory"); return v;
}
DEVI float ex2(float x) { float y; asm("ex2.approx.ftz.f32 %0, %1;" : "=f"(y) : "f"(x)); return y; }

DEVI void wgmma_ss_n64(float (&d)[32], uint64_t da, uint64_t db) {
  asm volatile("wgmma.mma_async.sync.aligned.m64n64k16.f32.bf16.bf16 {%0, %1, %2, %3, %4, %5, %6, %7, %8, %9, %10, %11, %12, %13, %14, %15, %16, %17, %18, %19, %20, %21, %22, %23, %24, %25, %26, %27, %28, %29, %30, %31}, %32, %33, 1, 1, 1, 0, 1;"
    : "+f"(d[0]), "+f"(d[1]), "+f"(d[2]), "+f"(d[3]), "+f"(d[4]), "+f"(d[5]), "+f"(d[6]), "+f"(d[7]), "+f"(d[8]), "+f"(d[9]), "+f"(d[10]), "+f"(d[11]), "+f"(d[12]), "+f"(d[13]), "+f"(d[14]), "+f"(d[15]), "+f"(d[16]), "+f"(d[17]), "+f"(d[18]), "+f"(d[19]), "+f"(d[20]), "+f"(d[21]), "+f"(d[22]), "+f"(d[23]), "+f"(d[24]), "+f"(d[25]), "+f"(d[26]), "+f"(d[27]), "+f"(d[28]), "+f"(d[29]), "+f"(d[30]), "+f"(d[31])
    : "l"(da), "l"(db));
}
DEVI void wgmma_ss_n128(float (&d)[64], uint64_t da, uint64_t db) {
  asm volatile("wgmma.mma_async.sync.aligned.m64n128k16.f32.bf16.bf16 {%0, %1, %2, %3, %4, %5, %6, %7, %8, %9, %10, %11, %12, %13, %14, %15, %16, %17, %18, %19, %20, %21, %22, %23, %24, %25, %26, %27, %28, %29, %30, %31, %32, %33, %34, %35, %36, %37, %38, %39, %40, %41, %42, %43, %44, %45, %46, %47, %48, %49, %50, %51, %52, %53, %54, %55, %56, %57, %58, %59, %60, %61, %62, %63}, %64, %65, 1, 1, 1, 0, 1;"
    : "+f"(d[0]), "+f"(d[1]), "+f"(d[2]), "+f"(d[3]), "+f"(d[4]), "+f"(d[5]), "+f"(d[6]), "+f"(d[7]), "+f"(d[8]), "+f"(d[9]), "+f"(d[10]), "+f"(d[11]), "+f"(d[12]), "+f"(d[13]), "+f"(d[14]), "+f"(d[15]), "+f"(d[16]), "+f"(d[17]), "+f"(d[18]), "+f"(d[19]), "+f"(d[20]), "+f"(d[21]), "+f"(d[22]), "+f"(d[23]), "+f"(d[24]), "+f"(d[25]), "+f"(d[26]), "+f"(d[27]), "+f"(d[28]), "+f"(d[29]), "+f"(d[30]), "+f"(d[31]), "+f"(d[32]), "+f"(d[33]), "+f"(d[34]), "+f"(d[35]), "+f"(d[36]), "+f"(d[37]), "+f"(d[38]), "+f"(d[39]), "+f"(d[40]), "+f"(d[41]), "+f"(d[42]), "+f"(d[43]), "+f"(d[44]), "+f"(d[45]), "+f"(d[46]), "+f"(d[47]), "+f"(d[48]), "+f"(d[49]), "+f"(d[50]), "+f"(d[51]), "+f"(d[52]), "+f"(d[53]), "+f"(d[54]), "+f"(d[55]), "+f"(d[56]), "+f"(d[57]), "+f"(d[58]), "+f"(d[59]), "+f"(d[60]), "+f"(d[61]), "+f"(d[62]), "+f"(d[63])
    : "l"(da), "l"(db));
}
DEVI void wgmma_qk64(float (&d)[32], uint32_t a0, uint32_t a1, uint32_t a2, uint32_t a3, uint64_t db) {
  asm volatile("wgmma.mma_async.sync.aligned.m64n64k16.f32.bf16.bf16 {%0, %1, %2, %3, %4, %5, %6, %7, %8, %9, %10, %11, %12, %13, %14, %15, %16, %17, %18, %19, %20, %21, %22, %23, %24, %25, %26, %27, %28, %29, %30, %31}, {%32, %33, %34, %35}, %36, 0, 1, 1, 0;"
    : "=f"(d[0]), "=f"(d[1]), "=f"(d[2]), "=f"(d[3]), "=f"(d[4]), "=f"(d[5]), "=f"(d[6]), "=f"(d[7]), "=f"(d[8]), "=f"(d[9]), "=f"(d[10]), "=f"(d[11]), "=f"(d[12]), "=f"(d[13]), "=f"(d[14]), "=f"(d[15]), "=f"(d[16]), "=f"(d[17]), "=f"(d[18]), "=f"(d[19]), "=f"(d[20]), "=f"(d[21]), "=f"(d[22]), "=f"(d[23]), "=f"(d[24]), "=f"(d[25]), "=f"(d[26]), "=f"(d[27]), "=f"(d[28]), "=f"(d[29]), "=f"(d[30]), "=f"(d[31])
    : "r"(a0), "r"(a1), "r"(a2), "r"(a3), "l"(db));
}
DEVI void wgmma_pv(float (&d)[8], uint32_t a0, uint32_t a1, uint32_t a2, uint32_t a3, uint64_t db) {
  asm volatile("wgmma.mma_async.sync.aligned.m64n16k16.f32.bf16.bf16 {%0, %1, %2, %3, %4, %5, %6, %7}, {%8, %9, %10, %11}, %12, 1, 1, 1, 1;"
    : "+f"(d[0]), "+f"(d[1]), "+f"(d[2]), "+f"(d[3]), "+f"(d[4]), "+f"(d[5]), "+f"(d[6]), "+f"(d[7])
    : "r"(a0), "r"(a1), "r"(a2), "r"(a3), "l"(db));
}
DEVI void wgmma_pv0(float (&d)[8], uint32_t a0, uint32_t a1, uint32_t a2, uint32_t a3, uint64_t db) {
  asm volatile("wgmma.mma_async.sync.aligned.m64n16k16.f32.bf16.bf16 {%0, %1, %2, %3, %4, %5, %6, %7}, {%8, %9, %10, %11}, %12, 0, 1, 1, 1;"
    : "=f"(d[0]), "=f"(d[1]), "=f"(d[2]), "=f"(d[3]), "=f"(d[4]), "=f"(d[5]), "=f"(d[6]), "=f"(d[7])
    : "r"(a0), "r"(a1), "r"(a2), "r"(a3), "l"(db));
}

template <int N> struct Acc { float a[64]; float b[(N - 128) / 2]; DEVI float& operator[](int i) { return i < 64 ? a[i] : b[i - 64]; } };
template <> struct Acc<128> { float a[64]; DEVI float& operator[](int i) { return a[i]; } };
template <int N> DEVI void wgmma_ss(Acc<N>& d, uint64_t da, uint64_t db) {
  wgmma_ss_n128(d.a, da, db);
  if constexpr (N == 192) wgmma_ss_n64(d.b, da, db + 256);
  if constexpr (N == 256) wgmma_ss_n128(d.b, da, db + 256);
}

DEVI int oh_chunk(int j, int i, int& need) {
  if (j & 1) {
    if (i >= 3 && i < 7) { need = 16 + 2 * (i - 3); return 24 + (i - 3); }
    if (i >= 7) i -= 4;
  }
  const int g = i / 3, o = (j + 2 * g) & 7;
  need = o;
  return 3 * o + (i - 3 * g);
}

DEVI int a_slot(int e, int ebig) { return e < ebig ? 1 + (e & 3) : (e - ebig + 5) & 7; }

struct Ctx {
  uint32_t sbase, bars, peer, t0, a16, b16;
  int wg, lane;
  int ai, bi; uint32_t aph, bph;
  int brem, ae;
  int pa, pb;
};

DEVI void release_prev(Ctx& c) {
  if (c.pb >= 0) {
    if (c.lane == 0) mbar_arrive(c.bars + 8 * (BAR_EMPTYB + c.pb));
    if (c.lane == 1) mbar_arrive_cluster(c.bars + 8 * (BAR_EMPTYB + c.pb), c.peer);
  }
  if (c.pa >= 0 && c.lane == 2) mbar_arrive(c.bars + 8 * (BAR_EMPTYA + c.pa));
}

DEVI void gemm_wait(Ctx& c) {
  asm volatile("{ .reg .pred p, q; .reg .u32 c;\n"
               "WAIT_%=:\n"
               "mbarrier.try_wait.parity.shared::cta.b64 p, [%0], %1;\n"
               "mbarrier.try_wait.parity.shared::cta.b64 q, [%2], %3;\n"
               "and.pred p, p, q;\n"
               "@p bra DONE_%=;\n"
               "mov.u32 c, %%clock; sub.u32 c, c, %4; setp.lt.u32 p, c, %5;\n"
               "@p bra WAIT_%=;\n"
               "DONE_%=: }" ::"r"(c.bars + 8 * (BAR_FULLA + c.ai)), "r"((c.aph >> c.ai) & 1), "r"(c.bars + 8 * (BAR_FULLB + c.bi)), "r"(c.bph), "r"(c.t0), "n"(TIMEOUT) : "memory");
}
template <int N>
DEVI void gemm_group(Acc<N>& acc, Ctx& c, int g, int& npa, int& npb) {
  const uint32_t a16 = c.a16 + c.ai * (SLOT >> 4);
  const uint32_t b16 = c.b16 + c.bi * (SLOT >> 4);
  bool adv;
  if constexpr (N >= 192) {
    const uint32_t a2 = a16 + (g & 1) * 4;
    wgmma_ss<N>(acc, desc_sw128<16>(a2), desc_sw128<2048>(b16));
    wgmma_ss<N>(acc, desc_sw128<16>(a2 + 2), desc_sw128<2048>(b16 + 512));
    adv = g & 1;
  } else {
#pragma unroll
    for (int s = 0; s < 4; s++) wgmma_ss<N>(acc, desc_sw128<16>(a16 + s * 2), desc_sw128<4096>(b16 + (s >> 1) * 512 + (s & 1) * 128));
    adv = true;
  }
  wgmma_commit();
  npb = c.brem > 0 ? c.bi : -1;
  c.brem--;
  if (++c.bi == NB) { c.bi = 0; c.bph ^= 1; }
  npa = -1;
  if (adv) { npa = c.ai; c.aph ^= 1u << c.ai; c.ae++; c.ai = 1 + (c.ae & 3); }
}

template <int N>
DEVI void bare_groups(Acc<N>& acc, Ctx& c, int g0, int g1) {
  for (int g = g0; g < g1; g++) {
    int npa, npb;
    gemm_wait(c);
    wgmma_fence();
    gemm_group<N>(acc, c, g, npa, npb);
    wgmma_wait<1>();
    release_prev(c);
    c.pa = npa; c.pb = npb;
  }
}
DEVI void drain(Ctx& c) {
  wgmma_wait<0>();
  release_prev(c);
  c.pa = c.pb = -1;
}

constexpr float SC = 0.25f * 1.4426950408889634f;

#define ONCE _Pragma("unroll 1") for (unsigned once_ = 0; once_ < gridDim.y; once_++)

struct Gate { float g0, g1; };

DEVI void kill32(float (&S)[32]) {
#pragma unroll
  for (int i = 0; i < 32; i++) S[i] = __int_as_float(0xff800000);
}
DEVI void row_max(const float (&S)[32], float& x0, float& x1) {
  float y0 = S[1], y1 = S[3];
  x0 = fmaxf(x0, S[0]); x1 = fmaxf(x1, S[2]);
#pragma unroll
  for (int n = 1; n < 8; n++) {
    x0 = fmaxf(x0, S[4 * n]); y0 = fmaxf(y0, S[4 * n + 1]); x1 = fmaxf(x1, S[4 * n + 2]); y1 = fmaxf(y1, S[4 * n + 3]);
  }
  x0 = fmaxf(x0, y0); x1 = fmaxf(x1, y1);
}
DEVI void quad_max(float& x0, float& x1) {
  x0 = fmaxf(x0, __shfl_xor_sync(0xffffffffu, x0, 1)); x1 = fmaxf(x1, __shfl_xor_sync(0xffffffffu, x1, 1));
  x0 = fmaxf(x0, __shfl_xor_sync(0xffffffffu, x0, 2)); x1 = fmaxf(x1, __shfl_xor_sync(0xffffffffu, x1, 2));
}
DEVI void exp32(const float (&S)[32], float (&E)[32], float n0, float n1, float (&l)[4]) {
#pragma unroll
  for (int i = 0; i < 32; i++) { E[i] = ex2(fmaf(S[i], SC, (i & 2) ? n1 : n0)); l[i & 3] += E[i]; }
}
DEVI void pack32(const float (&E)[32], uint32_t (&P)[16]) {
#pragma unroll
  for (int i = 0; i < 16; i++) P[i] = pack_bf16(E[2 * i], E[2 * i + 1]);
}
template <bool FIRST> DEVI void pv4(float (&O)[8], const uint32_t (&P)[16], uint32_t v16) {
  if (FIRST) wgmma_pv0(O, P[0], P[1], P[2], P[3], desc_sw64(v16)); else wgmma_pv(O, P[0], P[1], P[2], P[3], desc_sw64(v16));
#pragma unroll
  for (int k = 1; k < 4; k++) wgmma_pv(O, P[4 * k], P[4 * k + 1], P[4 * k + 2], P[4 * k + 3], desc_sw64(v16 + k * 64));
}
DEVI bool wg_any(int wg, bool v) {
  uint32_t r;
  if (wg == 0) asm volatile("{ .reg .pred p, q; setp.ne.u32 p, %1, 0; bar.red.or.pred q, 4, 128, p; selp.u32 %0, 1, 0, q; }" : "=r"(r) : "r"((uint32_t)v) : "memory");
  else asm volatile("{ .reg .pred p, q; setp.ne.u32 p, %1, 0; bar.red.or.pred q, 5, 128, p; selp.u32 %0, 1, 0, q; }" : "=r"(r) : "r"((uint32_t)v) : "memory");
  return r != 0;
}
DEVI void get_gate(Gate& g, uint32_t sbase, int row16, int lane, uint32_t t0) {
  mbar_wait(sbase + OFF_BAR + 8 * BAR_GIN, 0, t0);
  const uint32_t a = sbase + OFF_GIN + (row16 * 16 + (lane >> 2)) * 4;
  asm volatile("ld.shared.f32 %0, [%1];" : "=f"(g.g0) : "r"(a) : "memory");
  asm volatile("ld.shared.f32 %0, [%1];" : "=f"(g.g1) : "r"(a + 32) : "memory");
}

DEVI void attention(uint32_t sbase, int aw, int wi, int lane, int rb, uint32_t t0) {
  const uint32_t bars = sbase + OFF_BAR;
  const uint32_t kvb = ((sbase & 0x3FFFF) + OFF_KV + aw * 4096) >> 4;
  const int cmin = 4 - 2 * rb - aw;
  const int rowc = wi * 16 + (lane >> 2) - (lane & 3) * 2;
  const uint32_t qst = sbase + OFF_A + aw * 8192;
  const float NINF = __int_as_float(0xff800000);
  float xt0 = NINF, xt1 = NINF;
  int h = 0;
  mbar_wait(bars + 8 * (BAR_QRDY + aw), 0, t0);
#pragma unroll 1
  while (h < 4) {
    const uint32_t kb = kvb + (h & 1) * (KVBUF >> 4);
    const uint4 q = lds128(qst + h * 2048 + (wi * 32 + lane) * 16);
    float O[8], l[4] = {0.f, 0.f, 0.f, 0.f}, n0, n1;
    uint32_t P[16];
    mbar_wait(bars + 8 * (BAR_KVFULL + (h & 1)), h >> 1, t0);
    {
      float S[32], F[32];
      wgmma_fence();
      wgmma_qk64(S, q.x, q.y, q.z, q.w, desc_sw64(kb + 4 * 256));
      wgmma_qk64(F, q.x, q.y, q.z, q.w, desc_sw64(kb));
      wgmma_commit();
      wgmma_wait<0>();
      if (cmin > 0) kill32(F);
      float M[32];
#pragma unroll
      for (int i = 0; i < 32; i++) M[i] = ((i >> 2) * 8 + (i & 1) > rowc + (i & 2) * 4) ? F[i] : S[i];
      float x0 = xt0, x1 = xt1;
      row_max(M, x0, x1);
      quad_max(x0, x1);
      n0 = -x0 * SC; n1 = -x1 * SC;
      exp32(M, M, n0, n1, l);
      pack32(M, P);
      uint32_t PF[16];
#pragma unroll
      for (int i = 0; i < 16; i++) {
        const int col = (i >> 1) * 8, r = rowc + (i & 1) * 8;
        const uint32_t m = (col > r ? 0xFFFFu : 0u) | (col + 1 > r ? 0xFFFF0000u : 0u);
        PF[i] = P[i] & m; P[i] &= ~m;
      }
      wgmma_fence();
      pv4<true>(O, PF, kb + 2);
      wgmma_commit();
      wgmma_wait<0>();
    }
#pragma unroll 1
    for (int t = 3; t >= 1; t--) {
      float S[32], E[32];
      wgmma_fence();
      wgmma_qk64(S, q.x, q.y, q.z, q.w, desc_sw64(kb + t * 256));
      wgmma_commit();
      pv4<false>(O, P, kb + (t + 1) * 256 + 2);
      wgmma_commit();
      wgmma_wait<1>();
      if (t < cmin) kill32(S);
      exp32(S, E, n0, n1, l);
      wgmma_wait<0>();
      pack32(E, P);
    }
    wgmma_fence();
    pv4<false>(O, P, kb + 256 + 2);
    wgmma_commit();
    float l0 = l[0] + l[1], l1 = l[2] + l[3];
    l0 += __shfl_xor_sync(0xffffffffu, l0, 1); l1 += __shfl_xor_sync(0xffffffffu, l1, 1);
    l0 += __shfl_xor_sync(0xffffffffu, l0, 2); l1 += __shfl_xor_sync(0xffffffffu, l1, 2);
    const bool exact = xt0 != NINF || cmin > 3;
    const bool redo = wg_any(aw, !exact && !(l0 < 1e18f && l1 < 1e18f));
    wgmma_wait<0>();
    if (redo) {
      xt0 = -3.0e38f; xt1 = -3.0e38f;
#pragma unroll 1
      for (int t = 3; t >= 1 && t >= cmin; t--) {
        float S[32];
        wgmma_fence();
        wgmma_qk64(S, q.x, q.y, q.z, q.w, desc_sw64(kb + t * 256));
        wgmma_commit();
        wgmma_wait<0>();
        row_max(S, xt0, xt1);
      }
      continue;
    }
    if (lane == 0) mbar_arrive(bars + 8 * (h == 3 ? BAR_ATTDONE : BAR_KVEMPTY + (h & 1)));
    Gate g;
    get_gate(g, sbase, aw * 4 + wi, lane, t0);
    const float c0 = __fdividef(g.g0, l0), c1 = __fdividef(g.g1, l1);
    const int mi = lane >> 3;
    const int srow = wi * 16 + (lane & 7) + 8 * (mi & 1);
    stsm_x4(qst + h * 2048 + srow * 32 + (mi >> 1) * 16, pack_bf16(O[0] * c0, O[1] * c0), pack_bf16(O[2] * c1, O[3] * c1),
            pack_bf16(O[4] * c0, O[5] * c0), pack_bf16(O[6] * c1, O[7] * c1));
    fence_async_smem();
    __syncwarp();
    if (lane == 0) mbar_arrive(bars + 8 * (BAR_OST + aw));
    xt0 = NINF; xt1 = NINF;
    h++;
  }
}

template <int CH, int N>
DEVI void store_h_chunk(Acc<N>& acc, uint32_t base  , int lane, float s0, float s1) {
  const int mi = lane >> 3;
#pragma unroll
  for (int tp = 0; tp < 4; tp++) {
    const int t = CH * 8 + tp * 2;
    const uint32_t r0 = pack_bf16(fmaxf(acc[4 * t + 0], 0.f) * s0, fmaxf(acc[4 * t + 1], 0.f) * s0);
    const uint32_t r1 = pack_bf16(fmaxf(acc[4 * t + 2], 0.f) * s1, fmaxf(acc[4 * t + 3], 0.f) * s1);
    const uint32_t r2 = pack_bf16(fmaxf(acc[4 * t + 4], 0.f) * s0, fmaxf(acc[4 * t + 5], 0.f) * s0);
    const uint32_t r3 = pack_bf16(fmaxf(acc[4 * t + 6], 0.f) * s1, fmaxf(acc[4 * t + 7], 0.f) * s1);
    stsm_x4(base + (((tp * 2 + (mi >> 1)) ^ (lane & 7)) << 4), r0, r1, r2, r3);
  }
}

template <int N>
DEVI void phase_q(Ctx& c, int warp) {
  Acc<N> acc;
#pragma unroll
  for (int i = 0; i < N / 2; i++) acc[i] = 0.f;
  bare_groups<N>(acc, c, 0, 16);
  drain(c);
  const int lane = c.lane, mi = lane >> 3;
  const int row = warp * 16 + (lane & 7) + 8 * (mi & 1);
  const int sw = (row >> 1) & 3;
#pragma unroll
  for (int hh = 0; hh < 4; hh++) {
    const uint32_t base = c.sbase + OFF_KV + hh * 8192 + row * 64;
#pragma unroll
    for (int kv = 0; kv < 2; kv++) {
      const int t = 8 + kv * 8 + 2 * hh;
      stsm_x4(base + (((kv * 2 + (mi >> 1)) ^ sw) << 4),
              pack_bf16(acc[4 * t + 0], acc[4 * t + 1]), pack_bf16(acc[4 * t + 2], acc[4 * t + 3]),
              pack_bf16(acc[4 * t + 4], acc[4 * t + 5]), pack_bf16(acc[4 * t + 6], acc[4 * t + 7]));
    }
  }
  fence_async_smem();
  __syncwarp();
  if (lane == 0) mbar_arrive(c.bars + 8 * BAR_STG);
#pragma unroll
  for (int hh = 0; hh < 4; hh++)
    sts128(c.sbase + OFF_A + c.wg * 8192 + hh * 2048 + ((warp & 3) * 32 + lane) * 16,
           pack_bf16(acc[8 * hh], acc[8 * hh + 1]), pack_bf16(acc[8 * hh + 2], acc[8 * hh + 3]),
           pack_bf16(acc[8 * hh + 4], acc[8 * hh + 5]), pack_bf16(acc[8 * hh + 6], acc[8 * hh + 7]));
  __syncwarp();
  if (lane == 0) mbar_arrive(c.bars + 8 * (BAR_QRDY + c.wg));
  if constexpr (N == 256) {
    Gate g;
    get_gate(g, c.sbase, warp, lane, c.t0);
    store_h_chunk<3>(acc, c.sbase + OFF_KV + 32768 + row * 128, lane, 1.f - g.g0, 1.f - g.g1);
    fence_async_smem();
    __syncwarp();
    if (lane == 0) mbar_arrive(c.bars + 8 * BAR_STE);
  }
}

DEVI void first_loads(const Params& P, uint32_t sbase, int e, int j, int rb) {
  const uint32_t bars = sbase + OFF_BAR, fb = bars + 8 * (BAR_FULLB + e), fa = bars + 8 * (BAR_FULLA + 1 + e);
  mbar_expect_tx(fa, 16384);
  mbar_expect_tx(fb, (j & 1) ? 12288 : 16384);
  if (e == 0) tma_load_2d(sbase + OFF_A + SLOT, &P.tmX, 0, rb * 128, fa);
#pragma unroll
  for (int r = 0; r < 2; r++) {
    tma_load_3d(sbase + OFF_B + e * SLOT + r * 8192, &P.tmWqkv, 64 * j, e * 32 + r * 16, 0, fb);
    if (!(j & 1)) tma_load_3d(sbase + OFF_B + e * SLOT + r * 8192 + 6144, &P.tmW1a, 0, e * 32 + r * 16, 24 + (j >> 1), fb);
  }
  if (e == 1) tma_load_2d(sbase + OFF_A + 2 * SLOT, &P.tmX, 64, rb * 128, fa);
}

__global__ void __cluster_dims__(2, 1, 1) __launch_bounds__(640, 1) fused_kernel(const __grid_constant__ Params P) {
  extern __shared__ uint8_t smem_raw[];
  const uint32_t sbase = (smem_u32(smem_raw) + 1023u) & ~1023u;
  const uint32_t bars = sbase + OFF_BAR;
  const int tid = threadIdx.x, warp = tid >> 5, lane = tid & 31;
  const uint32_t rank = blockIdx.x & 1, peer = rank ^ 1;
  const int j = (blockIdx.x >> 1) & 7, rb = ((blockIdx.x >> 4) << 1) | rank;
  const uint32_t t0 = clk32();

  const int typeB = j & 1;
  if (tid == 544) {
    for (int s = 0; s < NA2; s++) mbar_init(bars + 8 * (BAR_FULLA + s), 1);
    for (int s = 0; s < NB; s++) mbar_init(bars + 8 * (BAR_FULLB + s), 1);
    fence_async_smem();
  } else if (tid < 10) {
    asm volatile("prefetch.tensormap [%0];" ::"l"(&P.tmX + tid) : "memory");
  } else if (tid == 512) {
    for (int s = 0; s < NA2; s++) mbar_init(bars + 8 * (BAR_EMPTYA + s), 9);
    for (int s = 0; s < NB; s++) mbar_init(bars + 8 * (BAR_EMPTYB + s), 16);
  } else if (tid == 576) {
    for (int s = 0; s < 2; s++) { mbar_init(bars + 8 * (BAR_KVFULL + s), 1); mbar_init(bars + 8 * (BAR_KVEMPTY + s), 8); mbar_init(bars + 8 * (BAR_OST + s), 4); mbar_init(bars + 8 * (BAR_QRDY + s), 4); }
    mbar_init(bars + 8 * BAR_STG, 8); mbar_init(bars + 8 * BAR_STE, 8); mbar_init(bars + 8 * BAR_KVOK, 1);
    mbar_init(bars + 8 * BAR_PIN, 1); mbar_init(bars + 8 * BAR_ATTDONE, 8); mbar_init(bars + 8 * BAR_GIN, 1);
  }
  if (tid >= 512 && lane == 0) asm volatile("fence.mbarrier_init.release.cluster;" ::: "memory");
  const unsigned ep1 = ld_relaxed(&g_epoch) + 1;
  __syncwarp();
  cluster_arrive();
  if (tid == 544) { first_loads(P, sbase, 0, j, rb); first_loads(P, sbase, 1, j, rb); }
  __syncwarp();

  const int on = 12 + 4 * typeB;

  if (warp < 8) {
    asm volatile("setmaxnreg.inc.sync.aligned.u32 160;");
    cluster_wait();
    const int wg = __shfl_sync(0xffffffffu, warp >> 2, 0), wi = warp & 3;
    Ctx c{sbase, bars, peer, t0, ((sbase & 0x3FFFF) + OFF_A + wg * 8192) >> 4, ((sbase & 0x3FFFF) + OFF_B) >> 4, wg, lane, 1, 0, 0u, 0u, 32 + on + 4 - NB, 0, -1, -1};
    if (tid == 0) TR(0);
    if (typeB) phase_q<192>(c, warp);
    else phase_q<256>(c, warp);
    asm volatile("setmaxnreg.dec.sync.aligned.u32 128;");
    if (tid == 0) TR(2);
    {
      Acc<192> acc;
#pragma unroll
      for (int i = 0; i < 96; i++) acc[i] = 0.f;
      bare_groups<192>(acc, c, 0, 16);
      Gate at;
      get_gate(at, sbase, warp, lane, t0);
      drain(c);
      if (tid == 0) TR(1);
      const uint32_t rowoff = (warp * 16 + (lane & 7) + 8 * ((lane >> 3) & 1)) * 128;
      const float s0 = 1.f - at.g0, s1 = 1.f - at.g1;
      constexpr int e0 = 1, e1 = 2, e2 = 3;
      mbar_wait(bars + 8 * (BAR_FULLA + e0), 0, t0);
      store_h_chunk<0>(acc, sbase + OFF_A + e0 * SLOT + rowoff, lane, s0, s1);
      mbar_wait(bars + 8 * (BAR_FULLA + e1), 0, t0);
      store_h_chunk<1>(acc, sbase + OFF_A + e1 * SLOT + rowoff, lane, s0, s1);
      mbar_wait(bars + 8 * (BAR_FULLA + e2), 0, t0);
      store_h_chunk<2>(acc, sbase + OFF_A + e2 * SLOT + rowoff, lane, s0, s1);
    }
    fence_async_smem();
    wg_bar(wg);
    if (lane == 0) mbar_arrive(bars + 8 * BAR_STG);
    if (tid == 0) TR(4);
    float own[32];
    {
      Acc<128> acc;
#pragma unroll
      for (int i = 0; i < 64; i++) acc[i] = 0.f;
      bare_groups<128>(acc, c, 0, on);
      drain(c);
      if (tid == 0) TR(5);
      named_bar<3>(256);
      const uint32_t pst = sbase + OFF_B + ((30 + on) % NB) * SLOT + wg * 8192 + (tid & 127) * 16;
#pragma unroll
      for (int i = 0; i < 4; i++) {
        uint32_t r[4];
#pragma unroll
        for (int k = 0; k < 4; k++) {
          const int idx = 8 * i + 2 * k;
          const float lo = typeB ? acc[idx] : acc[32 + idx], hi = typeB ? acc[idx + 1] : acc[32 + idx + 1];
          r[k] = pack_bf16(lo, hi);
        }
        sts128(pst + i * 2048, r[0], r[1], r[2], r[3]);
      }
#pragma unroll
      for (int i = 0; i < 32; i++) own[i] = typeB ? acc[32 + i] : acc[i];
      fence_async_smem();
      __syncwarp();
      if (lane == 0) mbar_arrive(bars + 8 * BAR_STG);
    }
    for (int g = 0; g < 8; g++) {
      const uint32_t a16 = c.a16 + c.ai * (SLOT >> 4);
      const uint32_t b16 = c.b16 + c.bi * (SLOT >> 4) + (g & 1) * 512;
      gemm_wait(c);
      wgmma_fence();
#pragma unroll
      for (int s = 0; s < 4; s++) wgmma_ss_n64(own, desc_sw128<16>(a16 + s * 2), desc_sw128<2048>(b16 + s * 128));
      wgmma_commit();
      c.ae++; c.ai = a_slot(c.ae, 20 + on);
      if (g & 1) { if (++c.bi == NB) { c.bi = 0; c.bph ^= 1; } }
    }
    wgmma_wait<0>();
    if (tid == 0) TR(6);
    mbar_wait(bars + 8 * BAR_PIN, 0, t0);
    if (tid == 0) TR(7);
    {
      const uint32_t pin = sbase + OFF_B + ((31 + on) % NB) * SLOT + wg * 8192 + (tid & 127) * 16;
      wg_bar(wg);
      const uint32_t ob = sbase + OFF_A + SLOT + wg * 8192;
      const uint32_t orow = ob + (wi * 16 + (lane & 7) + 8 * ((lane >> 3) & 1)) * 128;
#pragma unroll
      for (int i = 0; i < 4; i++) {
        const uint4 v = lds128(pin + i * 2048);
        const uint32_t r[4] = {v.x, v.y, v.z, v.w};
        uint32_t o[4];
#pragma unroll
        for (int k = 0; k < 4; k++) {
          const int idx = 8 * i + 2 * k;
          o[k] = pack_bf16(own[idx] + __uint_as_float(r[k] << 16), own[idx + 1] + __uint_as_float(r[k] & 0xffff0000u));
        }
        stsm_x4(orow + (((i * 2 + (lane >> 4)) ^ (lane & 7)) << 4), o[0], o[1], o[2], o[3]);
      }
      fence_async_smem();
      __syncwarp();
      if (lane == 0) {
        tma_store_2d(&P.tmOut, j * 64, rb * 128 + warp * 16, ob + wi * 2048);
        bulk_commit();
        asm volatile("cp.async.bulk.wait_group.read 0;" ::: "memory");
      }
    }
    if (tid == 0) TR(8);
  } else if (warp < 16) {
    asm volatile("setmaxnreg.dec.sync.aligned.u32 56;");
    cluster_wait();
    const int aw = __shfl_sync(0xffffffffu, (warp >> 2) & 1, 0);
    {
      const int rowg = rb * 128 + j * 16 + (warp - 8) * 2;
      const uint4* gw = (const uint4*)P.gate_w;
      const uint4* xr = (const uint4*)(P.x + (size_t)rowg * DM);
      mbar_wait(bars + 8 * (BAR_FULLB + 1), 0, t0);
      const uint4 w0 = __ldg(gw + lane), w1 = __ldg(gw + 32 + lane);
      const uint4 xa0 = __ldg(xr + lane), xa1 = __ldg(xr + 32 + lane), xb0 = __ldg(xr + 64 + lane), xb1 = __ldg(xr + 96 + lane);
#pragma unroll
      for (int i = 0; i < 4; i++) sts128(sbase + OFF_KV + 32768 + i * 4096 + (tid - 256) * 16, 0u, 0u, 0u, 0u);
      const uint32_t wa[8] = {w0.x, w0.y, w0.z, w0.w, w1.x, w1.y, w1.z, w1.w};
      const uint32_t xa[8] = {xa0.x, xa0.y, xa0.z, xa0.w, xa1.x, xa1.y, xa1.z, xa1.w};
      const uint32_t xb[8] = {xb0.x, xb0.y, xb0.z, xb0.w, xb1.x, xb1.y, xb1.z, xb1.w};
      float za = 0.f, zb = 0.f;
#pragma unroll
      for (int e = 0; e < 8; e++) {
        const float wl = __uint_as_float(wa[e] << 16), wh = __uint_as_float(wa[e] & 0xffff0000u);
        za = fmaf(__uint_as_float(xa[e] << 16), wl, za); za = fmaf(__uint_as_float(xa[e] & 0xffff0000u), wh, za);
        zb = fmaf(__uint_as_float(xb[e] << 16), wl, zb); zb = fmaf(__uint_as_float(xb[e] & 0xffff0000u), wh, zb);
      }
#pragma unroll
      for (int o = 16; o > 0; o >>= 1) { za += __shfl_xor_sync(0xffffffffu, za, o); zb += __shfl_xor_sync(0xffffffffu, zb, o); }
      if (lane < 2) asm volatile("st.shared.f32 [%0], %1;" ::"r"(sbase + OFF_GST + (warp - 8) * 8 + lane * 4), "f"(1.f / (1.f + __expf(-(lane ? zb : za)))) : "memory");
      fence_async_smem();
      named_bar<6>(256);
      if (tid == 256) {
        bulk_store(&g_gate[rb * 128 + j * 16], sbase + OFF_GST, 64);
        bulk_commit(); bulk_wait_all();
        flag_add(&g_flag_g[rb * FS]);
        flag_wait(&g_flag_g[rb * FS], ep1 * 8, t0);
        fence_async_global();
        mbar_expect_tx(bars + 8 * BAR_GIN, 512);
        bulk_load(sbase + OFF_GIN, &g_gate[rb * 128], 512, bars + 8 * BAR_GIN);
        TR(10);
      }
      __syncwarp();
    }
    mbar_wait(bars + 8 * (BAR_QRDY + aw), 0, t0);
    asm volatile("setmaxnreg.inc.sync.aligned.u32 96;");
    attention(sbase, aw, warp & 3, lane, rb, t0);
    if (tid == 256) TR(3);
  } else {
    asm volatile("setmaxnreg.dec.sync.aligned.u32 32;");
    if (warp == 16) {
      __syncwarp();
      cluster_wait();
      if (lane == 0) {
        int bi = 2; uint32_t bph = 1;
        const int nb = 32 + on + 4;
        for (int eb = 2; eb < nb; eb++) {
          if (eb == 4 || eb == 6) {
            const int ea = eb >> 1;
            mbar_expect_tx(bars + 8 * (BAR_FULLA + 1 + ea), 16384);
            tma_load_2d(sbase + OFF_A + (1 + ea) * SLOT, &P.tmX, ea * 64, rb * 128, bars + 8 * (BAR_FULLA + 1 + ea));
          }
          const uint32_t fb = bars + 8 * (BAR_FULLB + bi), dst = sbase + OFF_B + bi * SLOT + rank * 8192;
          mbar_wait(bars + 8 * (BAR_EMPTYB + bi), bph, t0);
          if (eb < 16) {
            mbar_expect_tx(fb, typeB ? 12288 : 16384);
            tma_load_3d_mc(dst, &P.tmWqkv, 64 * j, eb * 32 + rank * 16, 0, fb);
            if (!typeB) tma_load_3d_mc(dst + 6144, &P.tmW1a, 0, eb * 32 + rank * 16, 24 + (j >> 1), fb);
          }
          else if (eb < 32) { mbar_expect_tx(fb, 12288); tma_load_3d_mc(dst, &P.tmW1b, 0, (eb - 16) * 32 + rank * 16, 3 * j, fb); }
          else if (eb < 32 + on) { int ow; const int ch = oh_chunk(j, eb - 32, ow); mbar_expect_tx(fb, 16384); tma_load_3d_mc(dst, &P.tmW2, 0, ch * 64 + rank * 32, (j >> 1) * 2, fb); }
          else { mbar_expect_tx(fb, 16384); tma_load_4d_mc(dst, &P.tmWo, 64 * j, 0, eb - 32 - on, rank * 4, fb); }
          if (++bi == NB) { bi = 0; bph ^= 1; }
          if (eb == PFAT) {
            const int b = blockIdx.x;
            l2_prefetch((const uint8_t*)P.w1 + b * 14336, 14336);
            l2_prefetch((const uint8_t*)P.w2 + b * 14336, 14336);
            l2_prefetch((const uint8_t*)P.wo + b * 4096, 4096);
          }
        }
      }
    } else if (warp == 17) {
      cluster_wait();
      if (lane == 0) {
        for (int ea = 1; ea < 5; ea++) mbar_arrive(bars + 8 * (BAR_EMPTYA + ea));
        uint32_t aph = 0xE1;
        const int na = 16 + on + 8;
        unsigned ready = 0;
        for (int ea = 4; ea < na; ea++) {
          const int ai = a_slot(ea, 20 + on);
          const uint32_t fb = bars + 8 * (BAR_FULLA + ai), dst = sbase + OFF_A + ai * SLOT;
          int ch = ea & 7, need = -1;
          if (ea >= 16 + on) { need = 8 + ea - 16 - on; ch = 20 + need; }
          else if (ea >= 19) ch = oh_chunk(j, ea - 16, need);
          if (need >= 0 && !((ready >> need) & 1)) {
            const unsigned* fp = need < 8 ? &g_flag_h[rb * 8 * FS] : need < 16 ? &g_flag_o[rb * 8 * FS] : &g_flag_e[rb * 8 * FS];
            const unsigned tgt = (need & 8) ? ep1 * 4 : ep1;
            do {
              unsigned v[8];
#pragma unroll
              for (int i = 0; i < 8; i++) v[i] = ld_relaxed(fp + i * FS);
#pragma unroll
              for (int i = 0; i < 8; i++) if ((int)(v[i] - tgt) >= 0) ready |= 1u << (i + (need & 24));
            } while (!((ready >> need) & 1) && clk32() - t0 < TIMEOUT);
            fence_async_global();
          }
          if (ea == 20 + on) mbar_wait(bars + 8 * BAR_ATTDONE, 0, t0);
          mbar_wait(bars + 8 * (BAR_EMPTYA + ai), (aph >> ai) & 1, t0);
          if (ea >= 16 && ea < 19) mbar_arrive(fb);
          else {
            mbar_arrive(bars + 8 * (BAR_EMPTYA + ai));
            mbar_expect_tx(fb, 16384);
            tma_load_2d(dst, ea < 16 ? &P.tmX : &P.tmHO, ch * 64, rb * 128, fb);
          }
          TR(24 + ea);
          aph ^= 1u << ai;
        }
      }
    } else {
      const int wg = warp - 18;
      cluster_wait();
      if (lane == 0 && wg == 0) {
        const uint32_t stg = bars + 8 * BAR_STG;
        mbar_wait(stg, 0, t0);
        for (int hh = 0; hh < 4; hh++) bulk_store(g_kv + ((size_t)(4 * j + hh) * SEQ + rb * 128) * 64, sbase + OFF_KV + hh * 8192, 8192);
        bulk_commit(); bulk_wait_all();
        flag_add(&g_flag_kv[(rb * 8 + j) * FS]);
        TR(21);
        if (!typeB) {
          mbar_wait(bars + 8 * BAR_STE, 0, t0);
          tma_store_2d(&P.tmHO, (24 + (j >> 1)) * 64, rb * 128, sbase + OFF_KV + 32768);
          bulk_commit(); bulk_wait_all();
          flag_add(&g_flag_e[(rb * 8 + j) * FS]);
        }
        mbar_arrive(bars + 8 * BAR_KVOK);
        mbar_wait(stg, 1, t0);
        for (int i = 0; i < 3; i++) tma_store_2d(&P.tmHO, (3 * j + i) * 64, rb * 128, sbase + OFF_A + (1 + i) * SLOT);
        bulk_commit(); bulk_wait_all();
        flag_add(&g_flag_h[(rb * 8 + j) * FS]);
        for (int i = 0; i < 3; i++) mbar_arrive(bars + 8 * (BAR_EMPTYA + 1 + i));
        TR(22);
        {
          const unsigned old = atomicAdd(&g_done, 1u);
          if (old == gridDim.x - 1) { g_done = 0; *(volatile unsigned*)&g_epoch = ep1; }
        }
        mbar_wait(stg, 0, t0);
        bulk_store(g_part + (size_t)(rb * 8 + (j ^ 1)) * 16384, sbase + OFF_B + ((30 + on) % NB) * SLOT, 16384);
        bulk_commit(); bulk_wait_all();
        flag_add(&g_flag_p[(rb * 8 + (j ^ 1)) * FS]);
        TR(23);
        flag_wait(&g_flag_p[(rb * 8 + j) * FS], ep1, t0);
        fence_async_global();
        mbar_expect_tx(bars + 8 * BAR_PIN, 16384);
        bulk_load(sbase + OFF_B + ((31 + on) % NB) * SLOT, g_part + (size_t)(rb * 8 + j) * 16384, 16384, bars + 8 * BAR_PIN);
      } else if (lane == 0) {
        const int nblk = rb >= 2 ? 3 : rb + 1;
        const uint32_t kvbytes = nblk * 8192;
        const uint8_t* kvsrc = g_kv + ((size_t)(4 * j) * SEQ + (rb + 1 - nblk) * 128) * 64;
        const uint32_t kvdst = sbase + OFF_KV + (3 - nblk) * 8192;
        {
          const unsigned* f0 = &g_flag_kv[(rb * 8 + j) * FS];
          const unsigned* f1 = rb >= 1 ? f0 - 8 * FS : f0;
          const unsigned* f2 = rb >= 2 ? f0 - 16 * FS : f0;
          unsigned v0, v1, v2;
          do { v0 = ld_relaxed(f0); v1 = ld_relaxed(f1); v2 = ld_relaxed(f2); }
          while (((int)(v0 - ep1) < 0 || (int)(v1 - ep1) < 0 || (int)(v2 - ep1) < 0) && clk32() - t0 < TIMEOUT);
        }
        TR(11);
        mbar_wait(bars + 8 * BAR_GIN, 0, t0);
        fence_async_global();
        mbar_expect_tx(bars + 8 * BAR_KVFULL, kvbytes);
        bulk_load(kvdst, kvsrc, kvbytes, bars + 8 * BAR_KVFULL);
        mbar_wait(bars + 8 * BAR_KVOK, 0, t0);
        mbar_expect_tx(bars + 8 * (BAR_KVFULL + 1), kvbytes);
        bulk_load(kvdst + KVBUF, kvsrc + (size_t)SEQ * 64, kvbytes, bars + 8 * (BAR_KVFULL + 1));
        for (int hh = 0; hh < 4; hh++) {
          for (int aw = 0; aw < 2; aw++) {
            mbar_wait(bars + 8 * (BAR_OST + aw), hh & 1, t0);
            tma_store_2d(&P.tmOs, DFF + hh * 128 + j * 16, rb * 128 + aw * 64, sbase + OFF_A + aw * 8192 + hh * 2048);
          }
          bulk_commit();
          if (hh < 2) {
            mbar_wait(bars + 8 * (BAR_KVEMPTY + hh), 0, t0);
            mbar_expect_tx(bars + 8 * (BAR_KVFULL + hh), kvbytes);
            bulk_load(kvdst + hh * KVBUF, kvsrc + (size_t)(hh + 2) * SEQ * 64, kvbytes, bars + 8 * (BAR_KVFULL + hh));
          }
          bulk_wait_all();
          flag_add(&g_flag_o[(rb * 8 + hh * 2 + (j >> 2)) * FS]);
          TR(12 + hh);
        }
      }
    }
  }
}

typedef CUresult (*EncodeFn)(CUtensorMap*, CUtensorMapDataType, cuuint32_t, void*, const cuuint64_t*, const cuuint64_t*, const cuuint32_t*,
                             const cuuint32_t*, CUtensorMapInterleave, CUtensorMapSwizzle, CUtensorMapL2promotion, CUtensorMapFloatOOBfill);

void make_map(EncodeFn enc, CUtensorMap* m, const void* ptr, int rank, const cuuint64_t* dims, const cuuint64_t* strides, const cuuint32_t* box,
              CUtensorMapSwizzle sw = CU_TENSOR_MAP_SWIZZLE_128B) {
  cuuint32_t es[4] = {1, 1, 1, 1};
  enc(m, CU_TENSOR_MAP_DATA_TYPE_BFLOAT16, rank, const_cast<void*>(ptr), dims, strides, box, es, CU_TENSOR_MAP_INTERLEAVE_NONE, sw,
      CU_TENSOR_MAP_L2_PROMOTION_L2_256B, CU_TENSOR_MAP_FLOAT_OOB_FILL_NONE);
}

}

extern "C" void kernel_launch(void* const* d_in, const int* in_sizes, int n_in, void* d_out, int out_size) {
  (void)in_sizes; (void)n_in; (void)out_size;
  static EncodeFn enc = nullptr;
  static void* ho_ptr = nullptr;
  if (!enc) {
    void* fn = nullptr; cudaDriverEntryPointQueryResult st;
    cudaGetDriverEntryPoint("cuTensorMapEncodeTiled", &fn, cudaEnableDefault, &st);
    enc = (EncodeFn)fn;
    cudaGetSymbolAddress(&ho_ptr, g_ho);
    cudaFuncSetAttribute(fused_kernel, cudaFuncAttributeMaxDynamicSharedMemorySize, SMEM_BYTES);
  }
  const __nv_bfloat16* x = (const __nv_bfloat16*)d_in[0];
  const __nv_bfloat16* wqkv = (const __nv_bfloat16*)d_in[1];
  const __nv_bfloat16* wo = (const __nv_bfloat16*)d_in[2];
  const __nv_bfloat16* w1 = (const __nv_bfloat16*)d_in[4];
  const __nv_bfloat16* w2 = (const __nv_bfloat16*)d_in[5];
  const __nv_bfloat16* gate_w = (const __nv_bfloat16*)d_in[6];
  Params P;
  { cuuint64_t d[2] = {DM, SEQ}, s[1] = {DM * 2}; cuuint32_t b[2] = {64, 128}; make_map(enc, &P.tmX, x, 2, d, s, b); }
  { cuuint64_t d[3] = {512, 512, 3}, s[2] = {1536 * 2, 512 * 2}; cuuint32_t b[3] = {64, 16, 3}; make_map(enc, &P.tmWqkv, wqkv, 3, d, s, b); }
  { cuuint64_t d[3] = {64, 512, 28}, s[2] = {DFF * 2, 128}; cuuint32_t b[3] = {64, 16, 1}; make_map(enc, &P.tmW1a, w1, 3, d, s, b);
    b[2] = 3; make_map(enc, &P.tmW1b, w1, 3, d, s, b); }
  { cuuint64_t d[3] = {64, DFF, 8}, s[2] = {DM * 2, 128}; cuuint32_t b[3] = {64, 32, 2}; make_map(enc, &P.tmW2, w2, 3, d, s, b); }
  { cuuint64_t d[4] = {DM, 16, 4, 8}, s[3] = {DM * 2, 16 * DM * 2, 64 * DM * 2}; cuuint32_t b[4] = {64, 16, 1, 4}; make_map(enc, &P.tmWo, wo, 4, d, s, b); }
  { cuuint64_t d[2] = {KHO, SEQ}, s[1] = {KHO * 2}; cuuint32_t b[2] = {64, 128}; make_map(enc, &P.tmHO, ho_ptr, 2, d, s, b);
    b[1] = 64; make_map(enc, &P.tmHOs, ho_ptr, 2, d, s, b);
    b[0] = 16; make_map(enc, &P.tmOs, ho_ptr, 2, d, s, b, CU_TENSOR_MAP_SWIZZLE_NONE); }
  { cuuint64_t d[2] = {DM, SEQ}, s[1] = {DM * 2}; cuuint32_t b[2] = {64, 16}; make_map(enc, &P.tmOut, d_out, 2, d, s, b); }
  P.x = x; P.gate_w = gate_w; P.w1 = w1; P.w2 = w2; P.wo = wo; P.out = (__nv_bfloat16*)d_out;
  fused_kernel<<<128, 640, SMEM_BYTES>>>(P);
}
```

```cpp
#include <cuda_runtime.h>
#include <cuda_bf16.h>
#include <cuda.h>
#include <stdint.h>

#define DEVI __device__ __forceinline__

namespace {

constexpr int SEQ = 2048, DM = 512, DFF = 1792, KHO = 2304;
constexpr int NA = 5, NB = 6, SLOT = 16384, KVBUF = 24576;
constexpr int NA2 = 8;
constexpr int OFF_B = 0, OFF_A = NB * SLOT, OFF_KV = OFF_A + NA * SLOT, OFF_BAR = OFF_KV + 2 * KVBUF;
constexpr int OFF_GST = OFF_BAR + 512;
constexpr int OFF_GIN = OFF_BAR + 1024;
constexpr int SMEM_BYTES = OFF_BAR + 1536 + 1024;
constexpr uint32_t TIMEOUT = 1u << 28;
#define WAIT_HINT_NS 20000u
#define PFAT 8
#define SH false
#define SHW 1
#define SHG 1
constexpr int FS = 8;

constexpr int BAR_FULLA = 0, BAR_EMPTYA = BAR_FULLA + NA2, BAR_FULLB = BAR_EMPTYA + NA2, BAR_EMPTYB = BAR_FULLB + NB,
              BAR_KVFULL = BAR_EMPTYB + NB, BAR_KVEMPTY = BAR_KVFULL + 2, BAR_STG = BAR_KVEMPTY + 2, BAR_PIN = BAR_STG + 2, BAR_GATE = BAR_PIN + 1, BAR_STE = BAR_GATE + 2, BAR_ATTDONE = BAR_STE + 2, BAR_GIN = BAR_ATTDONE + 1, BAR_OST = BAR_GIN + 1, BAR_QRDY = BAR_OST + 2, BAR_KVOK = BAR_QRDY + 2;

__device__ __align__(1024) uint8_t g_kv[32 * SEQ * 64];
__device__ __align__(1024) __nv_bfloat16 g_ho[SEQ * KHO];
__device__ __align__(1024) uint8_t g_part[128 * 16384];
__device__ __align__(128) float g_gate[SEQ];
__device__ unsigned g_flag_kv[128 * FS], g_flag_h[128 * FS], g_flag_o[128 * FS], g_flag_g[16 * FS], g_flag_p[128 * FS], g_flag_e[128 * FS];
__device__ unsigned g_epoch, g_done;
#define TR(i) do {} while (0)

struct Params {
  CUtensorMap tmX, tmWqkv, tmW1a, tmW1b, tmW2, tmWo, tmHO, tmHOs, tmOs, tmOut;
  const __nv_bfloat16* x;
  const __nv_bfloat16* gate_w;
  const __nv_bfloat16* w1;
  const __nv_bfloat16* w2;
  const __nv_bfloat16* wo;
  __nv_bfloat16* out;
};

DEVI uint32_t smem_u32(const void* p) { return (uint32_t)__cvta_generic_to_shared(p); }
DEVI uint32_t clk32() { uint32_t c; asm volatile("mov.u32 %0, %%clock;" : "=r"(c)); return c; }
DEVI void mbar_init(uint32_t bar, uint32_t cnt) { asm volatile("mbarrier.init.shared::cta.b64 [%0], %1;" ::"r"(bar), "r"(cnt)); }
DEVI void mbar_expect_tx(uint32_t bar, uint32_t bytes) { asm volatile("mbarrier.arrive.expect_tx.shared::cta.b64 _, [%0], %1;" ::"r"(bar), "r"(bytes) : "memory"); }
DEVI void mbar_arrive(uint32_t bar) { asm volatile("mbarrier.arrive.shared::cta.b64 _, [%0];" ::"r"(bar) : "memory"); }
DEVI void mbar_arrive_cluster(uint32_t bar, uint32_t cta) {
  asm volatile("{ .reg .b32 ra; mapa.shared::cluster.u32 ra, %0, %1; mbarrier.arrive.shared::cluster.b64 _, [ra]; }" ::"r"(bar), "r"(cta) : "memory");
}
DEVI void mbar_wait(uint32_t bar, uint32_t parity, uint32_t t0) {
  asm volatile("{ .reg .pred p; .reg .u32 c;\n"
               "mbarrier.try_wait.parity.shared::cta.b64 p, [%0], %1;\n"
               "@p bra DONE_%=;\n"
               "WAIT_%=:\n"
               "mbarrier.try_wait.parity.shared::cta.b64 p, [%0], %1, %4;\n"
               "@p bra DONE_%=;\n"
               "mov.u32 c, %%clock; sub.u32 c, c, %2; setp.lt.u32 p, c, %3;\n"
               "@p bra WAIT_%=;\n"
               "DONE_%=: }" ::"r"(bar), "r"(parity), "r"(t0), "n"(TIMEOUT), "r"(WAIT_HINT_NS) : "memory");
}
DEVI unsigned ld_relaxed(const unsigned* p) { unsigned v; asm volatile("ld.relaxed.gpu.global.u32 %0, [%1];" : "=r"(v) : "l"(p) : "memory"); return v; }
DEVI void flag_wait(const unsigned* p, unsigned target, uint32_t t0) {
  while ((int)(ld_relaxed(p) - target) < 0) { if (clk32() - t0 > TIMEOUT) break; }
}
DEVI void flag_add(unsigned* p) { asm volatile("red.relaxed.gpu.global.add.u32 [%0], 1;" ::"l"(p) : "memory"); }
DEVI void fence_async_smem() { asm volatile("fence.proxy.async.shared::cta;" ::: "memory"); }
DEVI void fence_async_global() { asm volatile("fence.proxy.async.global;" ::: "memory"); }
DEVI void tma_load_2d(uint32_t dst, const CUtensorMap* m, int c0, int c1, uint32_t bar) {
  asm volatile("cp.async.bulk.tensor.2d.shared::cluster.global.mbarrier::complete_tx::bytes [%0], [%1, {%3, %4}], [%2];" ::"r"(dst), "l"(m), "r"(bar), "r"(c0), "r"(c1) : "memory");
}
DEVI void tma_load_3d(uint32_t dst, const CUtensorMap* m, int c0, int c1, int c2, uint32_t bar) {
  asm volatile("cp.async.bulk.tensor.3d.shared::cluster.global.mbarrier::complete_tx::bytes [%0], [%1, {%3, %4, %5}], [%2];"
               ::"r"(dst), "l"(m), "r"(bar), "r"(c0), "r"(c1), "r"(c2) : "memory");
}
DEVI void tma_load_3d_mc(uint32_t dst, const CUtensorMap* m, int c0, int c1, int c2, uint32_t bar) {
  asm volatile("cp.async.bulk.tensor.3d.shared::cluster.global.mbarrier::complete_tx::bytes.multicast::cluster [%0], [%1, {%3, %4, %5}], [%2], %6;"
               ::"r"(dst), "l"(m), "r"(bar), "r"(c0), "r"(c1), "r"(c2), "h"((uint16_t)3) : "memory");
}
DEVI void tma_load_4d_mc(uint32_t dst, const CUtensorMap* m, int c0, int c1, int c2, int c3, uint32_t bar) {
  asm volatile("cp.async.bulk.tensor.4d.shared::cluster.global.mbarrier::complete_tx::bytes.multicast::cluster [%0], [%1, {%3, %4, %5, %6}], [%2], %7;"
               ::"r"(dst), "l"(m), "r"(bar), "r"(c0), "r"(c1), "r"(c2), "r"(c3), "h"((uint16_t)3) : "memory");
}
DEVI void tma_store_2d(const CUtensorMap* m, int c0, int c1, uint32_t src) {
  asm volatile("cp.async.bulk.tensor.2d.global.shared::cta.bulk_group [%0, {%1, %2}], [%3];" ::"l"(m), "r"(c0), "r"(c1), "r"(src) : "memory");
}
DEVI void bulk_store(void* dst, uint32_t src, uint32_t bytes) {
  asm volatile("cp.async.bulk.global.shared::cta.bulk_group [%0], [%1], %2;" ::"l"(dst), "r"(src), "r"(bytes) : "memory");
}
DEVI void bulk_load(uint32_t dst, const void* src, uint32_t bytes, uint32_t bar) {
  asm volatile("cp.async.bulk.shared::cluster.global.mbarrier::complete_tx::bytes [%0], [%1], %2, [%3];" ::"r"(dst), "l"(src), "r"(bytes), "r"(bar) : "memory");
}
DEVI void bulk_commit() { asm volatile("cp.async.bulk.commit_group;" ::: "memory"); }
DEVI void bulk_wait_all() { asm volatile("cp.async.bulk.wait_group 0;" ::: "memory"); }
DEVI void l2_prefetch(const void* p, uint32_t bytes) { asm volatile("cp.async.bulk.prefetch.L2.global [%0], %1;" ::"l"(p), "r"(bytes) : "memory"); }
DEVI void cluster_arrive() { asm volatile("barrier.cluster.arrive.relaxed.aligned;" ::: "memory"); }
DEVI void cluster_wait() { asm volatile("barrier.cluster.wait.aligned;" ::: "memory"); }
template <int ID> DEVI void named_bar(int n) { asm volatile("bar.sync %0, %1;" ::"n"(ID), "r"(n) : "memory"); }
DEVI void wg_bar(int wg) { if (wg == 0) named_bar<1>(128); else named_bar<2>(128); }
DEVI void wgmma_fence() { asm volatile("wgmma.fence.sync.aligned;" ::: "memory"); }
DEVI void wgmma_commit() { asm volatile("wgmma.commit_group.sync.aligned;" ::: "memory"); }
template <int N> DEVI void wgmma_wait() { asm volatile("wgmma.wait_group.sync.aligned %0;" ::"n"(N) : "memory"); }
template <uint32_t LBO> DEVI uint64_t desc_sw128(uint32_t a16) {
  return ((uint64_t)(0x40000000u | (1024 >> 4)) << 32) | (a16 + ((LBO >> 4) << 16));
}
DEVI uint64_t desc_sw64(uint32_t a16) {
  return ((uint64_t)(0x80000000u | (512 >> 4)) << 32) | (a16 + ((512 >> 4) << 16));
}
DEVI uint32_t pack_bf16(float lo, float hi) { uint32_t r; asm("cvt.rn.bf16x2.f32 %0, %1, %2;" : "=r"(r) : "f"(hi), "f"(lo)); return r; }
DEVI void stsm_x4(uint32_t addr, uint32_t r0, uint32_t r1, uint32_t r2, uint32_t r3) {
  asm volatile("stmatrix.sync.aligned.m8n8.x4.shared.b16 [%0], {%1, %2, %3, %4};" ::"r"(addr), "r"(r0), "r"(r1), "r"(r2), "r"(r3) : "memory");
}
DEVI void sts128(uint32_t addr, uint32_t r0, uint32_t r1, uint32_t r2, uint32_t r3) {
  asm volatile("st.shared.v4.b32 [%0], {%1, %2, %3, %4};" ::"r"(addr), "r"(r0), "r"(r1), "r"(r2), "r"(r3) : "memory");
}
DEVI uint4 lds128(uint32_t addr) {
  uint4 v; asm volatile("ld.shared.v4.b32 {%0, %1, %2, %3}, [%4];" : "=r"(v.x), "=r"(v.y), "=r"(v.z), "=r"(v.w) : "r"(addr) : "memory"); return v;
}
DEVI float ex2(float x) { float y; asm("ex2.approx.ftz.f32 %0, %1;" : "=f"(y) : "f"(x)); return y; }

DEVI void wgmma_ss_n64(float (&d)[32], uint64_t da, uint64_t db) {
  asm volatile("wgmma.mma_async.sync.aligned.m64n64k16.f32.bf16.bf16 {%0, %1, %2, %3, %4, %5, %6, %7, %8, %9, %10, %11, %12, %13, %14, %15, %16, %17, %18, %19, %20, %21, %22, %23, %24, %25, %26, %27, %28, %29, %30, %31}, %32, %33, 1, 1, 1, 0, 1;"
    : "+f"(d[0]), "+f"(d[1]), "+f"(d[2]), "+f"(d[3]), "+f"(d[4]), "+f"(d[5]), "+f"(d[6]), "+f"(d[7]), "+f"(d[8]), "+f"(d[9]), "+f"(d[10]), "+f"(d[11]), "+f"(d[12]), "+f"(d[13]), "+f"(d[14]), "+f"(d[15]), "+f"(d[16]), "+f"(d[17]), "+f"(d[18]), "+f"(d[19]), "+f"(d[20]), "+f"(d[21]), "+f"(d[22]), "+f"(d[23]), "+f"(d[24]), "+f"(d[25]), "+f"(d[26]), "+f"(d[27]), "+f"(d[28]), "+f"(d[29]), "+f"(d[30]), "+f"(d[31])
    : "l"(da), "l"(db));
}
DEVI void wgmma_ss_n128(float (&d)[64], uint64_t da, uint64_t db) {
  asm volatile("wgmma.mma_async.sync.aligned.m64n128k16.f32.bf16.bf16 {%0, %1, %2, %3, %4, %5, %6, %7, %8, %9, %10, %11, %12, %13, %14, %15, %16, %17, %18, %19, %20, %21, %22, %23, %24, %25, %26, %27, %28, %29, %30, %31, %32, %33, %34, %35, %36, %37, %38, %39, %40, %41, %42, %43, %44, %45, %46, %47, %48, %49, %50, %51, %52, %53, %54, %55, %56, %57, %58, %59, %60, %61, %62, %63}, %64, %65, 1, 1, 1, 0, 1;"
    : "+f"(d[0]), "+f"(d[1]), "+f"(d[2]), "+f"(d[3]), "+f"(d[4]), "+f"(d[5]), "+f"(d[6]), "+f"(d[7]), "+f"(d[8]), "+f"(d[9]), "+f"(d[10]), "+f"(d[11]), "+f"(d[12]), "+f"(d[13]), "+f"(d[14]), "+f"(d[15]), "+f"(d[16]), "+f"(d[17]), "+f"(d[18]), "+f"(d[19]), "+f"(d[20]), "+f"(d[21]), "+f"(d[22]), "+f"(d[23]), "+f"(d[24]), "+f"(d[25]), "+f"(d[26]), "+f"(d[27]), "+f"(d[28]), "+f"(d[29]), "+f"(d[30]), "+f"(d[31]), "+f"(d[32]), "+f"(d[33]), "+f"(d[34]), "+f"(d[35]), "+f"(d[36]), "+f"(d[37]), "+f"(d[38]), "+f"(d[39]), "+f"(d[40]), "+f"(d[41]), "+f"(d[42]), "+f"(d[43]), "+f"(d[44]), "+f"(d[45]), "+f"(d[46]), "+f"(d[47]), "+f"(d[48]), "+f"(d[49]), "+f"(d[50]), "+f"(d[51]), "+f"(d[52]), "+f"(d[53]), "+f"(d[54]), "+f"(d[55]), "+f"(d[56]), "+f"(d[57]), "+f"(d[58]), "+f"(d[59]), "+f"(d[60]), "+f"(d[61]), "+f"(d[62]), "+f"(d[63])
    : "l"(da), "l"(db));
}
DEVI void wgmma_qk64(float (&d)[32], uint32_t a0, uint32_t a1, uint32_t a2, uint32_t a3, uint64_t db) {
  asm volatile("wgmma.mma_async.sync.aligned.m64n64k16.f32.bf16.bf16 {%0, %1, %2, %3, %4, %5, %6, %7, %8, %9, %10, %11, %12, %13, %14, %15, %16, %17, %18, %19, %20, %21, %22, %23, %24, %25, %26, %27, %28, %29, %30, %31}, {%32, %33, %34, %35}, %36, 0, 1, 1, 0;"
    : "=f"(d[0]), "=f"(d[1]), "=f"(d[2]), "=f"(d[3]), "=f"(d[4]), "=f"(d[5]), "=f"(d[6]), "=f"(d[7]), "=f"(d[8]), "=f"(d[9]), "=f"(d[10]), "=f"(d[11]), "=f"(d[12]), "=f"(d[13]), "=f"(d[14]), "=f"(d[15]), "=f"(d[16]), "=f"(d[17]), "=f"(d[18]), "=f"(d[19]), "=f"(d[20]), "=f"(d[21]), "=f"(d[22]), "=f"(d[23]), "=f"(d[24]), "=f"(d[25]), "=f"(d[26]), "=f"(d[27]), "=f"(d[28]), "=f"(d[29]), "=f"(d[30]), "=f"(d[31])
    : "r"(a0), "r"(a1), "r"(a2), "r"(a3), "l"(db));
}
DEVI void wgmma_pv(float (&d)[8], uint32_t a0, uint32_t a1, uint32_t a2, uint32_t a3, uint64_t db) {
  asm volatile("wgmma.mma_async.sync.aligned.m64n16k16.f32.bf16.bf16 {%0, %1, %2, %3, %4, %5, %6, %7}, {%8, %9, %10, %11}, %12, 1, 1, 1, 1;"
    : "+f"(d[0]), "+f"(d[1]), "+f"(d[2]), "+f"(d[3]), "+f"(d[4]), "+f"(d[5]), "+f"(d[6]), "+f"(d[7])
    : "r"(a0), "r"(a1), "r"(a2), "r"(a3), "l"(db));
}
DEVI void wgmma_pv0(float (&d)[8], uint32_t a0, uint32_t a1, uint32_t a2, uint32_t a3, uint64_t db) {
  asm volatile("wgmma.mma_async.sync.aligned.m64n16k16.f32.bf16.bf16 {%0, %1, %2, %3, %4, %5, %6, %7}, {%8, %9, %10, %11}, %12, 0, 1, 1, 1;"
    : "=f"(d[0]), "=f"(d[1]), "=f"(d[2]), "=f"(d[3]), "=f"(d[4]), "=f"(d[5]), "=f"(d[6]), "=f"(d[7])
    : "r"(a0), "r"(a1), "r"(a2), "r"(a3), "l"(db));
}

template <int N> struct Acc { float a[64]; float b[(N - 128) / 2]; DEVI float& operator[](int i) { return i < 64 ? a[i] : b[i - 64]; } };
template <> struct Acc<128> { float a[64]; DEVI float& operator[](int i) { return a[i]; } };
template <int N> DEVI void wgmma_ss(Acc<N>& d, uint64_t da, uint64_t db) {
  wgmma_ss_n128(d.a, da, db);
  if constexpr (N == 192) wgmma_ss_n64(d.b, da, db + 256);
  if constexpr (N == 256) wgmma_ss_n128(d.b, da, db + 256);
}

DEVI int oh_chunk(int j, int i, int& need) {
  if (j & 1) {
    if (i >= 3 && i < 7) { need = 16 + 2 * (i - 3); return 24 + (i - 3); }
    if (i >= 7) i -= 4;
  }
  const int g = i / 3, o = (j + 2 * g) & 7;
  need = o;
  return 3 * o + (i - 3 * g);
}

DEVI int a_slot(int e, int ebig) { return e < ebig ? 1 + (e & 3) : (e - ebig + 5) & 7; }

struct Ctx {
  uint32_t sbase, bars, peer, t0, a16, b16;
  int wg, lane;
  int ai, bi; uint32_t aph, bph;
  int brem, ae;
  int pa, pb;
};

DEVI void release_prev(Ctx& c) {
  if (c.pb >= 0) {
    if (c.lane == 0) mbar_arrive(c.bars + 8 * (BAR_EMPTYB + c.pb));
    if (c.lane == 1) mbar_arrive_cluster(c.bars + 8 * (BAR_EMPTYB + c.pb), c.peer);
  }
  if (c.pa >= 0 && c.lane == 2) mbar_arrive(c.bars + 8 * (BAR_EMPTYA + c.pa));
}

DEVI void gemm_wait(Ctx& c) {
  asm volatile("{ .reg .pred p, q; .reg .u32 c;\n"
               "mbarrier.try_wait.parity.shared::cta.b64 p, [%0], %1;\n"
               "mbarrier.try_wait.parity.shared::cta.b64 q, [%2], %3;\n"
               "and.pred p, p, q;\n"
               "@p bra DONE_%=;\n"
               "WAIT_%=:\n"
               "mbarrier.try_wait.parity.shared::cta.b64 p, [%0], %1, %6;\n"
               "mbarrier.try_wait.parity.shared::cta.b64 q, [%2], %3, %6;\n"
               "and.pred p, p, q;\n"
               "@p bra DONE_%=;\n"
               "mov.u32 c, %%clock; sub.u32 c, c, %4; setp.lt.u32 p, c, %5;\n"
               "@p bra WAIT_%=;\n"
               "DONE_%=: }" ::"r"(c.bars + 8 * (BAR_FULLA + c.ai)), "r"((c.aph >> c.ai) & 1), "r"(c.bars + 8 * (BAR_FULLB + c.bi)), "r"(c.bph), "r"(c.t0),
               "n"(TIMEOUT), "r"(WAIT_HINT_NS) : "memory");
}
template <int N, bool SHALLOW>
DEVI void gemm_group(Acc<N>& acc, Ctx& c, int g, int& npa, int& npb) {
  const uint32_t a16 = c.a16 + c.ai * (SLOT >> 4);
  const uint32_t b16 = c.b16 + c.bi * (SLOT >> 4);
  bool adv;
  if constexpr (N >= 192) {
    const uint32_t a2 = a16 + (g & 1) * 4;
    wgmma_ss<N>(acc, desc_sw128<16>(a2), desc_sw128<2048>(b16));
    if (SHALLOW) { wgmma_commit(); wgmma_wait<SHW>(); }
    wgmma_ss<N>(acc, desc_sw128<16>(a2 + 2), desc_sw128<2048>(b16 + 512));
    adv = g & 1;
  } else {
#pragma unroll
    for (int s = 0; s < 4; s++) {
      wgmma_ss<N>(acc, desc_sw128<16>(a16 + s * 2), desc_sw128<4096>(b16 + (s >> 1) * 512 + (s & 1) * 128));
      if (SHALLOW && s < 3 && (SHG == 1 || s == 1)) { wgmma_commit(); wgmma_wait<SHW>(); }
    }
    adv = true;
  }
  wgmma_commit();
  npb = c.brem > 0 ? c.bi : -1;
  c.brem--;
  if (++c.bi == NB) { c.bi = 0; c.bph ^= 1; }
  npa = -1;
  if (adv) { npa = c.ai; c.aph ^= 1u << c.ai; c.ae++; c.ai = 1 + (c.ae & 3); }
}

template <int N, bool SHALLOW = false>
DEVI void bare_groups(Acc<N>& acc, Ctx& c, int g0, int g1) {
  for (int g = g0; g < g1; g++) {
    int npa, npb;
    gemm_wait(c);
    wgmma_fence();
    gemm_group<N, SHALLOW>(acc, c, g, npa, npb);
    wgmma_wait<SHALLOW ? SHW : 1>();
    release_prev(c);
    c.pa = npa; c.pb = npb;
  }
}
DEVI void drain(Ctx& c) {
  wgmma_wait<0>();
  release_prev(c);
  c.pa = c.pb = -1;
}

constexpr float SC = 0.25f * 1.4426950408889634f;

#define ONCE _Pragma("unroll 1") for (unsigned once_ = 0; once_ < gridDim.y; once_++)

struct Gate { float g0, g1; };

DEVI void kill32(float (&S)[32]) {
#pragma unroll
  for (int i = 0; i < 32; i++) S[i] = __int_as_float(0xff800000);
}
DEVI void row_max(const float (&S)[32], float& x0, float& x1) {
  float y0 = S[1], y1 = S[3];
  x0 = fmaxf(x0, S[0]); x1 = fmaxf(x1, S[2]);
#pragma unroll
  for (int n = 1; n < 8; n++) {
    x0 = fmaxf(x0, S[4 * n]); y0 = fmaxf(y0, S[4 * n + 1]); x1 = fmaxf(x1, S[4 * n + 2]); y1 = fmaxf(y1, S[4 * n + 3]);
  }
  x0 = fmaxf(x0, y0); x1 = fmaxf(x1, y1);
}
DEVI void quad_max(float& x0, float& x1) {
  x0 = fmaxf(x0, __shfl_xor_sync(0xffffffffu, x0, 1)); x1 = fmaxf(x1, __shfl_xor_sync(0xffffffffu, x1, 1));
  x0 = fmaxf(x0, __shfl_xor_sync(0xffffffffu, x0, 2)); x1 = fmaxf(x1, __shfl_xor_sync(0xffffffffu, x1, 2));
}
DEVI void exp32(const float (&S)[32], float (&E)[32], float n0, float n1, float (&l)[4]) {
#pragma unroll
  for (int i = 0; i < 32; i++) { E[i] = ex2(fmaf(S[i], SC, (i & 2) ? n1 : n0)); l[i & 3] += E[i]; }
}
DEVI void pack32(const float (&E)[32], uint32_t (&P)[16]) {
#pragma unroll
  for (int i = 0; i < 16; i++) P[i] = pack_bf16(E[2 * i], E[2 * i + 1]);
}
template <bool FIRST> DEVI void pv4(float (&O)[8], const uint32_t (&P)[16], uint32_t v16) {
  if (FIRST) wgmma_pv0(O, P[0], P[1], P[2], P[3], desc_sw64(v16)); else wgmma_pv(O, P[0], P[1], P[2], P[3], desc_sw64(v16));
#pragma unroll
  for (int k = 1; k < 4; k++) wgmma_pv(O, P[4 * k], P[4 * k + 1], P[4 * k + 2], P[4 * k + 3], desc_sw64(v16 + k * 64));
}
DEVI bool wg_any(int wg, bool v) {
  uint32_t r;
  if (wg == 0) asm volatile("{ .reg .pred p, q; setp.ne.u32 p, %1, 0; bar.red.or.pred q, 4, 128, p; selp.u32 %0, 1, 0, q; }" : "=r"(r) : "r"((uint32_t)v) : "memory");
  else asm volatile("{ .reg .pred p, q; setp.ne.u32 p, %1, 0; bar.red.or.pred q, 5, 128, p; selp.u32 %0, 1, 0, q; }" : "=r"(r) : "r"((uint32_t)v) : "memory");
  return r != 0;
}
DEVI void get_gate(Gate& g, uint32_t sbase, int row16, int lane, uint32_t t0) {
  mbar_wait(sbase + OFF_BAR + 8 * BAR_GIN, 0, t0);
  const uint32_t a = sbase + OFF_GIN + (row16 * 16 + (lane >> 2)) * 4;
  asm volatile("ld.shared.f32 %0, [%1];" : "=f"(g.g0) : "r"(a) : "memory");
  asm volatile("ld.shared.f32 %0, [%1];" : "=f"(g.g1) : "r"(a + 32) : "memory");
}

DEVI void attention(uint32_t sbase, int aw, int wi, int lane, int rb, uint32_t t0) {
  const uint32_t bars = sbase + OFF_BAR;
  const uint32_t kvb = ((sbase & 0x3FFFF) + OFF_KV + aw * 4096) >> 4;
  const int cmin = 4 - 2 * rb - aw;
  const int rowc = wi * 16 + (lane >> 2) - (lane & 3) * 2;
  const uint32_t qst = sbase + OFF_A + aw * 8192;
  const float NINF = __int_as_float(0xff800000);
  const int tlo = max(cmin, 1);
#pragma unroll 1
  for (int h = 0; h < 4; h++) {
    const uint32_t kb = kvb + (h & 1) * (KVBUF >> 4);
    const uint4 q = lds128(qst + h * 2048 + (wi * 32 + lane) * 16);
    float O[8], l0, l1;
    float xt0 = NINF, xt1 = NINF;
    mbar_wait(bars + 8 * (BAR_KVFULL + (h & 1)), h >> 1, t0);
#pragma unroll 1
    for (int attempt = 0; attempt < 2; attempt++) {
      float l[4] = {0.f, 0.f, 0.f, 0.f}, n0, n1;
      uint32_t P[16];
      {
        float S[32], F[32];
        wgmma_fence();
        wgmma_qk64(S, q.x, q.y, q.z, q.w, desc_sw64(kb + 4 * 256));
        wgmma_qk64(F, q.x, q.y, q.z, q.w, desc_sw64(kb));
        wgmma_commit();
        wgmma_wait<0>();
        for (int r = 0; r < (cmin > 0 ? 1 : 0); r++) kill32(F);
        float M[32];
#pragma unroll
        for (int i = 0; i < 32; i++) M[i] = ((i >> 2) * 8 + (i & 1) > rowc + (i & 2) * 4) ? F[i] : S[i];
        float x0 = xt0, x1 = xt1;
        row_max(M, x0, x1);
        quad_max(x0, x1);
        n0 = -x0 * SC; n1 = -x1 * SC;
        exp32(M, M, n0, n1, l);
        pack32(M, P);
        uint32_t PF[16];
#pragma unroll
        for (int i = 0; i < 16; i++) {
          const int col = (i >> 1) * 8, r = rowc + (i & 1) * 8;
          const uint32_t m = (col > r ? 0xFFFFu : 0u) | (col + 1 > r ? 0xFFFF0000u : 0u);
          PF[i] = P[i] & m; P[i] &= ~m;
        }
        wgmma_fence();
        pv4<true>(O, PF, kb + 2);
        wgmma_commit();
        wgmma_wait<0>();
      }
      int t = 3;
#pragma unroll 1
      for (; t >= tlo; t--) {
        float S[32];
        wgmma_fence();
        wgmma_qk64(S, q.x, q.y, q.z, q.w, desc_sw64(kb + t * 256));
        wgmma_commit();
        pv4<false>(O, P, kb + (t + 1) * 256 + 2);
        wgmma_commit();
        wgmma_wait<1>();
        ONCE { exp32(S, S, n0, n1, l); }
        wgmma_wait<0>();
        pack32(S, P);
      }
      wgmma_fence();
      pv4<false>(O, P, kb + (t + 1) * 256 + 2);
      wgmma_commit();
      l0 = l[0] + l[1]; l1 = l[2] + l[3];
      l0 += __shfl_xor_sync(0xffffffffu, l0, 1); l1 += __shfl_xor_sync(0xffffffffu, l1, 1);
      l0 += __shfl_xor_sync(0xffffffffu, l0, 2); l1 += __shfl_xor_sync(0xffffffffu, l1, 2);
      const bool redo = wg_any(aw, attempt == 0 && !(l0 < 1e18f && l1 < 1e18f));
      wgmma_wait<0>();
      if (!redo) break;
#pragma unroll 1
      for (int u = 3; u >= tlo; u--) {
        float S[32];
        wgmma_fence();
        wgmma_qk64(S, q.x, q.y, q.z, q.w, desc_sw64(kb + u * 256));
        wgmma_commit();
        wgmma_wait<0>();
        row_max(S, xt0, xt1);
      }
    }
    if (lane == 0) mbar_arrive(bars + 8 * (h == 3 ? BAR_ATTDONE : BAR_KVEMPTY + (h & 1)));
    Gate g;
    get_gate(g, sbase, aw * 4 + wi, lane, t0);
    const float c0 = __fdividef(g.g0, l0), c1 = __fdividef(g.g1, l1);
    const int mi = lane >> 3;
    const int srow = wi * 16 + (lane & 7) + 8 * (mi & 1);
    stsm_x4(qst + h * 2048 + srow * 32 + (mi >> 1) * 16, pack_bf16(O[0] * c0, O[1] * c0), pack_bf16(O[2] * c1, O[3] * c1),
            pack_bf16(O[4] * c0, O[5] * c0), pack_bf16(O[6] * c1, O[7] * c1));
    fence_async_smem();
    __syncwarp();
    if (lane == 0) mbar_arrive(bars + 8 * (BAR_OST + aw));
  }
}

template <int CH, int N>
DEVI void store_h_chunk(Acc<N>& acc, uint32_t base  , int lane, float s0, float s1) {
  const int mi = lane >> 3;
#pragma unroll
  for (int tp = 0; tp < 4; tp++) {
    const int t = CH * 8 + tp * 2;
    const uint32_t r0 = pack_bf16(fmaxf(acc[4 * t + 0], 0.f) * s0, fmaxf(acc[4 * t + 1], 0.f) * s0);
    const uint32_t r1 = pack_bf16(fmaxf(acc[4 * t + 2], 0.f) * s1, fmaxf(acc[4 * t + 3], 0.f) * s1);
    const uint32_t r2 = pack_bf16(fmaxf(acc[4 * t + 4], 0.f) * s0, fmaxf(acc[4 * t + 5], 0.f) * s0);
    const uint32_t r3 = pack_bf16(fmaxf(acc[4 * t + 6], 0.f) * s1, fmaxf(acc[4 * t + 7], 0.f) * s1);
    stsm_x4(base + (((tp * 2 + (mi >> 1)) ^ (lane & 7)) << 4), r0, r1, r2, r3);
  }
}

template <int N>
DEVI void phase_q(Ctx& c, int warp) {
  Acc<N> acc;
#pragma unroll
  for (int i = 0; i < N / 2; i++) acc[i] = 0.f;
  bare_groups<N>(acc, c, 0, 16);
  drain(c);
  const int lane = c.lane, mi = lane >> 3;
  const int row = warp * 16 + (lane & 7) + 8 * (mi & 1);
  const int sw = (row >> 1) & 3;
#pragma unroll
  for (int hh = 0; hh < 4; hh++) {
    const uint32_t base = c.sbase + OFF_KV + hh * 8192 + row * 64;
#pragma unroll
    for (int kv = 0; kv < 2; kv++) {
      const int t = 8 + kv * 8 + 2 * hh;
      stsm_x4(base + (((kv * 2 + (mi >> 1)) ^ sw) << 4),
              pack_bf16(acc[4 * t + 0], acc[4 * t + 1]), pack_bf16(acc[4 * t + 2], acc[4 * t + 3]),
              pack_bf16(acc[4 * t + 4], acc[4 * t + 5]), pack_bf16(acc[4 * t + 6], acc[4 * t + 7]));
    }
  }
  fence_async_smem();
  __syncwarp();
  if (lane == 0) mbar_arrive(c.bars + 8 * BAR_STG);
#pragma unroll
  for (int hh = 0; hh < 4; hh++)
    sts128(c.sbase + OFF_A + c.wg * 8192 + hh * 2048 + ((warp & 3) * 32 + lane) * 16,
           pack_bf16(acc[8 * hh], acc[8 * hh + 1]), pack_bf16(acc[8 * hh + 2], acc[8 * hh + 3]),
           pack_bf16(acc[8 * hh + 4], acc[8 * hh + 5]), pack_bf16(acc[8 * hh + 6], acc[8 * hh + 7]));
  __syncwarp();
  if (lane == 0) mbar_arrive(c.bars + 8 * (BAR_QRDY + c.wg));
  if constexpr (N == 256) {
    Gate g;
    get_gate(g, c.sbase, warp, lane, c.t0);
    store_h_chunk<3>(acc, c.sbase + OFF_KV + 32768 + row * 128, lane, 1.f - g.g0, 1.f - g.g1);
    fence_async_smem();
    __syncwarp();
    if (lane == 0) mbar_arrive(c.bars + 8 * BAR_STE);
  }
}

DEVI void first_loads(const Params& P, uint32_t sbase, int e, int j, int rb) {
  const uint32_t bars = sbase + OFF_BAR, fb = bars + 8 * (BAR_FULLB + e), fa = bars + 8 * (BAR_FULLA + 1 + e);
  mbar_expect_tx(fa, 16384);
  mbar_expect_tx(fb, (j & 1) ? 12288 : 16384);
  if (e == 0) tma_load_2d(sbase + OFF_A + SLOT, &P.tmX, 0, rb * 128, fa);
#pragma unroll
  for (int r = 0; r < 2; r++) {
    tma_load_3d(sbase + OFF_B + e * SLOT + r * 8192, &P.tmWqkv, 64 * j, e * 32 + r * 16, 0, fb);
    if (!(j & 1)) tma_load_3d(sbase + OFF_B + e * SLOT + r * 8192 + 6144, &P.tmW1a, 0, e * 32 + r * 16, 24 + (j >> 1), fb);
  }
  if (e == 1) tma_load_2d(sbase + OFF_A + 2 * SLOT, &P.tmX, 64, rb * 128, fa);
}

__global__ void __cluster_dims__(2, 1, 1) __launch_bounds__(640, 1) fused_kernel(const __grid_constant__ Params P) {
  extern __shared__ uint8_t smem_raw[];
  const uint32_t sbase = (smem_u32(smem_raw) + 1023u) & ~1023u;
  const uint32_t bars = sbase + OFF_BAR;
  const int tid = threadIdx.x, warp = tid >> 5, lane = tid & 31;
  const uint32_t rank = blockIdx.x & 1, peer = rank ^ 1;
  const int j = (blockIdx.x >> 1) & 7, rb = ((blockIdx.x >> 4) << 1) | rank;
  const uint32_t t0 = clk32();

  const int typeB = j & 1;
  if (tid == 544) {
    for (int s = 0; s < NA2; s++) mbar_init(bars + 8 * (BAR_FULLA + s), 1);
    for (int s = 0; s < NB; s++) mbar_init(bars + 8 * (BAR_FULLB + s), 1);
    fence_async_smem();
  } else if (tid < 10) {
    asm volatile("prefetch.tensormap [%0];" ::"l"(&P.tmX + tid) : "memory");
  } else if (tid == 512) {
    for (int s = 0; s < NA2; s++) mbar_init(bars + 8 * (BAR_EMPTYA + s), 9);
    for (int s = 0; s < NB; s++) mbar_init(bars + 8 * (BAR_EMPTYB + s), 16);
  } else if (tid == 576) {
    for (int s = 0; s < 2; s++) { mbar_init(bars + 8 * (BAR_KVFULL + s), 1); mbar_init(bars + 8 * (BAR_KVEMPTY + s), 8); mbar_init(bars + 8 * (BAR_OST + s), 4); mbar_init(bars + 8 * (BAR_QRDY + s), 4); }
    mbar_init(bars + 8 * BAR_STG, 8); mbar_init(bars + 8 * BAR_STE, 8); mbar_init(bars + 8 * BAR_KVOK, 1);
    mbar_init(bars + 8 * BAR_PIN, 1); mbar_init(bars + 8 * BAR_ATTDONE, 8); mbar_init(bars + 8 * BAR_GIN, 1);
  }
  if (tid >= 512 && lane == 0) asm volatile("fence.mbarrier_init.release.cluster;" ::: "memory");
  const unsigned ep1 = ld_relaxed(&g_epoch) + 1;
  __syncwarp();
  cluster_arrive();
  if (tid == 544) { first_loads(P, sbase, 0, j, rb); first_loads(P, sbase, 1, j, rb); }
  __syncwarp();

  const int on = 12 + 4 * typeB;

  if (warp < 8) {
    asm volatile("setmaxnreg.inc.sync.aligned.u32 160;");
    cluster_wait();
    const int wg = __shfl_sync(0xffffffffu, warp >> 2, 0), wi = warp & 3;
    Ctx c{sbase, bars, peer, t0, ((sbase & 0x3FFFF) + OFF_A + wg * 8192) >> 4, ((sbase & 0x3FFFF) + OFF_B) >> 4, wg, lane, 1, 0, 0u, 0u, 32 + on + 4 - NB, 0, -1, -1};
    if (tid == 0) TR(0);
    if (typeB) phase_q<192>(c, warp);
    else phase_q<256>(c, warp);
    asm volatile("setmaxnreg.dec.sync.aligned.u32 128;");
    if (tid == 0) TR(2);
    {
      Acc<192> acc;
#pragma unroll
      for (int i = 0; i < 96; i++) acc[i] = 0.f;
      bare_groups<192, SH>(acc, c, 0, 16);
      Gate at;
      get_gate(at, sbase, warp, lane, t0);
      drain(c);
      if (tid == 0) TR(1);
      const uint32_t rowoff = (warp * 16 + (lane & 7) + 8 * ((lane >> 3) & 1)) * 128;
      const float s0 = 1.f - at.g0, s1 = 1.f - at.g1;
      constexpr int e0 = 1, e1 = 2, e2 = 3;
      mbar_wait(bars + 8 * (BAR_FULLA + e0), 0, t0);
      store_h_chunk<0>(acc, sbase + OFF_A + e0 * SLOT + rowoff, lane, s0, s1);
      mbar_wait(bars + 8 * (BAR_FULLA + e1), 0, t0);
      store_h_chunk<1>(acc, sbase + OFF_A + e1 * SLOT + rowoff, lane, s0, s1);
      mbar_wait(bars + 8 * (BAR_FULLA + e2), 0, t0);
      store_h_chunk<2>(acc, sbase + OFF_A + e2 * SLOT + rowoff, lane, s0, s1);
    }
    fence_async_smem();
    wg_bar(wg);
    if (lane == 0) mbar_arrive(bars + 8 * BAR_STG);
    if (tid == 0) TR(4);
    float own[32];
    {
      Acc<128> acc;
#pragma unroll
      for (int i = 0; i < 64; i++) acc[i] = 0.f;
      bare_groups<128, SH>(acc, c, 0, on);
      drain(c);
      if (tid == 0) TR(5);
      named_bar<3>(256);
      const uint32_t pst = sbase + OFF_B + ((30 + on) % NB) * SLOT + wg * 8192 + (tid & 127) * 16;
#pragma unroll
      for (int i = 0; i < 4; i++) {
        uint32_t r[4];
#pragma unroll
        for (int k = 0; k < 4; k++) {
          const int idx = 8 * i + 2 * k;
          const float lo = typeB ? acc[idx] : acc[32 + idx], hi = typeB ? acc[idx + 1] : acc[32 + idx + 1];
          r[k] = pack_bf16(lo, hi);
        }
        sts128(pst + i * 2048, r[0], r[1], r[2], r[3]);
      }
#pragma unroll
      for (int i = 0; i < 32; i++) own[i] = typeB ? acc[32 + i] : acc[i];
      fence_async_smem();
      __syncwarp();
      if (lane == 0) mbar_arrive(bars + 8 * BAR_STG);
    }
    for (int g = 0; g < 8; g++) {
      const uint32_t a16 = c.a16 + c.ai * (SLOT >> 4);
      const uint32_t b16 = c.b16 + c.bi * (SLOT >> 4) + (g & 1) * 512;
      gemm_wait(c);
      wgmma_fence();
#pragma unroll
      for (int s = 0; s < 4; s++) wgmma_ss_n64(own, desc_sw128<16>(a16 + s * 2), desc_sw128<2048>(b16 + s * 128));
      wgmma_commit();
      c.ae++; c.ai = a_slot(c.ae, 20 + on);
      if (g & 1) { if (++c.bi == NB) { c.bi = 0; c.bph ^= 1; } }
    }
    wgmma_wait<0>();
    if (tid == 0) TR(6);
    mbar_wait(bars + 8 * BAR_PIN, 0, t0);
    if (tid == 0) TR(7);
    {
      const uint32_t pin = sbase + OFF_B + ((31 + on) % NB) * SLOT + wg * 8192 + (tid & 127) * 16;
      wg_bar(wg);
      const uint32_t ob = sbase + OFF_A + SLOT + wg * 8192;
      const uint32_t orow = ob + (wi * 16 + (lane & 7) + 8 * ((lane >> 3) & 1)) * 128;
#pragma unroll
      for (int i = 0; i < 4; i++) {
        const uint4 v = lds128(pin + i * 2048);
        const uint32_t r[4] = {v.x, v.y, v.z, v.w};
        uint32_t o[4];
#pragma unroll
        for (int k = 0; k < 4; k++) {
          const int idx = 8 * i + 2 * k;
          o[k] = pack_bf16(own[idx] + __uint_as_float(r[k] << 16), own[idx + 1] + __uint_as_float(r[k] & 0xffff0000u));
        }
        stsm_x4(orow + (((i * 2 + (lane >> 4)) ^ (lane & 7)) << 4), o[0], o[1], o[2], o[3]);
      }
      fence_async_smem();
      __syncwarp();
      if (lane == 0) {
        tma_store_2d(&P.tmOut, j * 64, rb * 128 + warp * 16, ob + wi * 2048);
        bulk_commit();
        asm volatile("cp.async.bulk.wait_group.read 0;" ::: "memory");
      }
    }
    if (tid == 0) TR(8);
  } else if (warp < 16) {
    asm volatile("setmaxnreg.dec.sync.aligned.u32 56;");
    cluster_wait();
    const int aw = __shfl_sync(0xffffffffu, (warp >> 2) & 1, 0);
    {
      const int rowg = rb * 128 + j * 16 + (warp - 8) * 2;
      const uint4* gw = (const uint4*)P.gate_w;
      const uint4* xr = (const uint4*)(P.x + (size_t)rowg * DM);
      mbar_wait(bars + 8 * (BAR_FULLB + 1), 0, t0);
      const uint4 w0 = __ldg(gw + lane), w1 = __ldg(gw + 32 + lane);
      const uint4 xa0 = __ldg(xr + lane), xa1 = __ldg(xr + 32 + lane), xb0 = __ldg(xr + 64 + lane), xb1 = __ldg(xr + 96 + lane);
#pragma unroll
      for (int i = 0; i < 4; i++) sts128(sbase + OFF_KV + 32768 + i * 4096 + (tid - 256) * 16, 0u, 0u, 0u, 0u);
      const uint32_t wa[8] = {w0.x, w0.y, w0.z, w0.w, w1.x, w1.y, w1.z, w1.w};
      const uint32_t xa[8] = {xa0.x, xa0.y, xa0.z, xa0.w, xa1.x, xa1.y, xa1.z, xa1.w};
      const uint32_t xb[8] = {xb0.x, xb0.y, xb0.z, xb0.w, xb1.x, xb1.y, xb1.z, xb1.w};
      float za = 0.f, zb = 0.f;
#pragma unroll
      for (int e = 0; e < 8; e++) {
        const float wl = __uint_as_float(wa[e] << 16), wh = __uint_as_float(wa[e] & 0xffff0000u);
        za = fmaf(__uint_as_float(xa[e] << 16), wl, za); za = fmaf(__uint_as_float(xa[e] & 0xffff0000u), wh, za);
        zb = fmaf(__uint_as_float(xb[e] << 16), wl, zb); zb = fmaf(__uint_as_float(xb[e] & 0xffff0000u), wh, zb);
      }
#pragma unroll
      for (int o = 16; o > 0; o >>= 1) { za += __shfl_xor_sync(0xffffffffu, za, o); zb += __shfl_xor_sync(0xffffffffu, zb, o); }
      if (lane < 2) asm volatile("st.shared.f32 [%0], %1;" ::"r"(sbase + OFF_GST + (warp - 8) * 8 + lane * 4), "f"(1.f / (1.f + __expf(-(lane ? zb : za)))) : "memory");
      fence_async_smem();
      named_bar<6>(256);
      if (tid == 256) {
        bulk_store(&g_gate[rb * 128 + j * 16], sbase + OFF_GST, 64);
        bulk_commit(); bulk_wait_all();
        flag_add(&g_flag_g[rb * FS]);
        flag_wait(&g_flag_g[rb * FS], ep1 * 8, t0);
        fence_async_global();
        mbar_expect_tx(bars + 8 * BAR_GIN, 512);
        bulk_load(sbase + OFF_GIN, &g_gate[rb * 128], 512, bars + 8 * BAR_GIN);
        TR(10);
      }
      __syncwarp();
    }
    mbar_wait(bars + 8 * (BAR_QRDY + aw), 0, t0);
    asm volatile("setmaxnreg.inc.sync.aligned.u32 96;");
    attention(sbase, aw, warp & 3, lane, rb, t0);
    if (tid == 256) TR(3);
  } else {
    asm volatile("setmaxnreg.dec.sync.aligned.u32 32;");
    if (warp == 16) {
      __syncwarp();
      cluster_wait();
      if (lane == 0) {
        int bi = 2; uint32_t bph = 1;
        const int nb = 32 + on + 4;
        for (int eb = 2; eb < nb; eb++) {
          if (eb == 4 || eb == 6) {
            const int ea = eb >> 1;
            mbar_expect_tx(bars + 8 * (BAR_FULLA + 1 + ea), 16384);
            tma_load_2d(sbase + OFF_A + (1 + ea) * SLOT, &P.tmX, ea * 64, rb * 128, bars + 8 * (BAR_FULLA + 1 + ea));
          }
          const uint32_t fb = bars + 8 * (BAR_FULLB + bi), dst = sbase + OFF_B + bi * SLOT + rank * 8192;
          mbar_wait(bars + 8 * (BAR_EMPTYB + bi), bph, t0);
          if (eb < 16) {
            mbar_expect_tx(fb, typeB ? 12288 : 16384);
            tma_load_3d_mc(dst, &P.tmWqkv, 64 * j, eb * 32 + rank * 16, 0, fb);
            if (!typeB) tma_load_3d_mc(dst + 6144, &P.tmW1a, 0, eb * 32 + rank * 16, 24 + (j >> 1), fb);
          }
          else if (eb < 32) { mbar_expect_tx(fb, 12288); tma_load_3d_mc(dst, &P.tmW1b, 0, (eb - 16) * 32 + rank * 16, 3 * j, fb); }
          else if (eb < 32 + on) { int ow; const int ch = oh_chunk(j, eb - 32, ow); mbar_expect_tx(fb, 16384); tma_load_3d_mc(dst, &P.tmW2, 0, ch * 64 + rank * 32, (j >> 1) * 2, fb); }
          else { mbar_expect_tx(fb, 16384); tma_load_4d_mc(dst, &P.tmWo, 64 * j, 0, eb - 32 - on, rank * 4, fb); }
          if (++bi == NB) { bi = 0; bph ^= 1; }
          if (eb == PFAT) {
            const int b = blockIdx.x;
            l2_prefetch((const uint8_t*)P.w1 + b * 14336, 14336);
            l2_prefetch((const uint8_t*)P.w2 + b * 14336, 14336);
            l2_prefetch((const uint8_t*)P.wo + b * 4096, 4096);
          }
        }
      }
    } else if (warp == 17) {
      cluster_wait();
      if (lane == 0) {
        for (int ea = 1; ea < 5; ea++) mbar_arrive(bars + 8 * (BAR_EMPTYA + ea));
        uint32_t aph = 0xE1;
        const int na = 16 + on + 8;
        unsigned ready = 0;
        for (int ea = 4; ea < na; ea++) {
          const int ai = a_slot(ea, 20 + on);
          const uint32_t fb = bars + 8 * (BAR_FULLA + ai), dst = sbase + OFF_A + ai * SLOT;
          int ch = ea & 7, need = -1;
          if (ea >= 16 + on) { need = 8 + ea - 16 - on; ch = 20 + need; }
          else if (ea >= 19) ch = oh_chunk(j, ea - 16, need);
          if (need >= 0 && !((ready >> need) & 1)) {
            const unsigned* fp = need < 8 ? &g_flag_h[rb * 8 * FS] : need < 16 ? &g_flag_o[rb * 8 * FS] : &g_flag_e[rb * 8 * FS];
            const unsigned tgt = (need & 8) ? ep1 * 4 : ep1;
            do {
              unsigned v[8];
#pragma unroll
              for (int i = 0; i < 8; i++) v[i] = ld_relaxed(fp + i * FS);
#pragma unroll
              for (int i = 0; i < 8; i++) if ((int)(v[i] - tgt) >= 0) ready |= 1u << (i + (need & 24));
            } while (!((ready >> need) & 1) && clk32() - t0 < TIMEOUT);
            fence_async_global();
          }
          if (ea == 20 + on) mbar_wait(bars + 8 * BAR_ATTDONE, 0, t0);
          mbar_wait(bars + 8 * (BAR_EMPTYA + ai), (aph >> ai) & 1, t0);
          if (ea >= 16 && ea < 19) mbar_arrive(fb);
          else {
            mbar_arrive(bars + 8 * (BAR_EMPTYA + ai));
            mbar_expect_tx(fb, 16384);
            tma_load_2d(dst, ea < 16 ? &P.tmX : &P.tmHO, ch * 64, rb * 128, fb);
          }
          TR(24 + ea);
          aph ^= 1u << ai;
        }
      }
    } else {
      const int wg = warp - 18;
      cluster_wait();
      if (lane == 0 && wg == 0) {
        const uint32_t stg = bars + 8 * BAR_STG;
        mbar_wait(stg, 0, t0);
        for (int hh = 0; hh < 4; hh++) bulk_store(g_kv + ((size_t)(4 * j + hh) * SEQ + rb * 128) * 64, sbase + OFF_KV + hh * 8192, 8192);
        bulk_commit(); bulk_wait_all();
        flag_add(&g_flag_kv[(rb * 8 + j) * FS]);
        TR(21);
        if (!typeB) {
          mbar_wait(bars + 8 * BAR_STE, 0, t0);
          tma_store_2d(&P.tmHO, (24 + (j >> 1)) * 64, rb * 128, sbase + OFF_KV + 32768);
          bulk_commit(); bulk_wait_all();
          flag_add(&g_flag_e[(rb * 8 + j) * FS]);
        }
        mbar_arrive(bars + 8 * BAR_KVOK);
        mbar_wait(stg, 1, t0);
        for (int i = 0; i < 3; i++) tma_store_2d(&P.tmHO, (3 * j + i) * 64, rb * 128, sbase + OFF_A + (1 + i) * SLOT);
        bulk_commit(); bulk_wait_all();
        flag_add(&g_flag_h[(rb * 8 + j) * FS]);
        for (int i = 0; i < 3; i++) mbar_arrive(bars + 8 * (BAR_EMPTYA + 1 + i));
        TR(22);
        {
          const unsigned old = atomicAdd(&g_done, 1u);
          if (old == gridDim.x - 1) { g_done = 0; *(volatile unsigned*)&g_epoch = ep1; }
        }
        mbar_wait(stg, 0, t0);
        bulk_store(g_part + (size_t)(rb * 8 + (j ^ 1)) * 16384, sbase + OFF_B + ((30 + on) % NB) * SLOT, 16384);
        bulk_commit(); bulk_wait_all();
        flag_add(&g_flag_p[(rb * 8 + (j ^ 1)) * FS]);
        TR(23);
        flag_wait(&g_flag_p[(rb * 8 + j) * FS], ep1, t0);
        fence_async_global();
        mbar_expect_tx(bars + 8 * BAR_PIN, 16384);
        bulk_load(sbase + OFF_B + ((31 + on) % NB) * SLOT, g_part + (size_t)(rb * 8 + j) * 16384, 16384, bars + 8 * BAR_PIN);
      } else if (lane == 0) {
        const int nblk = rb >= 2 ? 3 : rb + 1;
        const uint32_t kvbytes = nblk * 8192;
        const uint8_t* kvsrc = g_kv + ((size_t)(4 * j) * SEQ + (rb + 1 - nblk) * 128) * 64;
        const uint32_t kvdst = sbase + OFF_KV + (3 - nblk) * 8192;
        {
          const unsigned* f0 = &g_flag_kv[(rb * 8 + j) * FS];
          const unsigned* f1 = rb >= 1 ? f0 - 8 * FS : f0;
          const unsigned* f2 = rb >= 2 ? f0 - 16 * FS : f0;
          unsigned v0, v1, v2;
          do { v0 = ld_relaxed(f0); v1 = ld_relaxed(f1); v2 = ld_relaxed(f2); }
          while (((int)(v0 - ep1) < 0 || (int)(v1 - ep1) < 0 || (int)(v2 - ep1) < 0) && clk32() - t0 < TIMEOUT);
        }
        TR(11);
        mbar_wait(bars + 8 * BAR_GIN, 0, t0);
        fence_async_global();
        mbar_expect_tx(bars + 8 * BAR_KVFULL, kvbytes);
        bulk_load(kvdst, kvsrc, kvbytes, bars + 8 * BAR_KVFULL);
        mbar_wait(bars + 8 * BAR_KVOK, 0, t0);
        mbar_expect_tx(bars + 8 * (BAR_KVFULL + 1), kvbytes);
        bulk_load(kvdst + KVBUF, kvsrc + (size_t)SEQ * 64, kvbytes, bars + 8 * (BAR_KVFULL + 1));
        for (int hh = 0; hh < 4; hh++) {
          for (int aw = 0; aw < 2; aw++) {
            mbar_wait(bars + 8 * (BAR_OST + aw), hh & 1, t0);
            tma_store_2d(&P.tmOs, DFF + hh * 128 + j * 16, rb * 128 + aw * 64, sbase + OFF_A + aw * 8192 + hh * 2048);
          }
          bulk_commit();
          if (hh < 2) {
            mbar_wait(bars + 8 * (BAR_KVEMPTY + hh), 0, t0);
            mbar_expect_tx(bars + 8 * (BAR_KVFULL + hh), kvbytes);
            bulk_load(kvdst + hh * KVBUF, kvsrc + (size_t)(hh + 2) * SEQ * 64, kvbytes, bars + 8 * (BAR_KVFULL + hh));
          }
          bulk_wait_all();
          flag_add(&g_flag_o[(rb * 8 + hh * 2 + (j >> 2)) * FS]);
          TR(12 + hh);
        }
      }
    }
  }
}

typedef CUresult (*EncodeFn)(CUtensorMap*, CUtensorMapDataType, cuuint32_t, void*, const cuuint64_t*, const cuuint64_t*, const cuuint32_t*,
                             const cuuint32_t*, CUtensorMapInterleave, CUtensorMapSwizzle, CUtensorMapL2promotion, CUtensorMapFloatOOBfill);

void make_map(EncodeFn enc, CUtensorMap* m, const void* ptr, int rank, const cuuint64_t* dims, const cuuint64_t* strides, const cuuint32_t* box,
              CUtensorMapSwizzle sw = CU_TENSOR_MAP_SWIZZLE_128B) {
  cuuint32_t es[4] = {1, 1, 1, 1};
  enc(m, CU_TENSOR_MAP_DATA_TYPE_BFLOAT16, rank, const_cast<void*>(ptr), dims, strides, box, es, CU_TENSOR_MAP_INTERLEAVE_NONE, sw,
      CU_TENSOR_MAP_L2_PROMOTION_L2_256B, CU_TENSOR_MAP_FLOAT_OOB_FILL_NONE);
}

}

extern "C" void kernel_launch(void* const* d_in, const int* in_sizes, int n_in, void* d_out, int out_size) {
  (void)in_sizes; (void)n_in; (void)out_size;
  static EncodeFn enc = nullptr;
  static void* ho_ptr = nullptr;
  if (!enc) {
    void* fn = nullptr; cudaDriverEntryPointQueryResult st;
    cudaGetDriverEntryPoint("cuTensorMapEncodeTiled", &fn, cudaEnableDefault, &st);
    enc = (EncodeFn)fn;
    cudaGetSymbolAddress(&ho_ptr, g_ho);
    cudaFuncSetAttribute(fused_kernel, cudaFuncAttributeMaxDynamicSharedMemorySize, SMEM_BYTES);
  }
  const __nv_bfloat16* x = (const __nv_bfloat16*)d_in[0];
  const __nv_bfloat16* wqkv = (const __nv_bfloat16*)d_in[1];
  const __nv_bfloat16* wo = (const __nv_bfloat16*)d_in[2];
  const __nv_bfloat16* w1 = (const __nv_bfloat16*)d_in[4];
  const __nv_bfloat16* w2 = (const __nv_bfloat16*)d_in[5];
  const __nv_bfloat16* gate_w = (const __nv_bfloat16*)d_in[6];
  Params P;
  { cuuint64_t d[2] = {DM, SEQ}, s[1] = {DM * 2}; cuuint32_t b[2] = {64, 128}; make_map(enc, &P.tmX, x, 2, d, s, b); }
  { cuuint64_t d[3] = {512, 512, 3}, s[2] = {1536 * 2, 512 * 2}; cuuint32_t b[3] = {64, 16, 3}; make_map(enc, &P.tmWqkv, wqkv, 3, d, s, b); }
  { cuuint64_t d[3] = {64, 512, 28}, s[2] = {DFF * 2, 128}; cuuint32_t b[3] = {64, 16, 1}; make_map(enc, &P.tmW1a, w1, 3, d, s, b);
    b[2] = 3; make_map(enc, &P.tmW1b, w1, 3, d, s, b); }
  { cuuint64_t d[3] = {64, DFF, 8}, s[2] = {DM * 2, 128}; cuuint32_t b[3] = {64, 32, 2}; make_map(enc, &P.tmW2, w2, 3, d, s, b); }
  { cuuint64_t d[4] = {DM, 16, 4, 8}, s[3] = {DM * 2, 16 * DM * 2, 64 * DM * 2}; cuuint32_t b[4] = {64, 16, 1, 4}; make_map(enc, &P.tmWo, wo, 4, d, s, b); }
  { cuuint64_t d[2] = {KHO, SEQ}, s[1] = {KHO * 2}; cuuint32_t b[2] = {64, 128}; make_map(enc, &P.tmHO, ho_ptr, 2, d, s, b);
    b[1] = 64; make_map(enc, &P.tmHOs, ho_ptr, 2, d, s, b);
    b[0] = 16; make_map(enc, &P.tmOs, ho_ptr, 2, d, s, b, CU_TENSOR_MAP_SWIZZLE_NONE); }
  { cuuint64_t d[2] = {DM, SEQ}, s[1] = {DM * 2}; cuuint32_t b[2] = {64, 16}; make_map(enc, &P.tmOut, d_out, 2, d, s, b); }
  P.x = x; P.gate_w = gate_w; P.w1 = w1; P.w2 = w2; P.wo = wo; P.out = (__nv_bfloat16*)d_out;
  fused_kernel<<<128, 640, SMEM_BYTES>>>(P);
}
```

```cpp
#include <cuda_runtime.h>
#include <cuda_bf16.h>
#include <cuda.h>
#include <stdint.h>

#define DEVI __device__ __forceinline__

namespace {

constexpr int SEQ = 2048, DM = 512, DFF = 1792, KHO = 2304;
constexpr int NA = 5, NB = 6, SLOT = 16384, KVBUF = 24576;
constexpr int NA2 = 8;
constexpr int OFF_B = 0, OFF_A = NB * SLOT, OFF_KV = OFF_A + NA * SLOT, OFF_BAR = OFF_KV + 2 * KVBUF;
constexpr int OFF_GST = OFF_BAR + 512;
constexpr int OFF_GIN = OFF_BAR + 1024;
constexpr int SMEM_BYTES = OFF_BAR + 1536 + 1024;
constexpr uint32_t TIMEOUT = 1u << 28;
#define WAIT_HINT_NS 20000u
#define PFAT 8
#define SH false
#define SHW 1
#define SHG 1
constexpr int FS = 8;

constexpr int BAR_FULLA = 0, BAR_EMPTYA = BAR_FULLA + NA2, BAR_FULLB = BAR_EMPTYA + NA2, BAR_EMPTYB = BAR_FULLB + NB,
              BAR_KVFULL = BAR_EMPTYB + NB, BAR_KVEMPTY = BAR_KVFULL + 2, BAR_STG = BAR_KVEMPTY + 2, BAR_PIN = BAR_STG + 2, BAR_GATE = BAR_PIN + 1, BAR_STE = BAR_GATE + 2, BAR_ATTDONE = BAR_STE + 2, BAR_GIN = BAR_ATTDONE + 1, BAR_OST = BAR_GIN + 1, BAR_QRDY = BAR_OST + 2, BAR_KVOK = BAR_QRDY + 2;

__device__ __align__(1024) uint8_t g_kv[32 * SEQ * 64];
__device__ __align__(1024) __nv_bfloat16 g_ho[SEQ * KHO];
__device__ __align__(1024) uint8_t g_part[128 * 16384];
__device__ __align__(128) float g_gate[SEQ];
__device__ unsigned g_flag_kv[128 * FS], g_flag_h[128 * FS], g_flag_o[128 * FS], g_flag_g[16 * FS], g_flag_p[128 * FS], g_flag_e[128 * FS];
__device__ unsigned g_epoch, g_done;
#define TR(i) do {} while (0)

struct Params {
  CUtensorMap tmX, tmWqkv, tmW1a, tmW1b, tmW2, tmWo, tmHO, tmHOs, tmOs, tmOut;
  const __nv_bfloat16* x;
  const __nv_bfloat16* gate_w;
  const __nv_bfloat16* w1;
  const __nv_bfloat16* w2;
  const __nv_bfloat16* wo;
  __nv_bfloat16* out;
};

DEVI uint32_t smem_u32(const void* p) { return (uint32_t)__cvta_generic_to_shared(p); }
DEVI uint32_t clk32() { uint32_t c; asm volatile("mov.u32 %0, %%clock;" : "=r"(c)); return c; }
DEVI void mbar_init(uint32_t bar, uint32_t cnt) { asm volatile("mbarrier.init.shared::cta.b64 [%0], %1;" ::"r"(bar), "r"(cnt)); }
DEVI void mbar_expect_tx(uint32_t bar, uint32_t bytes) { asm volatile("mbarrier.arrive.expect_tx.shared::cta.b64 _, [%0], %1;" ::"r"(bar), "r"(bytes) : "memory"); }
DEVI void mbar_arrive(uint32_t bar) { asm volatile("mbarrier.arrive.shared::cta.b64 _, [%0];" ::"r"(bar) : "memory"); }
DEVI void mbar_arrive_cluster(uint32_t bar, uint32_t cta) {
  asm volatile("{ .reg .b32 ra; mapa.shared::cluster.u32 ra, %0, %1; mbarrier.arrive.shared::cluster.b64 _, [ra]; }" ::"r"(bar), "r"(cta) : "memory");
}
DEVI void mbar_wait(uint32_t bar, uint32_t parity, uint32_t t0) {
  asm volatile("{ .reg .pred p; .reg .u32 c;\n"
               "mbarrier.try_wait.parity.shared::cta.b64 p, [%0], %1;\n"
               "@p bra DONE_%=;\n"
               "WAIT_%=:\n"
               "mbarrier.try_wait.parity.shared::cta.b64 p, [%0], %1, %4;\n"
               "@p bra DONE_%=;\n"
               "mov.u32 c, %%clock; sub.u32 c, c, %2; setp.lt.u32 p, c, %3;\n"
               "@p bra WAIT_%=;\n"
               "DONE_%=: }" ::"r"(bar), "r"(parity), "r"(t0), "n"(TIMEOUT), "r"(WAIT_HINT_NS) : "memory");
}
DEVI unsigned ld_relaxed(const unsigned* p) { unsigned v; asm volatile("ld.relaxed.gpu.global.u32 %0, [%1];" : "=r"(v) : "l"(p) : "memory"); return v; }
DEVI void flag_wait(const unsigned* p, unsigned target, uint32_t t0) {
  while ((int)(ld_relaxed(p) - target) < 0) { if (clk32() - t0 > TIMEOUT) break; }
}
DEVI void flag_add(unsigned* p) { asm volatile("red.relaxed.gpu.global.add.u32 [%0], 1;" ::"l"(p) : "memory"); }
DEVI void fence_async_smem() { asm volatile("fence.proxy.async.shared::cta;" ::: "memory"); }
DEVI void fence_async_global() { asm volatile("fence.proxy.async.global;" ::: "memory"); }
DEVI void tma_load_2d(uint32_t dst, const CUtensorMap* m, int c0, int c1, uint32_t bar) {
  asm volatile("cp.async.bulk.tensor.2d.shared::cluster.global.mbarrier::complete_tx::bytes [%0], [%1, {%3, %4}], [%2];" ::"r"(dst), "l"(m), "r"(bar), "r"(c0), "r"(c1) : "memory");
}
DEVI void tma_load_3d(uint32_t dst, const CUtensorMap* m, int c0, int c1, int c2, uint32_t bar) {
  asm volatile("cp.async.bulk.tensor.3d.shared::cluster.global.mbarrier::complete_tx::bytes [%0], [%1, {%3, %4, %5}], [%2];"
               ::"r"(dst), "l"(m), "r"(bar), "r"(c0), "r"(c1), "r"(c2) : "memory");
}
DEVI void tma_load_3d_mc(uint32_t dst, const CUtensorMap* m, int c0, int c1, int c2, uint32_t bar) {
  asm volatile("cp.async.bulk.tensor.3d.shared::cluster.global.mbarrier::complete_tx::bytes.multicast::cluster [%0], [%1, {%3, %4, %5}], [%2], %6;"
               ::"r"(dst), "l"(m), "r"(bar), "r"(c0), "r"(c1), "r"(c2), "h"((uint16_t)3) : "memory");
}
DEVI void tma_load_4d_mc(uint32_t dst, const CUtensorMap* m, int c0, int c1, int c2, int c3, uint32_t bar) {
  asm volatile("cp.async.bulk.tensor.4d.shared::cluster.global.mbarrier::complete_tx::bytes.multicast::cluster [%0], [%1, {%3, %4, %5, %6}], [%2], %7;"
               ::"r"(dst), "l"(m), "r"(bar), "r"(c0), "r"(c1), "r"(c2), "r"(c3), "h"((uint16_t)3) : "memory");
}
DEVI void tma_store_2d(const CUtensorMap* m, int c0, int c1, uint32_t src) {
  asm volatile("cp.async.bulk.tensor.2d.global.shared::cta.bulk_group [%0, {%1, %2}], [%3];" ::"l"(m), "r"(c0), "r"(c1), "r"(src) : "memory");
}
DEVI void bulk_store(void* dst, uint32_t src, uint32_t bytes) {
  asm volatile("cp.async.bulk.global.shared::cta.bulk_group [%0], [%1], %2;" ::"l"(dst), "r"(src), "r"(bytes) : "memory");
}
DEVI void bulk_load(uint32_t dst, const void* src, uint32_t bytes, uint32_t bar) {
  asm volatile("cp.async.bulk.shared::cluster.global.mbarrier::complete_tx::bytes [%0], [%1], %2, [%3];" ::"r"(dst), "l"(src), "r"(bytes), "r"(bar) : "memory");
}
DEVI void bulk_commit() { asm volatile("cp.async.bulk.commit_group;" ::: "memory"); }
DEVI void bulk_wait_all() { asm volatile("cp.async.bulk.wait_group 0;" ::: "memory"); }
DEVI void l2_prefetch(const void* p, uint32_t bytes) { asm volatile("cp.async.bulk.prefetch.L2.global [%0], %1;" ::"l"(p), "r"(bytes) : "memory"); }
DEVI void cluster_arrive() { asm volatile("barrier.cluster.arrive.relaxed.aligned;" ::: "memory"); }
DEVI void cluster_wait() { asm volatile("barrier.cluster.wait.aligned;" ::: "memory"); }
template <int ID> DEVI void named_bar(int n) { asm volatile("bar.sync %0, %1;" ::"n"(ID), "r"(n) : "memory"); }
DEVI void wg_bar(int wg) { if (wg == 0) named_bar<1>(128); else named_bar<2>(128); }
DEVI void wgmma_fence() { asm volatile("wgmma.fence.sync.aligned;" ::: "memory"); }
DEVI void wgmma_commit() { asm volatile("wgmma.commit_group.sync.aligned;" ::: "memory"); }
template <int N> DEVI void wgmma_wait() { asm volatile("wgmma.wait_group.sync.aligned %0;" ::"n"(N) : "memory"); }
template <uint32_t LBO> DEVI uint64_t desc_sw128(uint32_t a16) {
  return ((uint64_t)(0x40000000u | (1024 >> 4)) << 32) | (a16 + ((LBO >> 4) << 16));
}
DEVI uint64_t desc_sw64(uint32_t a16) {
  return ((uint64_t)(0x80000000u | (512 >> 4)) << 32) | (a16 + ((512 >> 4) << 16));
}
DEVI uint32_t pack_bf16(float lo, float hi) { uint32_t r; asm("cvt.rn.bf16x2.f32 %0, %1, %2;" : "=r"(r) : "f"(hi), "f"(lo)); return r; }
DEVI void stsm_x4(uint32_t addr, uint32_t r0, uint32_t r1, uint32_t r2, uint32_t r3) {
  asm volatile("stmatrix.sync.aligned.m8n8.x4.shared.b16 [%0], {%1, %2, %3, %4};" ::"r"(addr), "r"(r0), "r"(r1), "r"(r2), "r"(r3) : "memory");
}
DEVI void sts128(uint32_t addr, uint32_t r0, uint32_t r1, uint32_t r2, uint32_t r3) {
  asm volatile("st.shared.v4.b32 [%0], {%1, %2, %3, %4};" ::"r"(addr), "r"(r0), "r"(r1), "r"(r2), "r"(r3) : "memory");
}
DEVI uint4 lds128(uint32_t addr) {
  uint4 v; asm volatile("ld.shared.v4.b32 {%0, %1, %2, %3}, [%4];" : "=r"(v.x), "=r"(v.y), "=r"(v.z), "=r"(v.w) : "r"(addr) : "memory"); return v;
}
DEVI float ex2(float x) { float y; asm("ex2.approx.ftz.f32 %0, %1;" : "=f"(y) : "f"(x)); return y; }

DEVI void wgmma_ss_n64(float (&d)[32], uint64_t da, uint64_t db) {
  asm volatile("wgmma.mma_async.sync.aligned.m64n64k16.f32.bf16.bf16 {%0, %1, %2, %3, %4, %5, %6, %7, %8, %9, %10, %11, %12, %13, %14, %15, %16, %17, %18, %19, %20, %21, %22, %23, %24, %25, %26, %27, %28, %29, %30, %31}, %32, %33, 1, 1, 1, 0, 1;"
    : "+f"(d[0]), "+f"(d[1]), "+f"(d[2]), "+f"(d[3]), "+f"(d[4]), "+f"(d[5]), "+f"(d[6]), "+f"(d[7]), "+f"(d[8]), "+f"(d[9]), "+f"(d[10]), "+f"(d[11]), "+f"(d[12]), "+f"(d[13]), "+f"(d[14]), "+f"(d[15]), "+f"(d[16]), "+f"(d[17]), "+f"(d[18]), "+f"(d[19]), "+f"(d[20]), "+f"(d[21]), "+f"(d[22]), "+f"(d[23]), "+f"(d[24]), "+f"(d[25]), "+f"(d[26]), "+f"(d[27]), "+f"(d[28]), "+f"(d[29]), "+f"(d[30]), "+f"(d[31])
    : "l"(da), "l"(db));
}
DEVI void wgmma_ss_n128(float (&d)[64], uint64_t da, uint64_t db) {
  asm volatile("wgmma.mma_async.sync.aligned.m64n128k16.f32.bf16.bf16 {%0, %1, %2, %3, %4, %5, %6, %7, %8, %9, %10, %11, %12, %13, %14, %15, %16, %17, %18, %19, %20, %21, %22, %23, %24, %25, %26, %27, %28, %29, %30, %31, %32, %33, %34, %35, %36, %37, %38, %39, %40, %41, %42, %43, %44, %45, %46, %47, %48, %49, %50, %51, %52, %53, %54, %55, %56, %57, %58, %59, %60, %61, %62, %63}, %64, %65, 1, 1, 1, 0, 1;"
    : "+f"(d[0]), "+f"(d[1]), "+f"(d[2]), "+f"(d[3]), "+f"(d[4]), "+f"(d[5]), "+f"(d[6]), "+f"(d[7]), "+f"(d[8]), "+f"(d[9]), "+f"(d[10]), "+f"(d[11]), "+f"(d[12]), "+f"(d[13]), "+f"(d[14]), "+f"(d[15]), "+f"(d[16]), "+f"(d[17]), "+f"(d[18]), "+f"(d[19]), "+f"(d[20]), "+f"(d[21]), "+f"(d[22]), "+f"(d[23]), "+f"(d[24]), "+f"(d[25]), "+f"(d[26]), "+f"(d[27]), "+f"(d[28]), "+f"(d[29]), "+f"(d[30]), "+f"(d[31]), "+f"(d[32]), "+f"(d[33]), "+f"(d[34]), "+f"(d[35]), "+f"(d[36]), "+f"(d[37]), "+f"(d[38]), "+f"(d[39]), "+f"(d[40]), "+f"(d[41]), "+f"(d[42]), "+f"(d[43]), "+f"(d[44]), "+f"(d[45]), "+f"(d[46]), "+f"(d[47]), "+f"(d[48]), "+f"(d[49]), "+f"(d[50]), "+f"(d[51]), "+f"(d[52]), "+f"(d[53]), "+f"(d[54]), "+f"(d[55]), "+f"(d[56]), "+f"(d[57]), "+f"(d[58]), "+f"(d[59]), "+f"(d[60]), "+f"(d[61]), "+f"(d[62]), "+f"(d[63])
    : "l"(da), "l"(db));
}
DEVI void wgmma_qk64(float (&d)[32], uint32_t a0, uint32_t a1, uint32_t a2, uint32_t a3, uint64_t db) {
  asm volatile("wgmma.mma_async.sync.aligned.m64n64k16.f32.bf16.bf16 {%0, %1, %2, %3, %4, %5, %6, %7, %8, %9, %10, %11, %12, %13, %14, %15, %16, %17, %18, %19, %20, %21, %22, %23, %24, %25, %26, %27, %28, %29, %30, %31}, {%32, %33, %34, %35}, %36, 0, 1, 1, 0;"
    : "=f"(d[0]), "=f"(d[1]), "=f"(d[2]), "=f"(d[3]), "=f"(d[4]), "=f"(d[5]), "=f"(d[6]), "=f"(d[7]), "=f"(d[8]), "=f"(d[9]), "=f"(d[10]), "=f"(d[11]), "=f"(d[12]), "=f"(d[13]), "=f"(d[14]), "=f"(d[15]), "=f"(d[16]), "=f"(d[17]), "=f"(d[18]), "=f"(d[19]), "=f"(d[20]), "=f"(d[21]), "=f"(d[22]), "=f"(d[23]), "=f"(d[24]), "=f"(d[25]), "=f"(d[26]), "=f"(d[27]), "=f"(d[28]), "=f"(d[29]), "=f"(d[30]), "=f"(d[31])
    : "r"(a0), "r"(a1), "r"(a2), "r"(a3), "l"(db));
}
DEVI void wgmma_pv(float (&d)[8], uint32_t a0, uint32_t a1, uint32_t a2, uint32_t a3, uint64_t db) {
  asm volatile("wgmma.mma_async.sync.aligned.m64n16k16.f32.bf16.bf16 {%0, %1, %2, %3, %4, %5, %6, %7}, {%8, %9, %10, %11}, %12, 1, 1, 1, 1;"
    : "+f"(d[0]), "+f"(d[1]), "+f"(d[2]), "+f"(d[3]), "+f"(d[4]), "+f"(d[5]), "+f"(d[6]), "+f"(d[7])
    : "r"(a0), "r"(a1), "r"(a2), "r"(a3), "l"(db));
}
DEVI void wgmma_pv0(float (&d)[8], uint32_t a0, uint32_t a1, uint32_t a2, uint32_t a3, uint64_t db) {
  asm volatile("wgmma.mma_async.sync.aligned.m64n16k16.f32.bf16.bf16 {%0, %1, %2, %3, %4, %5, %6, %7}, {%8, %9, %10, %11}, %12, 0, 1, 1, 1;"
    : "=f"(d[0]), "=f"(d[1]), "=f"(d[2]), "=f"(d[3]), "=f"(d[4]), "=f"(d[5]), "=f"(d[6]), "=f"(d[7])
    : "r"(a0), "r"(a1), "r"(a2), "r"(a3), "l"(db));
}

template <int N> struct Acc { float a[64]; float b[(N - 128) / 2]; DEVI float& operator[](int i) { return i < 64 ? a[i] : b[i - 64]; } };
template <> struct Acc<128> { float a[64]; DEVI float& operator[](int i) { return a[i]; } };
template <int N> DEVI void wgmma_ss(Acc<N>& d, uint64_t da, uint64_t db) {
  wgmma_ss_n128(d.a, da, db);
  if constexpr (N == 192) wgmma_ss_n64(d.b, da, db + 256);
  if constexpr (N == 256) wgmma_ss_n128(d.b, da, db + 256);
}

DEVI int oh_chunk(int j, int i, int& need) {
  if (i >= 3 && i < 5) { const int e = (j & 1) * 2 + i - 3; need = 16 + 2 * e; return 24 + e; }
  if (i >= 5) i -= 2;
  int o, r;
  if (i >= 12) { o = (j + 5) & 7; r = i - 11; }
  else { const int g = i / 3; o = (j + 2 * g) & 7; r = i - 3 * g; }
  need = o;
  return 3 * o + r;
}

DEVI int a_slot(int e, int) { return 1 + (e & 3); }

struct Ctx {
  uint32_t sbase, bars, peer, t0, a16, b16;
  int wg, lane;
  int ai, bi; uint32_t aph, bph;
  int brem, ae;
  int pa, pb;
};

DEVI void release_prev(Ctx& c) {
  if (c.pb >= 0) {
    if (c.lane == 0) mbar_arrive(c.bars + 8 * (BAR_EMPTYB + c.pb));
    if (c.lane == 1) mbar_arrive_cluster(c.bars + 8 * (BAR_EMPTYB + c.pb), c.peer);
  }
  if (c.pa >= 0 && c.lane == 2) mbar_arrive(c.bars + 8 * (BAR_EMPTYA + c.pa));
}

DEVI void gemm_wait(Ctx& c) {
  asm volatile("{ .reg .pred p, q; .reg .u32 c;\n"
               "mbarrier.try_wait.parity.shared::cta.b64 p, [%0], %1;\n"
               "mbarrier.try_wait.parity.shared::cta.b64 q, [%2], %3;\n"
               "and.pred p, p, q;\n"
               "@p bra DONE_%=;\n"
               "WAIT_%=:\n"
               "mbarrier.try_wait.parity.shared::cta.b64 p, [%0], %1, %6;\n"
               "mbarrier.try_wait.parity.shared::cta.b64 q, [%2], %3, %6;\n"
               "and.pred p, p, q;\n"
               "@p bra DONE_%=;\n"
               "mov.u32 c, %%clock; sub.u32 c, c, %4; setp.lt.u32 p, c, %5;\n"
               "@p bra WAIT_%=;\n"
               "DONE_%=: }" ::"r"(c.bars + 8 * (BAR_FULLA + c.ai)), "r"((c.aph >> c.ai) & 1), "r"(c.bars + 8 * (BAR_FULLB + c.bi)), "r"(c.bph), "r"(c.t0),
               "n"(TIMEOUT), "r"(WAIT_HINT_NS) : "memory");
}
template <int N, bool SHALLOW>
DEVI void gemm_group(Acc<N>& acc, Ctx& c, int g, int& npa, int& npb) {
  const uint32_t a16 = c.a16 + c.ai * (SLOT >> 4);
  const uint32_t b16 = c.b16 + c.bi * (SLOT >> 4);
  bool adv;
  if constexpr (N >= 192) {
    const uint32_t a2 = a16 + (g & 1) * 4;
    wgmma_ss<N>(acc, desc_sw128<16>(a2), desc_sw128<2048>(b16));
    if (SHALLOW) { wgmma_commit(); wgmma_wait<SHW>(); }
    wgmma_ss<N>(acc, desc_sw128<16>(a2 + 2), desc_sw128<2048>(b16 + 512));
    adv = g & 1;
  } else {
#pragma unroll
    for (int s = 0; s < 4; s++) {
      wgmma_ss<N>(acc, desc_sw128<16>(a16 + s * 2), desc_sw128<4096>(b16 + (s >> 1) * 512 + (s & 1) * 128));
      if (SHALLOW && s < 3 && (SHG == 1 || s == 1)) { wgmma_commit(); wgmma_wait<SHW>(); }
    }
    adv = true;
  }
  wgmma_commit();
  npb = c.brem > 0 ? c.bi : -1;
  c.brem--;
  if (++c.bi == NB) { c.bi = 0; c.bph ^= 1; }
  npa = -1;
  if (adv) { npa = c.ai; c.aph ^= 1u << c.ai; c.ae++; c.ai = 1 + (c.ae & 3); }
}

template <int N, bool SHALLOW = false>
DEVI void bare_groups(Acc<N>& acc, Ctx& c, int g0, int g1) {
  for (int g = g0; g < g1; g++) {
    int npa, npb;
    gemm_wait(c);
    wgmma_fence();
    gemm_group<N, SHALLOW>(acc, c, g, npa, npb);
    wgmma_wait<SHALLOW ? SHW : 1>();
    release_prev(c);
    c.pa = npa; c.pb = npb;
  }
}
DEVI void drain(Ctx& c) {
  wgmma_wait<0>();
  release_prev(c);
  c.pa = c.pb = -1;
}

constexpr float SC = 0.25f * 1.4426950408889634f;

#define ONCE _Pragma("unroll 1") for (unsigned once_ = 0; once_ < gridDim.y; once_++)

struct Gate { float g0, g1; };

DEVI void kill32(float (&S)[32]) {
#pragma unroll
  for (int i = 0; i < 32; i++) S[i] = __int_as_float(0xff800000);
}
DEVI void row_max(const float (&S)[32], float& x0, float& x1) {
  float y0 = S[1], y1 = S[3];
  x0 = fmaxf(x0, S[0]); x1 = fmaxf(x1, S[2]);
#pragma unroll
  for (int n = 1; n < 8; n++) {
    x0 = fmaxf(x0, S[4 * n]); y0 = fmaxf(y0, S[4 * n + 1]); x1 = fmaxf(x1, S[4 * n + 2]); y1 = fmaxf(y1, S[4 * n + 3]);
  }
  x0 = fmaxf(x0, y0); x1 = fmaxf(x1, y1);
}
DEVI void quad_max(float& x0, float& x1) {
  x0 = fmaxf(x0, __shfl_xor_sync(0xffffffffu, x0, 1)); x1 = fmaxf(x1, __shfl_xor_sync(0xffffffffu, x1, 1));
  x0 = fmaxf(x0, __shfl_xor_sync(0xffffffffu, x0, 2)); x1 = fmaxf(x1, __shfl_xor_sync(0xffffffffu, x1, 2));
}
DEVI void exp32(const float (&S)[32], float (&E)[32], float n0, float n1, float (&l)[4]) {
#pragma unroll
  for (int i = 0; i < 32; i++) { E[i] = ex2(fmaf(S[i], SC, (i & 2) ? n1 : n0)); l[i & 3] += E[i]; }
}
DEVI void pack32(const float (&E)[32], uint32_t (&P)[16]) {
#pragma unroll
  for (int i = 0; i < 16; i++) P[i] = pack_bf16(E[2 * i], E[2 * i + 1]);
}
template <bool FIRST> DEVI void pv4(float (&O)[8], const uint32_t (&P)[16], uint32_t v16) {
  if (FIRST) wgmma_pv0(O, P[0], P[1], P[2], P[3], desc_sw64(v16)); else wgmma_pv(O, P[0], P[1], P[2], P[3], desc_sw64(v16));
#pragma unroll
  for (int k = 1; k < 4; k++) wgmma_pv(O, P[4 * k], P[4 * k + 1], P[4 * k + 2], P[4 * k + 3], desc_sw64(v16 + k * 64));
}
DEVI bool wg_any(int wg, bool v) {
  uint32_t r;
  if (wg == 0) asm volatile("{ .reg .pred p, q; setp.ne.u32 p, %1, 0; bar.red.or.pred q, 4, 128, p; selp.u32 %0, 1, 0, q; }" : "=r"(r) : "r"((uint32_t)v) : "memory");
  else asm volatile("{ .reg .pred p, q; setp.ne.u32 p, %1, 0; bar.red.or.pred q, 5, 128, p; selp.u32 %0, 1, 0, q; }" : "=r"(r) : "r"((uint32_t)v) : "memory");
  return r != 0;
}
DEVI void get_gate(Gate& g, uint32_t sbase, int row16, int lane, uint32_t t0) {
  mbar_wait(sbase + OFF_BAR + 8 * BAR_GIN, 0, t0);
  const uint32_t a = sbase + OFF_GIN + (row16 * 16 + (lane >> 2)) * 4;
  asm volatile("ld.shared.f32 %0, [%1];" : "=f"(g.g0) : "r"(a) : "memory");
  asm volatile("ld.shared.f32 %0, [%1];" : "=f"(g.g1) : "r"(a + 32) : "memory");
}

DEVI void attention(uint32_t sbase, int aw, int wi, int lane, int rb, uint32_t t0) {
  const uint32_t bars = sbase + OFF_BAR;
  const uint32_t kvb = ((sbase & 0x3FFFF) + OFF_KV + aw * 4096) >> 4;
  const int cmin = 4 - 2 * rb - aw;
  const int rowc = wi * 16 + (lane >> 2) - (lane & 3) * 2;
  const uint32_t qst = sbase + OFF_A + aw * 8192;
  const float NINF = __int_as_float(0xff800000);
  const int tlo = max(cmin, 1);
#pragma unroll 1
  for (int h = 0; h < 4; h++) {
    const uint32_t kb = kvb + (h & 1) * (KVBUF >> 4);
    const uint4 q = lds128(qst + h * 2048 + (wi * 32 + lane) * 16);
    float O[8], l0, l1;
    float xt0 = NINF, xt1 = NINF;
    mbar_wait(bars + 8 * (BAR_KVFULL + (h & 1)), h >> 1, t0);
#pragma unroll 1
    for (int attempt = 0; attempt < 2; attempt++) {
      float l[4] = {0.f, 0.f, 0.f, 0.f}, n0, n1;
      uint32_t P[16];
      {
        float S[32], F[32];
        wgmma_fence();
        wgmma_qk64(S, q.x, q.y, q.z, q.w, desc_sw64(kb + 4 * 256));
        wgmma_qk64(F, q.x, q.y, q.z, q.w, desc_sw64(kb));
        wgmma_commit();
        wgmma_wait<0>();
        for (int r = 0; r < (cmin > 0 ? 1 : 0); r++) kill32(F);
        float M[32];
#pragma unroll
        for (int i = 0; i < 32; i++) M[i] = ((i >> 2) * 8 + (i & 1) > rowc + (i & 2) * 4) ? F[i] : S[i];
        float x0 = xt0, x1 = xt1;
        row_max(M, x0, x1);
        quad_max(x0, x1);
        n0 = -x0 * SC; n1 = -x1 * SC;
        exp32(M, M, n0, n1, l);
        pack32(M, P);
        uint32_t PF[16];
#pragma unroll
        for (int i = 0; i < 16; i++) {
          const int col = (i >> 1) * 8, r = rowc + (i & 1) * 8;
          const uint32_t m = (col > r ? 0xFFFFu : 0u) | (col + 1 > r ? 0xFFFF0000u : 0u);
          PF[i] = P[i] & m; P[i] &= ~m;
        }
        wgmma_fence();
        pv4<true>(O, PF, kb + 2);
        wgmma_commit();
        wgmma_wait<0>();
      }
      int t = 3;
#pragma unroll 1
      for (; t >= tlo; t--) {
        float S[32];
        wgmma_fence();
        wgmma_qk64(S, q.x, q.y, q.z, q.w, desc_sw64(kb + t * 256));
        wgmma_commit();
        pv4<false>(O, P, kb + (t + 1) * 256 + 2);
        wgmma_commit();
        wgmma_wait<1>();
        ONCE { exp32(S, S, n0, n1, l); }
        wgmma_wait<0>();
        pack32(S, P);
      }
      wgmma_fence();
      pv4<false>(O, P, kb + (t + 1) * 256 + 2);
      wgmma_commit();
      l0 = l[0] + l[1]; l1 = l[2] + l[3];
      l0 += __shfl_xor_sync(0xffffffffu, l0, 1); l1 += __shfl_xor_sync(0xffffffffu, l1, 1);
      l0 += __shfl_xor_sync(0xffffffffu, l0, 2); l1 += __shfl_xor_sync(0xffffffffu, l1, 2);
      const bool redo = wg_any(aw, attempt == 0 && !(l0 < 1e18f && l1 < 1e18f));
      wgmma_wait<0>();
      if (!redo) break;
#pragma unroll 1
      for (int u = 3; u >= tlo; u--) {
        float S[32];
        wgmma_fence();
        wgmma_qk64(S, q.x, q.y, q.z, q.w, desc_sw64(kb + u * 256));
        wgmma_commit();
        wgmma_wait<0>();
        row_max(S, xt0, xt1);
      }
    }
    if (lane == 0) mbar_arrive(bars + 8 * (BAR_KVEMPTY + (h & 1)));
    Gate g;
    get_gate(g, sbase, aw * 4 + wi, lane, t0);
    const float c0 = __fdividef(g.g0, l0), c1 = __fdividef(g.g1, l1);
    const int mi = lane >> 3;
    const int srow = wi * 16 + (lane & 7) + 8 * (mi & 1);
    stsm_x4(qst + h * 2048 + srow * 32 + (mi >> 1) * 16, pack_bf16(O[0] * c0, O[1] * c0), pack_bf16(O[2] * c1, O[3] * c1),
            pack_bf16(O[4] * c0, O[5] * c0), pack_bf16(O[6] * c1, O[7] * c1));
    fence_async_smem();
    __syncwarp();
    if (lane == 0) mbar_arrive(bars + 8 * (BAR_OST + aw));
  }
}

template <int CH, int N>
DEVI void store_h_chunk(Acc<N>& acc, uint32_t base  , int lane, float s0, float s1) {
  const int mi = lane >> 3;
#pragma unroll
  for (int tp = 0; tp < 4; tp++) {
    const int t = CH * 8 + tp * 2;
    const uint32_t r0 = pack_bf16(fmaxf(acc[4 * t + 0], 0.f) * s0, fmaxf(acc[4 * t + 1], 0.f) * s0);
    const uint32_t r1 = pack_bf16(fmaxf(acc[4 * t + 2], 0.f) * s1, fmaxf(acc[4 * t + 3], 0.f) * s1);
    const uint32_t r2 = pack_bf16(fmaxf(acc[4 * t + 4], 0.f) * s0, fmaxf(acc[4 * t + 5], 0.f) * s0);
    const uint32_t r3 = pack_bf16(fmaxf(acc[4 * t + 6], 0.f) * s1, fmaxf(acc[4 * t + 7], 0.f) * s1);
    stsm_x4(base + (((tp * 2 + (mi >> 1)) ^ (lane & 7)) << 4), r0, r1, r2, r3);
  }
}

template <int N>
DEVI void phase_q(Ctx& c, int warp) {
  Acc<N> acc;
#pragma unroll
  for (int i = 0; i < N / 2; i++) acc[i] = 0.f;
  bare_groups<N>(acc, c, 0, 16);
  drain(c);
  const int lane = c.lane, mi = lane >> 3;
  const int row = warp * 16 + (lane & 7) + 8 * (mi & 1);
  const int sw = (row >> 1) & 3;
#pragma unroll
  for (int hh = 0; hh < 4; hh++) {
    const uint32_t base = c.sbase + OFF_KV + hh * 8192 + row * 64;
#pragma unroll
    for (int kv = 0; kv < 2; kv++) {
      const int t = 8 + kv * 8 + 2 * hh;
      stsm_x4(base + (((kv * 2 + (mi >> 1)) ^ sw) << 4),
              pack_bf16(acc[4 * t + 0], acc[4 * t + 1]), pack_bf16(acc[4 * t + 2], acc[4 * t + 3]),
              pack_bf16(acc[4 * t + 4], acc[4 * t + 5]), pack_bf16(acc[4 * t + 6], acc[4 * t + 7]));
    }
  }
  fence_async_smem();
  __syncwarp();
  if (lane == 0) mbar_arrive(c.bars + 8 * BAR_STG);
#pragma unroll
  for (int hh = 0; hh < 4; hh++)
    sts128(c.sbase + OFF_A + c.wg * 8192 + hh * 2048 + ((warp & 3) * 32 + lane) * 16,
           pack_bf16(acc[8 * hh], acc[8 * hh + 1]), pack_bf16(acc[8 * hh + 2], acc[8 * hh + 3]),
           pack_bf16(acc[8 * hh + 4], acc[8 * hh + 5]), pack_bf16(acc[8 * hh + 6], acc[8 * hh + 7]));
  __syncwarp();
  if (lane == 0) mbar_arrive(c.bars + 8 * (BAR_QRDY + c.wg));
  if constexpr (N == 256) {
    Gate g;
    get_gate(g, c.sbase, warp, lane, c.t0);
    store_h_chunk<3>(acc, c.sbase + OFF_KV + 32768 + row * 128, lane, 1.f - g.g0, 1.f - g.g1);
    fence_async_smem();
    __syncwarp();
    if (lane == 0) mbar_arrive(c.bars + 8 * BAR_STE);
  }
}

DEVI void first_loads(const Params& P, uint32_t sbase, int e, int j, int rb) {
  const uint32_t bars = sbase + OFF_BAR, fb = bars + 8 * (BAR_FULLB + e), fa = bars + 8 * (BAR_FULLA + 1 + e);
  mbar_expect_tx(fa, 16384);
  mbar_expect_tx(fb, (j & 1) ? 12288 : 16384);
  if (e == 0) tma_load_2d(sbase + OFF_A + SLOT, &P.tmX, 0, rb * 128, fa);
#pragma unroll
  for (int r = 0; r < 2; r++) {
    tma_load_3d(sbase + OFF_B + e * SLOT + r * 8192, &P.tmWqkv, 64 * j, e * 32 + r * 16, 0, fb);
    if (!(j & 1)) tma_load_3d(sbase + OFF_B + e * SLOT + r * 8192 + 6144, &P.tmW1a, 0, e * 32 + r * 16, 24 + (j >> 1), fb);
  }
  if (e == 1) tma_load_2d(sbase + OFF_A + 2 * SLOT, &P.tmX, 64, rb * 128, fa);
}

__global__ void __cluster_dims__(2, 1, 1) __launch_bounds__(640, 1) fused_kernel(const __grid_constant__ Params P) {
  extern __shared__ uint8_t smem_raw[];
  const uint32_t sbase = (smem_u32(smem_raw) + 1023u) & ~1023u;
  const uint32_t bars = sbase + OFF_BAR;
  const int tid = threadIdx.x, warp = tid >> 5, lane = tid & 31;
  const uint32_t rank = blockIdx.x & 1, peer = rank ^ 1;
  const int j = (blockIdx.x >> 1) & 7, rb = ((blockIdx.x >> 4) << 1) | rank;
  const uint32_t t0 = clk32();

  const int typeB = j & 1;
  if (tid == 544) {
    for (int s = 0; s < NA2; s++) mbar_init(bars + 8 * (BAR_FULLA + s), 1);
    for (int s = 0; s < NB; s++) mbar_init(bars + 8 * (BAR_FULLB + s), 1);
    fence_async_smem();
  } else if (tid < 10) {
    asm volatile("prefetch.tensormap [%0];" ::"l"(&P.tmX + tid) : "memory");
  } else if (tid == 512) {
    for (int s = 0; s < NA2; s++) mbar_init(bars + 8 * (BAR_EMPTYA + s), 9);
    for (int s = 0; s < NB; s++) mbar_init(bars + 8 * (BAR_EMPTYB + s), 16);
  } else if (tid == 576) {
    for (int s = 0; s < 2; s++) { mbar_init(bars + 8 * (BAR_KVFULL + s), 1); mbar_init(bars + 8 * (BAR_KVEMPTY + s), 8); mbar_init(bars + 8 * (BAR_OST + s), 4); mbar_init(bars + 8 * (BAR_QRDY + s), 4); }
    mbar_init(bars + 8 * BAR_STG, 8); mbar_init(bars + 8 * BAR_STE, 8); mbar_init(bars + 8 * BAR_KVOK, 1);
    mbar_init(bars + 8 * BAR_PIN, 1); mbar_init(bars + 8 * BAR_ATTDONE, 8); mbar_init(bars + 8 * BAR_GIN, 1);
  }
  if (tid >= 512 && lane == 0) asm volatile("fence.mbarrier_init.release.cluster;" ::: "memory");
  const unsigned ep1 = ld_relaxed(&g_epoch) + 1;
  __syncwarp();
  cluster_arrive();
  if (tid == 544) { first_loads(P, sbase, 0, j, rb); first_loads(P, sbase, 1, j, rb); }
  __syncwarp();

  const int on = 12 + 4 * typeB;

  if (warp < 8) {
    asm volatile("setmaxnreg.inc.sync.aligned.u32 160;");
    cluster_wait();
    const int wg = __shfl_sync(0xffffffffu, warp >> 2, 0), wi = warp & 3;
    Ctx c{sbase, bars, peer, t0, ((sbase & 0x3FFFF) + OFF_A + wg * 8192) >> 4, ((sbase & 0x3FFFF) + OFF_B) >> 4, wg, lane, 1, 0, 0u, 0u, 32 + on + 4 - NB, 0, -1, -1};
    if (tid == 0) TR(0);
    if (typeB) phase_q<192>(c, warp);
    else phase_q<256>(c, warp);
    asm volatile("setmaxnreg.dec.sync.aligned.u32 128;");
    if (tid == 0) TR(2);
    {
      Acc<192> acc;
#pragma unroll
      for (int i = 0; i < 96; i++) acc[i] = 0.f;
      bare_groups<192, SH>(acc, c, 0, 16);
      Gate at;
      get_gate(at, sbase, warp, lane, t0);
      drain(c);
      if (tid == 0) TR(1);
      const uint32_t rowoff = (warp * 16 + (lane & 7) + 8 * ((lane >> 3) & 1)) * 128;
      const float s0 = 1.f - at.g0, s1 = 1.f - at.g1;
      constexpr int e0 = 1, e1 = 2, e2 = 3;
      mbar_wait(bars + 8 * (BAR_FULLA + e0), 0, t0);
      store_h_chunk<0>(acc, sbase + OFF_A + e0 * SLOT + rowoff, lane, s0, s1);
      mbar_wait(bars + 8 * (BAR_FULLA + e1), 0, t0);
      store_h_chunk<1>(acc, sbase + OFF_A + e1 * SLOT + rowoff, lane, s0, s1);
      mbar_wait(bars + 8 * (BAR_FULLA + e2), 0, t0);
      store_h_chunk<2>(acc, sbase + OFF_A + e2 * SLOT + rowoff, lane, s0, s1);
    }
    fence_async_smem();
    wg_bar(wg);
    if (lane == 0) mbar_arrive(bars + 8 * BAR_STG);
    if (tid == 0) TR(4);
    float own[32];
    {
      Acc<128> acc;
#pragma unroll
      for (int i = 0; i < 64; i++) acc[i] = 0.f;
      bare_groups<128, SH>(acc, c, 0, on);
      drain(c);
      if (tid == 0) TR(5);
      named_bar<3>(256);
      const uint32_t pst = sbase + OFF_B + ((30 + on) % NB) * SLOT + wg * 8192 + (tid & 127) * 16;
#pragma unroll
      for (int i = 0; i < 4; i++) {
        uint32_t r[4];
#pragma unroll
        for (int k = 0; k < 4; k++) {
          const int idx = 8 * i + 2 * k;
          const float lo = typeB ? acc[idx] : acc[32 + idx], hi = typeB ? acc[idx + 1] : acc[32 + idx + 1];
          r[k] = pack_bf16(lo, hi);
        }
        sts128(pst + i * 2048, r[0], r[1], r[2], r[3]);
      }
#pragma unroll
      for (int i = 0; i < 32; i++) own[i] = typeB ? acc[32 + i] : acc[i];
      fence_async_smem();
      __syncwarp();
      if (lane == 0) mbar_arrive(bars + 8 * BAR_STG);
    }
    for (int g = 0; g < 8; g++) {
      const uint32_t a16 = c.a16 + c.ai * (SLOT >> 4);
      const uint32_t b16 = c.b16 + c.bi * (SLOT >> 4) + (g & 1) * 512;
      gemm_wait(c);
      wgmma_fence();
#pragma unroll
      for (int s = 0; s < 4; s++) wgmma_ss_n64(own, desc_sw128<16>(a16 + s * 2), desc_sw128<2048>(b16 + s * 128));
      wgmma_commit();
      wgmma_wait<1>();
      release_prev(c);
      c.pa = c.ai; c.aph ^= 1u << c.ai;
      c.ae++; c.ai = a_slot(c.ae, 0);
      if (g & 1) { if (++c.bi == NB) { c.bi = 0; c.bph ^= 1; } }
    }
    wgmma_wait<0>();
    if (tid == 0) TR(6);
    mbar_wait(bars + 8 * BAR_PIN, 0, t0);
    if (tid == 0) TR(7);
    {
      const uint32_t pin = sbase + OFF_B + ((31 + on) % NB) * SLOT + wg * 8192 + (tid & 127) * 16;
      wg_bar(wg);
      const uint32_t ob = sbase + OFF_A + SLOT + wg * 8192;
      const uint32_t orow = ob + (wi * 16 + (lane & 7) + 8 * ((lane >> 3) & 1)) * 128;
#pragma unroll
      for (int i = 0; i < 4; i++) {
        const uint4 v = lds128(pin + i * 2048);
        const uint32_t r[4] = {v.x, v.y, v.z, v.w};
        uint32_t o[4];
#pragma unroll
        for (int k = 0; k < 4; k++) {
          const int idx = 8 * i + 2 * k;
          o[k] = pack_bf16(own[idx] + __uint_as_float(r[k] << 16), own[idx + 1] + __uint_as_float(r[k] & 0xffff0000u));
        }
        stsm_x4(orow + (((i * 2 + (lane >> 4)) ^ (lane & 7)) << 4), o[0], o[1], o[2], o[3]);
      }
      fence_async_smem();
      __syncwarp();
      if (lane == 0) {
        tma_store_2d(&P.tmOut, j * 64, rb * 128 + warp * 16, ob + wi * 2048);
        bulk_commit();
        asm volatile("cp.async.bulk.wait_group.read 0;" ::: "memory");
      }
    }
    if (tid == 0) TR(8);
  } else if (warp < 16) {
    asm volatile("setmaxnreg.dec.sync.aligned.u32 56;");
    cluster_wait();
    const int aw = __shfl_sync(0xffffffffu, (warp >> 2) & 1, 0);
    {
      const int rowg = rb * 128 + j * 16 + (warp - 8) * 2;
      const uint4* gw = (const uint4*)P.gate_w;
      const uint4* xr = (const uint4*)(P.x + (size_t)rowg * DM);
      mbar_wait(bars + 8 * (BAR_FULLB + 1), 0, t0);
      const uint4 w0 = __ldg(gw + lane), w1 = __ldg(gw + 32 + lane);
      const uint4 xa0 = __ldg(xr + lane), xa1 = __ldg(xr + 32 + lane), xb0 = __ldg(xr + 64 + lane), xb1 = __ldg(xr + 96 + lane);
#pragma unroll
      for (int i = 0; i < 4; i++) sts128(sbase + OFF_KV + 32768 + i * 4096 + (tid - 256) * 16, 0u, 0u, 0u, 0u);
      const uint32_t wa[8] = {w0.x, w0.y, w0.z, w0.w, w1.x, w1.y, w1.z, w1.w};
      const uint32_t xa[8] = {xa0.x, xa0.y, xa0.z, xa0.w, xa1.x, xa1.y, xa1.z, xa1.w};
      const uint32_t xb[8] = {xb0.x, xb0.y, xb0.z, xb0.w, xb1.x, xb1.y, xb1.z, xb1.w};
      float za = 0.f, zb = 0.f;
#pragma unroll
      for (int e = 0; e < 8; e++) {
        const float wl = __uint_as_float(wa[e] << 16), wh = __uint_as_float(wa[e] & 0xffff0000u);
        za = fmaf(__uint_as_float(xa[e] << 16), wl, za); za = fmaf(__uint_as_float(xa[e] & 0xffff0000u), wh, za);
        zb = fmaf(__uint_as_float(xb[e] << 16), wl, zb); zb = fmaf(__uint_as_float(xb[e] & 0xffff0000u), wh, zb);
      }
#pragma unroll
      for (int o = 16; o > 0; o >>= 1) { za += __shfl_xor_sync(0xffffffffu, za, o); zb += __shfl_xor_sync(0xffffffffu, zb, o); }
      if (lane < 2) asm volatile("st.shared.f32 [%0], %1;" ::"r"(sbase + OFF_GST + (warp - 8) * 8 + lane * 4), "f"(1.f / (1.f + __expf(-(lane ? zb : za)))) : "memory");
      fence_async_smem();
      named_bar<6>(256);
      if (tid == 256) {
        bulk_store(&g_gate[rb * 128 + j * 16], sbase + OFF_GST, 64);
        bulk_commit(); bulk_wait_all();
        flag_add(&g_flag_g[rb * FS]);
        flag_wait(&g_flag_g[rb * FS], ep1 * 8, t0);
        fence_async_global();
        mbar_expect_tx(bars + 8 * BAR_GIN, 512);
        bulk_load(sbase + OFF_GIN, &g_gate[rb * 128], 512, bars + 8 * BAR_GIN);
        TR(10);
      }
      __syncwarp();
    }
    mbar_wait(bars + 8 * (BAR_QRDY + aw), 0, t0);
    asm volatile("setmaxnreg.inc.sync.aligned.u32 96;");
    attention(sbase, aw, warp & 3, lane, rb, t0);
    if (tid == 256) TR(3);
  } else {
    asm volatile("setmaxnreg.dec.sync.aligned.u32 32;");
    if (warp == 16) {
      __syncwarp();
      cluster_wait();
      if (lane == 0) {
        int bi = 2; uint32_t bph = 1;
        const int nb = 32 + on + 4;
        for (int eb = 2; eb < nb; eb++) {
          if (eb == 4 || eb == 6) {
            const int ea = eb >> 1;
            mbar_expect_tx(bars + 8 * (BAR_FULLA + 1 + ea), 16384);
            tma_load_2d(sbase + OFF_A + (1 + ea) * SLOT, &P.tmX, ea * 64, rb * 128, bars + 8 * (BAR_FULLA + 1 + ea));
          }
          const uint32_t fb = bars + 8 * (BAR_FULLB + bi), dst = sbase + OFF_B + bi * SLOT + rank * 8192;
          mbar_wait(bars + 8 * (BAR_EMPTYB + bi), bph, t0);
          if (eb < 16) {
            mbar_expect_tx(fb, typeB ? 12288 : 16384);
            tma_load_3d_mc(dst, &P.tmWqkv, 64 * j, eb * 32 + rank * 16, 0, fb);
            if (!typeB) tma_load_3d_mc(dst + 6144, &P.tmW1a, 0, eb * 32 + rank * 16, 24 + (j >> 1), fb);
          }
          else if (eb < 32) { mbar_expect_tx(fb, 12288); tma_load_3d_mc(dst, &P.tmW1b, 0, (eb - 16) * 32 + rank * 16, 3 * j, fb); }
          else if (eb < 32 + on) { int ow; const int ch = oh_chunk(j, eb - 32, ow); mbar_expect_tx(fb, 16384); tma_load_3d_mc(dst, &P.tmW2, 0, ch * 64 + rank * 32, (j >> 1) * 2, fb); }
          else { mbar_expect_tx(fb, 16384); tma_load_4d_mc(dst, &P.tmWo, 64 * j, 0, eb - 32 - on, rank * 4, fb); }
          if (++bi == NB) { bi = 0; bph ^= 1; }
          if (eb == PFAT) {
            const int b = blockIdx.x;
            l2_prefetch((const uint8_t*)P.w1 + b * 14336, 14336);
            l2_prefetch((const uint8_t*)P.w2 + b * 14336, 14336);
            l2_prefetch((const uint8_t*)P.wo + b * 4096, 4096);
          }
        }
      }
    } else if (warp == 17) {
      cluster_wait();
      if (lane == 0) {
        for (int ea = 1; ea < 5; ea++) mbar_arrive(bars + 8 * (BAR_EMPTYA + ea));
        uint32_t aph = 0xE1;
        const int na = 16 + on + 8;
        unsigned ready = 0;
        for (int ea = 4; ea < na; ea++) {
          const int ai = a_slot(ea, 20 + on);
          const uint32_t fb = bars + 8 * (BAR_FULLA + ai), dst = sbase + OFF_A + ai * SLOT;
          int ch = ea & 7, need = -1;
          if (ea >= 16 + on) { need = 8 + ea - 16 - on; ch = 20 + need; }
          else if (ea >= 19) ch = oh_chunk(j, ea - 16, need);
          if (need >= 0 && !((ready >> need) & 1)) {
            const unsigned* fp = need < 8 ? &g_flag_h[rb * 8 * FS] : need < 16 ? &g_flag_o[rb * 8 * FS] : &g_flag_e[rb * 8 * FS];
            const unsigned tgt = (need & 8) ? ep1 * 4 : ep1;
            do {
              unsigned v[8];
#pragma unroll
              for (int i = 0; i < 8; i++) v[i] = ld_relaxed(fp + i * FS);
#pragma unroll
              for (int i = 0; i < 8; i++) if ((int)(v[i] - tgt) >= 0) ready |= 1u << (i + (need & 24));
            } while (!((ready >> need) & 1) && clk32() - t0 < TIMEOUT);
            fence_async_global();
          }
          mbar_wait(bars + 8 * (BAR_EMPTYA + ai), (aph >> ai) & 1, t0);
          if (ea >= 16 && ea < 19) mbar_arrive(fb);
          else {
            mbar_arrive(bars + 8 * (BAR_EMPTYA + ai));
            mbar_expect_tx(fb, 16384);
            tma_load_2d(dst, ea < 16 ? &P.tmX : &P.tmHO, ch * 64, rb * 128, fb);
          }
          TR(24 + ea);
          aph ^= 1u << ai;
        }
      }
    } else {
      const int wg = warp - 18;
      cluster_wait();
      if (lane == 0 && wg == 0) {
        const uint32_t stg = bars + 8 * BAR_STG;
        mbar_wait(stg, 0, t0);
        for (int hh = 0; hh < 4; hh++) bulk_store(g_kv + ((size_t)(4 * j + hh) * SEQ + rb * 128) * 64, sbase + OFF_KV + hh * 8192, 8192);
        bulk_commit(); bulk_wait_all();
        flag_add(&g_flag_kv[(rb * 8 + j) * FS]);
        TR(21);
        if (!typeB) {
          mbar_wait(bars + 8 * BAR_STE, 0, t0);
          tma_store_2d(&P.tmHO, (24 + (j >> 1)) * 64, rb * 128, sbase + OFF_KV + 32768);
          bulk_commit(); bulk_wait_all();
          flag_add(&g_flag_e[(rb * 8 + j) * FS]);
        }
        mbar_arrive(bars + 8 * BAR_KVOK);
        mbar_wait(stg, 1, t0);
        for (int i = 0; i < 3; i++) tma_store_2d(&P.tmHO, (3 * j + i) * 64, rb * 128, sbase + OFF_A + (1 + i) * SLOT);
        bulk_commit(); bulk_wait_all();
        flag_add(&g_flag_h[(rb * 8 + j) * FS]);
        for (int i = 0; i < 3; i++) mbar_arrive(bars + 8 * (BAR_EMPTYA + 1 + i));
        TR(22);
        {
          const unsigned old = atomicAdd(&g_done, 1u);
          if (old == gridDim.x - 1) { g_done = 0; *(volatile unsigned*)&g_epoch = ep1; }
        }
        mbar_wait(stg, 0, t0);
        bulk_store(g_part + (size_t)(rb * 8 + (j ^ 1)) * 16384, sbase + OFF_B + ((30 + on) % NB) * SLOT, 16384);
        bulk_commit(); bulk_wait_all();
        flag_add(&g_flag_p[(rb * 8 + (j ^ 1)) * FS]);
        TR(23);
        flag_wait(&g_flag_p[(rb * 8 + j) * FS], ep1, t0);
        fence_async_global();
        mbar_expect_tx(bars + 8 * BAR_PIN, 16384);
        bulk_load(sbase + OFF_B + ((31 + on) % NB) * SLOT, g_part + (size_t)(rb * 8 + j) * 16384, 16384, bars + 8 * BAR_PIN);
      } else if (lane == 0) {
        const int nblk = rb >= 2 ? 3 : rb + 1;
        const uint32_t kvbytes = nblk * 8192;
        const uint8_t* kvsrc = g_kv + ((size_t)(4 * j) * SEQ + (rb + 1 - nblk) * 128) * 64;
        const uint32_t kvdst = sbase + OFF_KV + (3 - nblk) * 8192;
        {
          const unsigned* f0 = &g_flag_kv[(rb * 8 + j) * FS];
          const unsigned* f1 = rb >= 1 ? f0 - 8 * FS : f0;
          const unsigned* f2 = rb >= 2 ? f0 - 16 * FS : f0;
          unsigned v0, v1, v2;
          do { v0 = ld_relaxed(f0); v1 = ld_relaxed(f1); v2 = ld_relaxed(f2); }
          while (((int)(v0 - ep1) < 0 || (int)(v1 - ep1) < 0 || (int)(v2 - ep1) < 0) && clk32() - t0 < TIMEOUT);
        }
        TR(11);
        mbar_wait(bars + 8 * BAR_GIN, 0, t0);
        fence_async_global();
        mbar_expect_tx(bars + 8 * BAR_KVFULL, kvbytes);
        bulk_load(kvdst, kvsrc, kvbytes, bars + 8 * BAR_KVFULL);
        mbar_wait(bars + 8 * BAR_KVOK, 0, t0);
        mbar_expect_tx(bars + 8 * (BAR_KVFULL + 1), kvbytes);
        bulk_load(kvdst + KVBUF, kvsrc + (size_t)SEQ * 64, kvbytes, bars + 8 * (BAR_KVFULL + 1));
        for (int hh = 0; hh < 4; hh++) {
          for (int aw = 0; aw < 2; aw++) {
            mbar_wait(bars + 8 * (BAR_OST + aw), hh & 1, t0);
            tma_store_2d(&P.tmOs, DFF + hh * 128 + j * 16, rb * 128 + aw * 64, sbase + OFF_A + aw * 8192 + hh * 2048);
          }
          bulk_commit();
          if (hh < 2) {
            mbar_wait(bars + 8 * (BAR_KVEMPTY + hh), 0, t0);
            mbar_expect_tx(bars + 8 * (BAR_KVFULL + hh), kvbytes);
            bulk_load(kvdst + hh * KVBUF, kvsrc + (size_t)(hh + 2) * SEQ * 64, kvbytes, bars + 8 * (BAR_KVFULL + hh));
          }
          bulk_wait_all();
          flag_add(&g_flag_o[(rb * 8 + hh * 2 + (j >> 2)) * FS]);
          TR(12 + hh);
        }
      }
    }
  }
}

typedef CUresult (*EncodeFn)(CUtensorMap*, CUtensorMapDataType, cuuint32_t, void*, const cuuint64_t*, const cuuint64_t*, const cuuint32_t*,
                             const cuuint32_t*, CUtensorMapInterleave, CUtensorMapSwizzle, CUtensorMapL2promotion, CUtensorMapFloatOOBfill);

void make_map(EncodeFn enc, CUtensorMap* m, const void* ptr, int rank, const cuuint64_t* dims, const cuuint64_t* strides, const cuuint32_t* box,
              CUtensorMapSwizzle sw = CU_TENSOR_MAP_SWIZZLE_128B) {
  cuuint32_t es[4] = {1, 1, 1, 1};
  enc(m, CU_TENSOR_MAP_DATA_TYPE_BFLOAT16, rank, const_cast<void*>(ptr), dims, strides, box, es, CU_TENSOR_MAP_INTERLEAVE_NONE, sw,
      CU_TENSOR_MAP_L2_PROMOTION_L2_256B, CU_TENSOR_MAP_FLOAT_OOB_FILL_NONE);
}

}

extern "C" void kernel_launch(void* const* d_in, const int* in_sizes, int n_in, void* d_out, int out_size) {
  (void)in_sizes; (void)n_in; (void)out_size;
  static EncodeFn enc = nullptr;
  static void* ho_ptr = nullptr;
  if (!enc) {
    void* fn = nullptr; cudaDriverEntryPointQueryResult st;
    cudaGetDriverEntryPoint("cuTensorMapEncodeTiled", &fn, cudaEnableDefault, &st);
    enc = (EncodeFn)fn;
    cudaGetSymbolAddress(&ho_ptr, g_ho);
    cudaFuncSetAttribute(fused_kernel, cudaFuncAttributeMaxDynamicSharedMemorySize, SMEM_BYTES);
  }
  const __nv_bfloat16* x = (const __nv_bfloat16*)d_in[0];
  const __nv_bfloat16* wqkv = (const __nv_bfloat16*)d_in[1];
  const __nv_bfloat16* wo = (const __nv_bfloat16*)d_in[2];
  const __nv_bfloat16* w1 = (const __nv_bfloat16*)d_in[4];
  const __nv_bfloat16* w2 = (const __nv_bfloat16*)d_in[5];
  const __nv_bfloat16* gate_w = (const __nv_bfloat16*)d_in[6];
  Params P;
  { cuuint64_t d[2] = {DM, SEQ}, s[1] = {DM * 2}; cuuint32_t b[2] = {64, 128}; make_map(enc, &P.tmX, x, 2, d, s, b); }
  { cuuint64_t d[3] = {512, 512, 3}, s[2] = {1536 * 2, 512 * 2}; cuuint32_t b[3] = {64, 16, 3}; make_map(enc, &P.tmWqkv, wqkv, 3, d, s, b); }
  { cuuint64_t d[3] = {64, 512, 28}, s[2] = {DFF * 2, 128}; cuuint32_t b[3] = {64, 16, 1}; make_map(enc, &P.tmW1a, w1, 3, d, s, b);
    b[2] = 3; make_map(enc, &P.tmW1b, w1, 3, d, s, b); }
  { cuuint64_t d[3] = {64, DFF, 8}, s[2] = {DM * 2, 128}; cuuint32_t b[3] = {64, 32, 2}; make_map(enc, &P.tmW2, w2, 3, d, s, b); }
  { cuuint64_t d[4] = {DM, 16, 4, 8}, s[3] = {DM * 2, 16 * DM * 2, 64 * DM * 2}; cuuint32_t b[4] = {64, 16, 1, 4}; make_map(enc, &P.tmWo, wo, 4, d, s, b); }
  { cuuint64_t d[2] = {KHO, SEQ}, s[1] = {KHO * 2}; cuuint32_t b[2] = {64, 128}; make_map(enc, &P.tmHO, ho_ptr, 2, d, s, b);
    b[1] = 64; make_map(enc, &P.tmHOs, ho_ptr, 2, d, s, b);
    b[0] = 16; make_map(enc, &P.tmOs, ho_ptr, 2, d, s, b, CU_TENSOR_MAP_SWIZZLE_NONE); }
  { cuuint64_t d[2] = {DM, SEQ}, s[1] = {DM * 2}; cuuint32_t b[2] = {64, 16}; make_map(enc, &P.tmOut, d_out, 2, d, s, b); }
  P.x = x; P.gate_w = gate_w; P.w1 = w1; P.w2 = w2; P.wo = wo; P.out = (__nv_bfloat16*)d_out;
  fused_kernel<<<128, 640, SMEM_BYTES>>>(P);
}
```

```cpp
#include <cuda_runtime.h>
#include <cuda_bf16.h>
#include <cuda.h>
#include <stdint.h>

#define DEVI __device__ __forceinline__

namespace {

constexpr int SEQ = 2048, DM = 512, DFF = 1792, KHO = 2304;
constexpr int NA = 5, NB = 6, SLOT = 16384, KVBUF = 24576;
constexpr int NA2 = 8;
constexpr int OFF_B = 0, OFF_A = NB * SLOT, OFF_KV = OFF_A + NA * SLOT, OFF_BAR = OFF_KV + 2 * KVBUF;
constexpr int OFF_GST = OFF_BAR + 512;
constexpr int OFF_GIN = OFF_BAR + 1024;
constexpr int OFF_NM = OFF_BAR + 1536;
constexpr int SMEM_BYTES = OFF_BAR + 2560;
constexpr uint32_t TIMEOUT = 1u << 28;
#define WAIT_HINT_NS 20000u
#define PFAT 8
#define SH false
#define SHW 1
#define SHG 1
constexpr int FS = 8;

constexpr int BAR_FULLA = 0, BAR_EMPTYA = BAR_FULLA + NA2, BAR_FULLB = BAR_EMPTYA + NA2, BAR_EMPTYB = BAR_FULLB + NB,
              BAR_KVFULL = BAR_EMPTYB + NB, BAR_KVEMPTY = BAR_KVFULL + 2, BAR_STG = BAR_KVEMPTY + 2, BAR_PIN = BAR_STG + 2, BAR_GATE = BAR_PIN + 1, BAR_STE = BAR_GATE + 2, BAR_ATTDONE = BAR_STE + 2, BAR_GIN = BAR_ATTDONE + 1, BAR_OST = BAR_GIN + 1, BAR_QRDY = BAR_OST + 2, BAR_KVOK = BAR_QRDY + 2;

__device__ __align__(1024) uint8_t g_kv[32 * SEQ * 64];
__device__ __align__(1024) __nv_bfloat16 g_ho[SEQ * KHO];
__device__ __align__(1024) uint8_t g_part[128 * 16384];
__device__ __align__(128) float g_gate[SEQ];
__device__ unsigned g_flag_kv[128 * FS], g_flag_h[128 * FS], g_flag_o[128 * FS], g_flag_g[16 * FS], g_flag_p[128 * FS], g_flag_e[128 * FS];
__device__ unsigned g_epoch, g_done;
#define TR(i) do {} while (0)

struct Params {
  CUtensorMap tmX, tmWqkv, tmW1a, tmW1b, tmW2, tmWo, tmHO, tmHOs, tmOs, tmOut;
  const __nv_bfloat16* x;
  const __nv_bfloat16* gate_w;
  const __nv_bfloat16* w1;
  const __nv_bfloat16* w2;
  const __nv_bfloat16* wo;
  __nv_bfloat16* out;
};

DEVI uint32_t smem_u32(const void* p) { return (uint32_t)__cvta_generic_to_shared(p); }
DEVI uint32_t clk32() { uint32_t c; asm volatile("mov.u32 %0, %%clock;" : "=r"(c)); return c; }
DEVI void mbar_init(uint32_t bar, uint32_t cnt) { asm volatile("mbarrier.init.shared::cta.b64 [%0], %1;" ::"r"(bar), "r"(cnt)); }
DEVI void mbar_expect_tx(uint32_t bar, uint32_t bytes) { asm volatile("mbarrier.arrive.expect_tx.shared::cta.b64 _, [%0], %1;" ::"r"(bar), "r"(bytes) : "memory"); }
DEVI void mbar_arrive(uint32_t bar) { asm volatile("mbarrier.arrive.shared::cta.b64 _, [%0];" ::"r"(bar) : "memory"); }
DEVI void mbar_arrive_cluster(uint32_t bar, uint32_t cta) {
  asm volatile("{ .reg .b32 ra; mapa.shared::cluster.u32 ra, %0, %1; mbarrier.arrive.shared::cluster.b64 _, [ra]; }" ::"r"(bar), "r"(cta) : "memory");
}
DEVI void mbar_wait(uint32_t bar, uint32_t parity, uint32_t t0) {
  asm volatile("{ .reg .pred p; .reg .u32 c;\n"
               "mbarrier.try_wait.parity.shared::cta.b64 p, [%0], %1;\n"
               "@p bra DONE_%=;\n"
               "WAIT_%=:\n"
               "mbarrier.try_wait.parity.shared::cta.b64 p, [%0], %1, %4;\n"
               "@p bra DONE_%=;\n"
               "mov.u32 c, %%clock; sub.u32 c, c, %2; setp.lt.u32 p, c, %3;\n"
               "@p bra WAIT_%=;\n"
               "DONE_%=: }" ::"r"(bar), "r"(parity), "r"(t0), "n"(TIMEOUT), "r"(WAIT_HINT_NS) : "memory");
}
DEVI unsigned ld_relaxed(const unsigned* p) { unsigned v; asm volatile("ld.relaxed.gpu.global.u32 %0, [%1];" : "=r"(v) : "l"(p) : "memory"); return v; }
DEVI void flag_wait(const unsigned* p, unsigned target, uint32_t t0) {
  while ((int)(ld_relaxed(p) - target) < 0) { if (clk32() - t0 > TIMEOUT) break; }
}
DEVI void flag_add(unsigned* p) { asm volatile("red.relaxed.gpu.global.add.u32 [%0], 1;" ::"l"(p) : "memory"); }
DEVI void fence_async_smem() { asm volatile("fence.proxy.async.shared::cta;" ::: "memory"); }
DEVI void fence_async_global() { asm volatile("fence.proxy.async.global;" ::: "memory"); }
DEVI void tma_load_2d(uint32_t dst, const CUtensorMap* m, int c0, int c1, uint32_t bar) {
  asm volatile("cp.async.bulk.tensor.2d.shared::cluster.global.mbarrier::complete_tx::bytes [%0], [%1, {%3, %4}], [%2];" ::"r"(dst), "l"(m), "r"(bar), "r"(c0), "r"(c1) : "memory");
}
DEVI void tma_load_3d(uint32_t dst, const CUtensorMap* m, int c0, int c1, int c2, uint32_t bar) {
  asm volatile("cp.async.bulk.tensor.3d.shared::cluster.global.mbarrier::complete_tx::bytes [%0], [%1, {%3, %4, %5}], [%2];"
               ::"r"(dst), "l"(m), "r"(bar), "r"(c0), "r"(c1), "r"(c2) : "memory");
}
DEVI void tma_load_3d_mc(uint32_t dst, const CUtensorMap* m, int c0, int c1, int c2, uint32_t bar) {
  asm volatile("cp.async.bulk.tensor.3d.shared::cluster.global.mbarrier::complete_tx::bytes.multicast::cluster [%0], [%1, {%3, %4, %5}], [%2], %6;"
               ::"r"(dst), "l"(m), "r"(bar), "r"(c0), "r"(c1), "r"(c2), "h"((uint16_t)3) : "memory");
}
DEVI void tma_load_4d_mc(uint32_t dst, const CUtensorMap* m, int c0, int c1, int c2, int c3, uint32_t bar) {
  asm volatile("cp.async.bulk.tensor.4d.shared::cluster.global.mbarrier::complete_tx::bytes.multicast::cluster [%0], [%1, {%3, %4, %5, %6}], [%2], %7;"
               ::"r"(dst), "l"(m), "r"(bar), "r"(c0), "r"(c1), "r"(c2), "r"(c3), "h"((uint16_t)3) : "memory");
}
DEVI void tma_store_2d(const CUtensorMap* m, int c0, int c1, uint32_t src) {
  asm volatile("cp.async.bulk.tensor.2d.global.shared::cta.bulk_group [%0, {%1, %2}], [%3];" ::"l"(m), "r"(c0), "r"(c1), "r"(src) : "memory");
}
DEVI void bulk_store(void* dst, uint32_t src, uint32_t bytes) {
  asm volatile("cp.async.bulk.global.shared::cta.bulk_group [%0], [%1], %2;" ::"l"(dst), "r"(src), "r"(bytes) : "memory");
}
DEVI void bulk_load(uint32_t dst, const void* src, uint32_t bytes, uint32_t bar) {
  asm volatile("cp.async.bulk.shared::cluster.global.mbarrier::complete_tx::bytes [%0], [%1], %2, [%3];" ::"r"(dst), "l"(src), "r"(bytes), "r"(bar) : "memory");
}
DEVI void bulk_commit() { asm volatile("cp.async.bulk.commit_group;" ::: "memory"); }
DEVI void bulk_wait_all() { asm volatile("cp.async.bulk.wait_group 0;" ::: "memory"); }
DEVI void l2_prefetch(const void* p, uint32_t bytes) { asm volatile("cp.async.bulk.prefetch.L2.global [%0], %1;" ::"l"(p), "r"(bytes) : "memory"); }
DEVI void cluster_arrive() { asm volatile("barrier.cluster.arrive.relaxed.aligned;" ::: "memory"); }
DEVI void cluster_wait() { asm volatile("barrier.cluster.wait.aligned;" ::: "memory"); }
template <int ID> DEVI void named_bar(int n) { asm volatile("bar.sync %0, %1;" ::"n"(ID), "r"(n) : "memory"); }
DEVI void wg_bar(int wg) { if (wg == 0) named_bar<1>(128); else named_bar<2>(128); }
DEVI void wgmma_fence() { asm volatile("wgmma.fence.sync.aligned;" ::: "memory"); }
DEVI void wgmma_commit() { asm volatile("wgmma.commit_group.sync.aligned;" ::: "memory"); }
template <int N> DEVI void wgmma_wait() { asm volatile("wgmma.wait_group.sync.aligned %0;" ::"n"(N) : "memory"); }
template <uint32_t LBO> DEVI uint64_t desc_sw128(uint32_t a16) {
  return ((uint64_t)(0x40000000u | (1024 >> 4)) << 32) | (a16 + ((LBO >> 4) << 16));
}
DEVI uint64_t desc_sw64(uint32_t a16) {
  return ((uint64_t)(0x80000000u | (512 >> 4)) << 32) | (a16 + ((512 >> 4) << 16));
}
DEVI uint32_t pack_bf16(float lo, float hi) { uint32_t r; asm("cvt.rn.bf16x2.f32 %0, %1, %2;" : "=r"(r) : "f"(hi), "f"(lo)); return r; }
DEVI void stsm_x4(uint32_t addr, uint32_t r0, uint32_t r1, uint32_t r2, uint32_t r3) {
  asm volatile("stmatrix.sync.aligned.m8n8.x4.shared.b16 [%0], {%1, %2, %3, %4};" ::"r"(addr), "r"(r0), "r"(r1), "r"(r2), "r"(r3) : "memory");
}
DEVI void sts128(uint32_t addr, uint32_t r0, uint32_t r1, uint32_t r2, uint32_t r3) {
  asm volatile("st.shared.v4.b32 [%0], {%1, %2, %3, %4};" ::"r"(addr), "r"(r0), "r"(r1), "r"(r2), "r"(r3) : "memory");
}
DEVI uint4 lds128(uint32_t addr) {
  uint4 v; asm volatile("ld.shared.v4.b32 {%0, %1, %2, %3}, [%4];" : "=r"(v.x), "=r"(v.y), "=r"(v.z), "=r"(v.w) : "r"(addr) : "memory"); return v;
}
DEVI float ex2(float x) { float y; asm("ex2.approx.ftz.f32 %0, %1;" : "=f"(y) : "f"(x)); return y; }

DEVI void wgmma_ss_n64(float (&d)[32], uint64_t da, uint64_t db) {
  asm volatile("wgmma.mma_async.sync.aligned.m64n64k16.f32.bf16.bf16 {%0, %1, %2, %3, %4, %5, %6, %7, %8, %9, %10, %11, %12, %13, %14, %15, %16, %17, %18, %19, %20, %21, %22, %23, %24, %25, %26, %27, %28, %29, %30, %31}, %32, %33, 1, 1, 1, 0, 1;"
    : "+f"(d[0]), "+f"(d[1]), "+f"(d[2]), "+f"(d[3]), "+f"(d[4]), "+f"(d[5]), "+f"(d[6]), "+f"(d[7]), "+f"(d[8]), "+f"(d[9]), "+f"(d[10]), "+f"(d[11]), "+f"(d[12]), "+f"(d[13]), "+f"(d[14]), "+f"(d[15]), "+f"(d[16]), "+f"(d[17]), "+f"(d[18]), "+f"(d[19]), "+f"(d[20]), "+f"(d[21]), "+f"(d[22]), "+f"(d[23]), "+f"(d[24]), "+f"(d[25]), "+f"(d[26]), "+f"(d[27]), "+f"(d[28]), "+f"(d[29]), "+f"(d[30]), "+f"(d[31])
    : "l"(da), "l"(db));
}
DEVI void wgmma_ss_n128(float (&d)[64], uint64_t da, uint64_t db) {
  asm volatile("wgmma.mma_async.sync.aligned.m64n128k16.f32.bf16.bf16 {%0, %1, %2, %3, %4, %5, %6, %7, %8, %9, %10, %11, %12, %13, %14, %15, %16, %17, %18, %19, %20, %21, %22, %23, %24, %25, %26, %27, %28, %29, %30, %31, %32, %33, %34, %35, %36, %37, %38, %39, %40, %41, %42, %43, %44, %45, %46, %47, %48, %49, %50, %51, %52, %53, %54, %55, %56, %57, %58, %59, %60, %61, %62, %63}, %64, %65, 1, 1, 1, 0, 1;"
    : "+f"(d[0]), "+f"(d[1]), "+f"(d[2]), "+f"(d[3]), "+f"(d[4]), "+f"(d[5]), "+f"(d[6]), "+f"(d[7]), "+f"(d[8]), "+f"(d[9]), "+f"(d[10]), "+f"(d[11]), "+f"(d[12]), "+f"(d[13]), "+f"(d[14]), "+f"(d[15]), "+f"(d[16]), "+f"(d[17]), "+f"(d[18]), "+f"(d[19]), "+f"(d[20]), "+f"(d[21]), "+f"(d[22]), "+f"(d[23]), "+f"(d[24]), "+f"(d[25]), "+f"(d[26]), "+f"(d[27]), "+f"(d[28]), "+f"(d[29]), "+f"(d[30]), "+f"(d[31]), "+f"(d[32]), "+f"(d[33]), "+f"(d[34]), "+f"(d[35]), "+f"(d[36]), "+f"(d[37]), "+f"(d[38]), "+f"(d[39]), "+f"(d[40]), "+f"(d[41]), "+f"(d[42]), "+f"(d[43]), "+f"(d[44]), "+f"(d[45]), "+f"(d[46]), "+f"(d[47]), "+f"(d[48]), "+f"(d[49]), "+f"(d[50]), "+f"(d[51]), "+f"(d[52]), "+f"(d[53]), "+f"(d[54]), "+f"(d[55]), "+f"(d[56]), "+f"(d[57]), "+f"(d[58]), "+f"(d[59]), "+f"(d[60]), "+f"(d[61]), "+f"(d[62]), "+f"(d[63])
    : "l"(da), "l"(db));
}
DEVI void wgmma_qk64(float (&d)[32], uint32_t a0, uint32_t a1, uint32_t a2, uint32_t a3, uint64_t db) {
  asm volatile("wgmma.mma_async.sync.aligned.m64n64k16.f32.bf16.bf16 {%0, %1, %2, %3, %4, %5, %6, %7, %8, %9, %10, %11, %12, %13, %14, %15, %16, %17, %18, %19, %20, %21, %22, %23, %24, %25, %26, %27, %28, %29, %30, %31}, {%32, %33, %34, %35}, %36, 0, 1, 1, 0;"
    : "=f"(d[0]), "=f"(d[1]), "=f"(d[2]), "=f"(d[3]), "=f"(d[4]), "=f"(d[5]), "=f"(d[6]), "=f"(d[7]), "=f"(d[8]), "=f"(d[9]), "=f"(d[10]), "=f"(d[11]), "=f"(d[12]), "=f"(d[13]), "=f"(d[14]), "=f"(d[15]), "=f"(d[16]), "=f"(d[17]), "=f"(d[18]), "=f"(d[19]), "=f"(d[20]), "=f"(d[21]), "=f"(d[22]), "=f"(d[23]), "=f"(d[24]), "=f"(d[25]), "=f"(d[26]), "=f"(d[27]), "=f"(d[28]), "=f"(d[29]), "=f"(d[30]), "=f"(d[31])
    : "r"(a0), "r"(a1), "r"(a2), "r"(a3), "l"(db));
}
DEVI void wgmma_pv(float (&d)[8], uint32_t a0, uint32_t a1, uint32_t a2, uint32_t a3, uint64_t db) {
  asm volatile("wgmma.mma_async.sync.aligned.m64n16k16.f32.bf16.bf16 {%0, %1, %2, %3, %4, %5, %6, %7}, {%8, %9, %10, %11}, %12, 1, 1, 1, 1;"
    : "+f"(d[0]), "+f"(d[1]), "+f"(d[2]), "+f"(d[3]), "+f"(d[4]), "+f"(d[5]), "+f"(d[6]), "+f"(d[7])
    : "r"(a0), "r"(a1), "r"(a2), "r"(a3), "l"(db));
}
DEVI void wgmma_pv0(float (&d)[8], uint32_t a0, uint32_t a1, uint32_t a2, uint32_t a3, uint64_t db) {
  asm volatile("wgmma.mma_async.sync.aligned.m64n16k16.f32.bf16.bf16 {%0, %1, %2, %3, %4, %5, %6, %7}, {%8, %9, %10, %11}, %12, 0, 1, 1, 1;"
    : "=f"(d[0]), "=f"(d[1]), "=f"(d[2]), "=f"(d[3]), "=f"(d[4]), "=f"(d[5]), "=f"(d[6]), "=f"(d[7])
    : "r"(a0), "r"(a1), "r"(a2), "r"(a3), "l"(db));
}

template <int N> struct Acc { float a[64]; float b[(N - 128) / 2]; DEVI float& operator[](int i) { return i < 64 ? a[i] : b[i - 64]; } };
template <> struct Acc<64> { float a[32]; DEVI float& operator[](int i) { return a[i]; } };
template <> struct Acc<128> { float a[64]; DEVI float& operator[](int i) { return a[i]; } };
template <int N> DEVI void wgmma_ss(Acc<N>& d, uint64_t da, uint64_t db) {
  if constexpr (N == 64) wgmma_ss_n64(d.a, da, db); else wgmma_ss_n128(d.a, da, db);
  if constexpr (N == 192) wgmma_ss_n64(d.b, da, db + 256);
  if constexpr (N == 256) wgmma_ss_n128(d.b, da, db + 256);
}

DEVI int oh_chunk(int j, int i, int& need) {
  if (i >= 3 && i < 5) { const int e = (j & 1) * 2 + i - 3; need = 16 + 2 * e; return 24 + e; }
  if (i >= 5) i -= 2;
  int o, r;
  if (i >= 12) { o = (j + 5) & 7; r = i - 11; }
  else { const int g = i / 3; o = (j + 2 * g) & 7; r = i - 3 * g; }
  need = o;
  return 3 * o + r;
}

DEVI int a_slot(int e) { return 1 + (e & 3); }

struct Ctx {
  uint32_t sbase, bars, peer, t0, a16, b16;
  int wg, lane;
  int ai, bi; uint32_t aph, bph;
  int brem, ae;
  int pa, pb;
};

DEVI void release_prev(Ctx& c) {
  if (c.pb >= 0) {
    if (c.lane == 0) mbar_arrive(c.bars + 8 * (BAR_EMPTYB + c.pb));
    if (c.lane == 1) mbar_arrive_cluster(c.bars + 8 * (BAR_EMPTYB + c.pb), c.peer);
  }
  if (c.pa >= 0 && c.lane == 2) mbar_arrive(c.bars + 8 * (BAR_EMPTYA + c.pa));
}

DEVI void gemm_wait(Ctx& c) {
  asm volatile("{ .reg .pred p, q; .reg .u32 c;\n"
               "mbarrier.try_wait.parity.shared::cta.b64 p, [%0], %1;\n"
               "mbarrier.try_wait.parity.shared::cta.b64 q, [%2], %3;\n"
               "and.pred p, p, q;\n"
               "@p bra DONE_%=;\n"
               "WAIT_%=:\n"
               "mbarrier.try_wait.parity.shared::cta.b64 p, [%0], %1, %6;\n"
               "mbarrier.try_wait.parity.shared::cta.b64 q, [%2], %3, %6;\n"
               "and.pred p, p, q;\n"
               "@p bra DONE_%=;\n"
               "mov.u32 c, %%clock; sub.u32 c, c, %4; setp.lt.u32 p, c, %5;\n"
               "@p bra WAIT_%=;\n"
               "DONE_%=: }" ::"r"(c.bars + 8 * (BAR_FULLA + c.ai)), "r"((c.aph >> c.ai) & 1), "r"(c.bars + 8 * (BAR_FULLB + c.bi)), "r"(c.bph), "r"(c.t0),
               "n"(TIMEOUT), "r"(WAIT_HINT_NS) : "memory");
}
template <int N, bool SHALLOW>
DEVI void gemm_group(Acc<N>& acc, Ctx& c, int g, int& npa, int& npb) {
  const uint32_t a16 = c.a16 + c.ai * (SLOT >> 4);
  const uint32_t b16 = c.b16 + c.bi * (SLOT >> 4);
  bool adv;
  if constexpr (N >= 192) {
    const uint32_t a2 = a16 + (g & 1) * 4;
    wgmma_ss<N>(acc, desc_sw128<16>(a2), desc_sw128<2048>(b16));
    if (SHALLOW) { wgmma_commit(); wgmma_wait<SHW>(); }
    wgmma_ss<N>(acc, desc_sw128<16>(a2 + 2), desc_sw128<2048>(b16 + 512));
    adv = g & 1;
  } else {
#pragma unroll
    for (int s = 0; s < 4; s++) {
      wgmma_ss<N>(acc, desc_sw128<16>(a16 + s * 2), desc_sw128<4096>(b16 + (s >> 1) * 512 + (s & 1) * 128));
      if (SHALLOW && s < 3 && (SHG == 1 || s == 1)) { wgmma_commit(); wgmma_wait<SHW>(); }
    }
    adv = true;
  }
  wgmma_commit();
  npb = c.brem > 0 ? c.bi : -1;
  c.brem--;
  if (++c.bi == NB) { c.bi = 0; c.bph ^= 1; }
  npa = -1;
  if (adv) { npa = c.ai; c.aph ^= 1u << c.ai; c.ae++; c.ai = 1 + (c.ae & 3); }
}

template <int N, bool SHALLOW = false>
DEVI void bare_groups(Acc<N>& acc, Ctx& c, int g0, int g1) {
  for (int g = g0; g < g1; g++) {
    int npa, npb;
    gemm_wait(c);
    wgmma_fence();
    gemm_group<N, SHALLOW>(acc, c, g, npa, npb);
    wgmma_wait<SHALLOW ? SHW : 1>();
    release_prev(c);
    c.pa = npa; c.pb = npb;
  }
}
DEVI void drain(Ctx& c) {
  wgmma_wait<0>();
  release_prev(c);
  c.pa = c.pb = -1;
}

constexpr float SC = 0.25f * 1.4426950408889634f;

#define ONCE _Pragma("unroll 1") for (unsigned once_ = 0; once_ < gridDim.y; once_++)

struct Gate { float g0, g1; };

DEVI void kill32(float (&S)[32]) {
#pragma unroll
  for (int i = 0; i < 32; i++) S[i] = __int_as_float(0xff800000);
}
DEVI void row_max(const float (&S)[32], float& x0, float& x1) {
  float y0 = S[1], y1 = S[3];
  x0 = fmaxf(x0, S[0]); x1 = fmaxf(x1, S[2]);
#pragma unroll
  for (int n = 1; n < 8; n++) {
    x0 = fmaxf(x0, S[4 * n]); y0 = fmaxf(y0, S[4 * n + 1]); x1 = fmaxf(x1, S[4 * n + 2]); y1 = fmaxf(y1, S[4 * n + 3]);
  }
  x0 = fmaxf(x0, y0); x1 = fmaxf(x1, y1);
}
DEVI void quad_max(float& x0, float& x1) {
  x0 = fmaxf(x0, __shfl_xor_sync(0xffffffffu, x0, 1)); x1 = fmaxf(x1, __shfl_xor_sync(0xffffffffu, x1, 1));
  x0 = fmaxf(x0, __shfl_xor_sync(0xffffffffu, x0, 2)); x1 = fmaxf(x1, __shfl_xor_sync(0xffffffffu, x1, 2));
}
DEVI void exp32(const float (&S)[32], float (&E)[32], float n0, float n1, float (&l)[4]) {
#pragma unroll
  for (int i = 0; i < 32; i++) { E[i] = ex2(fmaf(S[i], SC, (i & 2) ? n1 : n0)); l[i & 3] += E[i]; }
}
DEVI void pack32(const float (&E)[32], uint32_t (&P)[16]) {
#pragma unroll
  for (int i = 0; i < 16; i++) P[i] = pack_bf16(E[2 * i], E[2 * i + 1]);
}
template <bool FIRST> DEVI void pv4(float (&O)[8], const uint32_t (&P)[16], uint32_t v16) {
  if (FIRST) wgmma_pv0(O, P[0], P[1], P[2], P[3], desc_sw64(v16)); else wgmma_pv(O, P[0], P[1], P[2], P[3], desc_sw64(v16));
#pragma unroll
  for (int k = 1; k < 4; k++) wgmma_pv(O, P[4 * k], P[4 * k + 1], P[4 * k + 2], P[4 * k + 3], desc_sw64(v16 + k * 64));
}
DEVI bool wg_any(int wg, bool v) {
  uint32_t r;
  if (wg == 0) asm volatile("{ .reg .pred p, q; setp.ne.u32 p, %1, 0; bar.red.or.pred q, 4, 128, p; selp.u32 %0, 1, 0, q; }" : "=r"(r) : "r"((uint32_t)v) : "memory");
  else asm volatile("{ .reg .pred p, q; setp.ne.u32 p, %1, 0; bar.red.or.pred q, 5, 128, p; selp.u32 %0, 1, 0, q; }" : "=r"(r) : "r"((uint32_t)v) : "memory");
  return r != 0;
}
DEVI void get_gate(Gate& g, uint32_t sbase, int row16, int lane, uint32_t t0) {
  mbar_wait(sbase + OFF_BAR + 8 * BAR_GIN, 0, t0);
  const uint32_t a = sbase + OFF_GIN + (row16 * 16 + (lane >> 2)) * 4;
  asm volatile("ld.shared.f32 %0, [%1];" : "=f"(g.g0) : "r"(a) : "memory");
  asm volatile("ld.shared.f32 %0, [%1];" : "=f"(g.g1) : "r"(a + 32) : "memory");
}

DEVI void attention(uint32_t sbase, int aw, int wi, int lane, int rb, uint32_t t0) {
  const uint32_t bars = sbase + OFF_BAR;
  const uint32_t kvb = ((sbase & 0x3FFFF) + OFF_KV + aw * 4096) >> 4;
  const int cmin = 4 - 2 * rb - aw;
  const int rowc = wi * 16 + (lane >> 2) - (lane & 3) * 2;
  const uint32_t qst = sbase + OFF_A + aw * 8192;
  const float NINF = __int_as_float(0xff800000);
  const int tlo = max(cmin, 1);
#pragma unroll 1
  for (int h = 0; h < 4; h++) {
    const uint32_t kb = kvb + (h & 1) * (KVBUF >> 4);
    const uint4 q = lds128(qst + h * 2048 + (wi * 32 + lane) * 16);
    float O[8], l0, l1;
    uint32_t nm;
    asm volatile("ld.shared.u32 %0, [%1];" : "=r"(nm) : "r"(sbase + OFF_NM + ((aw * 4 + wi) * 32 + (lane & 28) + h) * 4) : "memory");
    float n0 = __uint_as_float(nm << 16), n1 = __uint_as_float(nm & 0xffff0000u);
    mbar_wait(bars + 8 * (BAR_KVFULL + (h & 1)), h >> 1, t0);
#pragma unroll 1
    for (int attempt = 0; attempt < 2; attempt++) {
      float l[4] = {0.f, 0.f, 0.f, 0.f};
      uint32_t P[16];
      {
        float S[32], F[32];
        wgmma_fence();
        wgmma_qk64(S, q.x, q.y, q.z, q.w, desc_sw64(kb + 4 * 256));
        wgmma_qk64(F, q.x, q.y, q.z, q.w, desc_sw64(kb));
        wgmma_commit();
        wgmma_wait<0>();
        for (int r = 0; r < (cmin > 0 ? 1 : 0); r++) kill32(F);
        float M[32];
#pragma unroll
        for (int i = 0; i < 32; i++) M[i] = ((i >> 2) * 8 + (i & 1) > rowc + (i & 2) * 4) ? F[i] : S[i];
        for (int r = 0; r < attempt; r++) {
          row_max(M, n0, n1);
          quad_max(n0, n1);
          n0 *= -SC; n1 *= -SC;
        }
        exp32(M, M, n0, n1, l);
        pack32(M, P);
        uint32_t PF[16];
#pragma unroll
        for (int i = 0; i < 16; i++) {
          const int col = (i >> 1) * 8, r = rowc + (i & 1) * 8;
          const uint32_t m = (col > r ? 0xFFFFu : 0u) | (col + 1 > r ? 0xFFFF0000u : 0u);
          PF[i] = P[i] & m; P[i] &= ~m;
        }
        wgmma_fence();
        pv4<true>(O, PF, kb + 2);
        wgmma_commit();
        wgmma_wait<0>();
      }
      int t = 3;
#pragma unroll 1
      for (; t >= tlo; t--) {
        float S[32];
        wgmma_fence();
        wgmma_qk64(S, q.x, q.y, q.z, q.w, desc_sw64(kb + t * 256));
        wgmma_commit();
        pv4<false>(O, P, kb + (t + 1) * 256 + 2);
        wgmma_commit();
        wgmma_wait<1>();
        ONCE { exp32(S, S, n0, n1, l); }
        wgmma_wait<0>();
        pack32(S, P);
      }
      wgmma_fence();
      pv4<false>(O, P, kb + (t + 1) * 256 + 2);
      wgmma_commit();
      l0 = l[0] + l[1]; l1 = l[2] + l[3];
      l0 += __shfl_xor_sync(0xffffffffu, l0, 1); l1 += __shfl_xor_sync(0xffffffffu, l1, 1);
      l0 += __shfl_xor_sync(0xffffffffu, l0, 2); l1 += __shfl_xor_sync(0xffffffffu, l1, 2);
      const bool redo = wg_any(aw, attempt == 0 && !(l0 > 1e-6f && l0 < 1e18f && l1 > 1e-6f && l1 < 1e18f));
      wgmma_wait<0>();
      if (!redo) break;
      n0 = NINF; n1 = NINF;
#pragma unroll 1
      for (int u = 3; u >= tlo; u--) {
        float S[32];
        wgmma_fence();
        wgmma_qk64(S, q.x, q.y, q.z, q.w, desc_sw64(kb + u * 256));
        wgmma_commit();
        wgmma_wait<0>();
        row_max(S, n0, n1);
      }
    }
    if (lane == 0) mbar_arrive(bars + 8 * (BAR_KVEMPTY + (h & 1)));
    Gate g;
    get_gate(g, sbase, aw * 4 + wi, lane, t0);
    const float c0 = __fdividef(g.g0, l0), c1 = __fdividef(g.g1, l1);
    const int mi = lane >> 3;
    const int srow = wi * 16 + (lane & 7) + 8 * (mi & 1);
    stsm_x4(qst + h * 2048 + srow * 32 + (mi >> 1) * 16, pack_bf16(O[0] * c0, O[1] * c0), pack_bf16(O[2] * c1, O[3] * c1),
            pack_bf16(O[4] * c0, O[5] * c0), pack_bf16(O[6] * c1, O[7] * c1));
    fence_async_smem();
    __syncwarp();
    if (lane == 0) mbar_arrive(bars + 8 * (BAR_OST + aw));
  }
}

template <int CH, int N>
DEVI void store_h_chunk(Acc<N>& acc, uint32_t base  , int lane, float s0, float s1) {
  const int mi = lane >> 3;
#pragma unroll
  for (int tp = 0; tp < 4; tp++) {
    const int t = CH * 8 + tp * 2;
    const uint32_t r0 = pack_bf16(fmaxf(acc[4 * t + 0], 0.f) * s0, fmaxf(acc[4 * t + 1], 0.f) * s0);
    const uint32_t r1 = pack_bf16(fmaxf(acc[4 * t + 2], 0.f) * s1, fmaxf(acc[4 * t + 3], 0.f) * s1);
    const uint32_t r2 = pack_bf16(fmaxf(acc[4 * t + 4], 0.f) * s0, fmaxf(acc[4 * t + 5], 0.f) * s0);
    const uint32_t r3 = pack_bf16(fmaxf(acc[4 * t + 6], 0.f) * s1, fmaxf(acc[4 * t + 7], 0.f) * s1);
    stsm_x4(base + (((tp * 2 + (mi >> 1)) ^ (lane & 7)) << 4), r0, r1, r2, r3);
  }
}

template <int N>
DEVI void phase_q(Ctx& c, int warp) {
  Acc<N> acc;
#pragma unroll
  for (int i = 0; i < N / 2; i++) acc[i] = 0.f;
  bare_groups<N>(acc, c, 0, 16);
  drain(c);
  const int lane = c.lane, mi = lane >> 3;
  const int row = warp * 16 + (lane & 7) + 8 * (mi & 1);
  const int sw = (row >> 1) & 3;
#pragma unroll
  for (int hh = 0; hh < 4; hh++) {
    const uint32_t base = c.sbase + OFF_KV + hh * 8192 + row * 64;
#pragma unroll
    for (int kv = 0; kv < 2; kv++) {
      const int t = 8 + kv * 8 + 2 * hh;
      stsm_x4(base + (((kv * 2 + (mi >> 1)) ^ sw) << 4),
              pack_bf16(acc[4 * t + 0], acc[4 * t + 1]), pack_bf16(acc[4 * t + 2], acc[4 * t + 3]),
              pack_bf16(acc[4 * t + 4], acc[4 * t + 5]), pack_bf16(acc[4 * t + 6], acc[4 * t + 7]));
    }
  }
  fence_async_smem();
  __syncwarp();
  if (lane == 0) mbar_arrive(c.bars + 8 * BAR_STG);
#pragma unroll
  for (int hh = 0; hh < 4; hh++)
    sts128(c.sbase + OFF_A + c.wg * 8192 + hh * 2048 + ((warp & 3) * 32 + lane) * 16,
           pack_bf16(acc[8 * hh], acc[8 * hh + 1]), pack_bf16(acc[8 * hh + 2], acc[8 * hh + 3]),
           pack_bf16(acc[8 * hh + 4], acc[8 * hh + 5]), pack_bf16(acc[8 * hh + 6], acc[8 * hh + 7]));
#pragma unroll
  for (int hh = 0; hh < 4; hh++) {
    const int q = 8 * hh, k = 32 + 8 * hh;
    float d0 = acc[q] * acc[k] + acc[q + 1] * acc[k + 1] + acc[q + 4] * acc[k + 4] + acc[q + 5] * acc[k + 5];
    float d1 = acc[q + 2] * acc[k + 2] + acc[q + 3] * acc[k + 3] + acc[q + 6] * acc[k + 6] + acc[q + 7] * acc[k + 7];
    d0 += __shfl_xor_sync(0xffffffffu, d0, 1); d1 += __shfl_xor_sync(0xffffffffu, d1, 1);
    d0 += __shfl_xor_sync(0xffffffffu, d0, 2); d1 += __shfl_xor_sync(0xffffffffu, d1, 2);
    if ((lane & 3) == hh)
      asm volatile("st.shared.u32 [%0], %1;" ::"r"(c.sbase + OFF_NM + (warp * 32 + lane) * 4), "r"(pack_bf16(-d0 * SC, -d1 * SC)) : "memory");
  }
  __syncwarp();
  if (lane == 0) mbar_arrive(c.bars + 8 * (BAR_QRDY + c.wg));
}

DEVI void first_loads(const Params& P, uint32_t sbase, int e, int j, int rb) {
  const uint32_t bars = sbase + OFF_BAR, fb = bars + 8 * (BAR_FULLB + e), fa = bars + 8 * (BAR_FULLA + 1 + e);
  mbar_expect_tx(fa, 16384);
  mbar_expect_tx(fb, 12288);
  if (e == 0) tma_load_2d(sbase + OFF_A + SLOT, &P.tmX, 0, rb * 128, fa);
#pragma unroll
  for (int r = 0; r < 2; r++) {
    tma_load_3d(sbase + OFF_B + e * SLOT + r * 8192, &P.tmWqkv, 64 * j, e * 32 + r * 16, 0, fb);
  }
  if (e == 1) tma_load_2d(sbase + OFF_A + 2 * SLOT, &P.tmX, 64, rb * 128, fa);
}

__global__ void __cluster_dims__(2, 1, 1) __launch_bounds__(640, 1) fused_kernel(const __grid_constant__ Params P) {
  extern __shared__ __align__(1024) uint8_t smem_raw[];
  const uint32_t sbase = smem_u32(smem_raw);
  const uint32_t bars = sbase + OFF_BAR;
  const int tid = threadIdx.x, warp = tid >> 5, lane = tid & 31;
  const uint32_t rank = blockIdx.x & 1, peer = rank ^ 1;
  const int j = (blockIdx.x >> 1) & 7, rb = ((blockIdx.x >> 4) << 1) | rank;
  const uint32_t t0 = clk32();

  const int typeB = j & 1;
  if (tid == 544) {
    for (int s = 0; s < NA2; s++) mbar_init(bars + 8 * (BAR_FULLA + s), 1);
    for (int s = 0; s < NB; s++) mbar_init(bars + 8 * (BAR_FULLB + s), 1);
    fence_async_smem();
  } else if (tid < 10) {
    asm volatile("prefetch.tensormap [%0];" ::"l"(&P.tmX + tid) : "memory");
  } else if (tid == 512) {
    for (int s = 0; s < NA2; s++) mbar_init(bars + 8 * (BAR_EMPTYA + s), 9);
    for (int s = 0; s < NB; s++) mbar_init(bars + 8 * (BAR_EMPTYB + s), 16);
  } else if (tid == 576) {
    for (int s = 0; s < 2; s++) { mbar_init(bars + 8 * (BAR_KVFULL + s), 1); mbar_init(bars + 8 * (BAR_KVEMPTY + s), 8); mbar_init(bars + 8 * (BAR_OST + s), 4); mbar_init(bars + 8 * (BAR_QRDY + s), 4); }
    mbar_init(bars + 8 * BAR_STG, 8); mbar_init(bars + 8 * BAR_STE, 8);
    mbar_init(bars + 8 * BAR_PIN, 1); mbar_init(bars + 8 * BAR_ATTDONE, 8); mbar_init(bars + 8 * BAR_GIN, 1);
  }
  if (tid >= 512 && lane == 0) asm volatile("fence.mbarrier_init.release.cluster;" ::: "memory");
  const unsigned ep1 = ld_relaxed(&g_epoch) + 1;
  __syncwarp();
  cluster_arrive();
  if (tid == 544) { first_loads(P, sbase, 0, j, rb); first_loads(P, sbase, 1, j, rb); }
  __syncwarp();

  const int on = 12 + 4 * typeB;
  const int xe = typeB ? 0 : 8;
  const int nb = 32 + xe + on + 4;

  if (warp < 8) {
    asm volatile("setmaxnreg.inc.sync.aligned.u32 128;");
    cluster_wait();
    const int wg = __shfl_sync(0xffffffffu, warp >> 2, 0), wi = warp & 3;
    Ctx c{sbase, bars, peer, t0, ((sbase & 0x3FFFF) + OFF_A + wg * 8192) >> 4, ((sbase & 0x3FFFF) + OFF_B) >> 4, wg, lane, 1, 0, 0u, 0u, nb - NB, 0, -1, -1};
    if (tid == 0) TR(0);
    phase_q<192>(c, warp);
    if (tid == 0) TR(2);
    const uint32_t rowoff = (warp * 16 + (lane & 7) + 8 * ((lane >> 3) & 1)) * 128;
    Gate at;
    if (!typeB) {
      Acc<64> acc;
#pragma unroll
      for (int i = 0; i < 32; i++) acc[i] = 0.f;
      bare_groups<64, SH>(acc, c, 0, 8);
      get_gate(at, sbase, warp, lane, t0);
      drain(c);
      mbar_wait(bars + 8 * (BAR_FULLA + c.ai), (c.aph >> c.ai) & 1, t0);
      store_h_chunk<0>(acc, sbase + OFF_A + c.ai * SLOT + rowoff, lane, 1.f - at.g0, 1.f - at.g1);
      fence_async_smem();
      __syncwarp();
      if (lane == 0) { mbar_arrive(bars + 8 * BAR_STE); mbar_arrive(bars + 8 * (BAR_EMPTYA + c.ai)); }
      c.aph ^= 1u << c.ai; c.ae++; c.ai = a_slot(c.ae);
    }
    {
      Acc<192> acc;
#pragma unroll
      for (int i = 0; i < 96; i++) acc[i] = 0.f;
      bare_groups<192, SH>(acc, c, 0, 16);
      get_gate(at, sbase, warp, lane, t0);
      drain(c);
      if (tid == 0) TR(1);
      const float s0 = 1.f - at.g0, s1 = 1.f - at.g1;
      const int e0 = c.ai, e1 = a_slot(c.ae + 1), e2 = a_slot(c.ae + 2);
      mbar_wait(bars + 8 * (BAR_FULLA + e0), (c.aph >> e0) & 1, t0);
      store_h_chunk<0>(acc, sbase + OFF_A + e0 * SLOT + rowoff, lane, s0, s1);
      mbar_wait(bars + 8 * (BAR_FULLA + e1), (c.aph >> e1) & 1, t0);
      store_h_chunk<1>(acc, sbase + OFF_A + e1 * SLOT + rowoff, lane, s0, s1);
      mbar_wait(bars + 8 * (BAR_FULLA + e2), (c.aph >> e2) & 1, t0);
      store_h_chunk<2>(acc, sbase + OFF_A + e2 * SLOT + rowoff, lane, s0, s1);
    }
    fence_async_smem();
    wg_bar(wg);
    if (lane == 0) mbar_arrive(bars + 8 * BAR_STG);
    if (tid == 0) TR(4);
    float own[32];
    {
      Acc<128> acc;
#pragma unroll
      for (int i = 0; i < 64; i++) acc[i] = 0.f;
      bare_groups<128, SH>(acc, c, 0, on);
      drain(c);
      if (tid == 0) TR(5);
      named_bar<3>(256);
      const uint32_t pst = sbase + OFF_B + ((nb - 6) % NB) * SLOT + wg * 8192 + (tid & 127) * 16;
#pragma unroll
      for (int i = 0; i < 4; i++) {
        uint32_t r[4];
#pragma unroll
        for (int k = 0; k < 4; k++) {
          const int idx = 8 * i + 2 * k;
          const float lo = typeB ? acc[idx] : acc[32 + idx], hi = typeB ? acc[idx + 1] : acc[32 + idx + 1];
          r[k] = pack_bf16(lo, hi);
        }
        sts128(pst + i * 2048, r[0], r[1], r[2], r[3]);
      }
#pragma unroll
      for (int i = 0; i < 32; i++) own[i] = typeB ? acc[32 + i] : acc[i];
      fence_async_smem();
      __syncwarp();
      if (lane == 0) mbar_arrive(bars + 8 * BAR_STG);
    }
    for (int g = 0; g < 8; g++) {
      const uint32_t a16 = c.a16 + c.ai * (SLOT >> 4);
      const uint32_t b16 = c.b16 + c.bi * (SLOT >> 4) + (g & 1) * 512;
      gemm_wait(c);
      wgmma_fence();
#pragma unroll
      for (int s = 0; s < 4; s++) wgmma_ss_n64(own, desc_sw128<16>(a16 + s * 2), desc_sw128<2048>(b16 + s * 128));
      wgmma_commit();
      wgmma_wait<1>();
      release_prev(c);
      c.pa = c.ai; c.aph ^= 1u << c.ai;
      c.ae++; c.ai = a_slot(c.ae);
      if (g & 1) { if (++c.bi == NB) { c.bi = 0; c.bph ^= 1; } }
    }
    wgmma_wait<0>();
    if (tid == 0) TR(6);
    mbar_wait(bars + 8 * BAR_PIN, 0, t0);
    if (tid == 0) TR(7);
    {
      const uint32_t pin = sbase + OFF_B + ((nb - 5) % NB) * SLOT + wg * 8192 + (tid & 127) * 16;
      wg_bar(wg);
      const uint32_t ob = sbase + OFF_A + SLOT + wg * 8192;
      const uint32_t orow = ob + (wi * 16 + (lane & 7) + 8 * ((lane >> 3) & 1)) * 128;
#pragma unroll
      for (int i = 0; i < 4; i++) {
        const uint4 v = lds128(pin + i * 2048);
        const uint32_t r[4] = {v.x, v.y, v.z, v.w};
        uint32_t o[4];
#pragma unroll
        for (int k = 0; k < 4; k++) {
          const int idx = 8 * i + 2 * k;
          o[k] = pack_bf16(own[idx] + __uint_as_float(r[k] << 16), own[idx + 1] + __uint_as_float(r[k] & 0xffff0000u));
        }
        stsm_x4(orow + (((i * 2 + (lane >> 4)) ^ (lane & 7)) << 4), o[0], o[1], o[2], o[3]);
      }
      fence_async_smem();
      __syncwarp();
      if (lane == 0) {
        tma_store_2d(&P.tmOut, j * 64, rb * 128 + warp * 16, ob + wi * 2048);
        bulk_commit();
        asm volatile("cp.async.bulk.wait_group.read 0;" ::: "memory");
      }
    }
    if (tid == 0) TR(8);
  } else if (warp < 16) {
    cluster_wait();
    const int aw = __shfl_sync(0xffffffffu, (warp >> 2) & 1, 0);
    {
      const int rowg = rb * 128 + j * 16 + (warp - 8) * 2;
      const uint4* gw = (const uint4*)P.gate_w;
      const uint4* xr = (const uint4*)(P.x + (size_t)rowg * DM);
      mbar_wait(bars + 8 * (BAR_FULLB + 1), 0, t0);
      const uint4 w0 = __ldg(gw + lane), w1 = __ldg(gw + 32 + lane);
      const uint4 xa0 = __ldg(xr + lane), xa1 = __ldg(xr + 32 + lane), xb0 = __ldg(xr + 64 + lane), xb1 = __ldg(xr + 96 + lane);
#pragma unroll
      for (int i = 0; i < 4; i++) sts128(sbase + OFF_KV + 32768 + i * 4096 + (tid - 256) * 16, 0u, 0u, 0u, 0u);
      const uint32_t wa[8] = {w0.x, w0.y, w0.z, w0.w, w1.x, w1.y, w1.z, w1.w};
      const uint32_t xa[8] = {xa0.x, xa0.y, xa0.z, xa0.w, xa1.x, xa1.y, xa1.z, xa1.w};
      const uint32_t xb[8] = {xb0.x, xb0.y, xb0.z, xb0.w, xb1.x, xb1.y, xb1.z, xb1.w};
      float za = 0.f, zb = 0.f;
#pragma unroll
      for (int e = 0; e < 8; e++) {
        const float wl = __uint_as_float(wa[e] << 16), wh = __uint_as_float(wa[e] & 0xffff0000u);
        za = fmaf(__uint_as_float(xa[e] << 16), wl, za); za = fmaf(__uint_as_float(xa[e] & 0xffff0000u), wh, za);
        zb = fmaf(__uint_as_float(xb[e] << 16), wl, zb); zb = fmaf(__uint_as_float(xb[e] & 0xffff0000u), wh, zb);
      }
#pragma unroll
      for (int o = 16; o > 0; o >>= 1) { za += __shfl_xor_sync(0xffffffffu, za, o); zb += __shfl_xor_sync(0xffffffffu, zb, o); }
      if (lane < 2) asm volatile("st.shared.f32 [%0], %1;" ::"r"(sbase + OFF_GST + (warp - 8) * 8 + lane * 4), "f"(1.f / (1.f + __expf(-(lane ? zb : za)))) : "memory");
      fence_async_smem();
      named_bar<6>(256);
      if (tid == 256) {
        bulk_store(&g_gate[rb * 128 + j * 16], sbase + OFF_GST, 64);
        bulk_commit(); bulk_wait_all();
        flag_add(&g_flag_g[rb * FS]);
        flag_wait(&g_flag_g[rb * FS], ep1 * 8, t0);
        fence_async_global();
        mbar_expect_tx(bars + 8 * BAR_GIN, 512);
        bulk_load(sbase + OFF_GIN, &g_gate[rb * 128], 512, bars + 8 * BAR_GIN);
        TR(10);
      }
      __syncwarp();
    }
    mbar_wait(bars + 8 * (BAR_QRDY + aw), 0, t0);
    attention(sbase, aw, warp & 3, lane, rb, t0);
    if (tid == 256) TR(3);
  } else {
    asm volatile("setmaxnreg.dec.sync.aligned.u32 32;");
    if (warp == 16) {
      __syncwarp();
      cluster_wait();
      if (lane == 0) {
        int bi = 2; uint32_t bph = 1;
        for (int eb = 2; eb < nb; eb++) {
          if (eb == 4 || eb == 6) {
            const int ea = eb >> 1;
            mbar_expect_tx(bars + 8 * (BAR_FULLA + 1 + ea), 16384);
            tma_load_2d(sbase + OFF_A + (1 + ea) * SLOT, &P.tmX, ea * 64, rb * 128, bars + 8 * (BAR_FULLA + 1 + ea));
          }
          const uint32_t fb = bars + 8 * (BAR_FULLB + bi), dst = sbase + OFF_B + bi * SLOT + rank * 8192;
          mbar_wait(bars + 8 * (BAR_EMPTYB + bi), bph, t0);
          const int e = eb < 16 ? eb : eb - xe;
          if (eb < 16) { mbar_expect_tx(fb, 12288); tma_load_3d_mc(dst, &P.tmWqkv, 64 * j, eb * 32 + rank * 16, 0, fb); }
          else if (e < 16) { mbar_expect_tx(fb, 8192); tma_load_3d_mc(dst, &P.tmW1a, 0, (eb - 16) * 64 + rank * 32, 24 + (j >> 1), fb); }
          else if (e < 32) { mbar_expect_tx(fb, 12288); tma_load_3d_mc(dst, &P.tmW1b, 0, (e - 16) * 32 + rank * 16, 3 * j, fb); }
          else if (e < 32 + on) { int ow; const int ch = oh_chunk(j, e - 32, ow); mbar_expect_tx(fb, 16384); tma_load_3d_mc(dst, &P.tmW2, 0, ch * 64 + rank * 32, (j >> 1) * 2, fb); }
          else { mbar_expect_tx(fb, 16384); tma_load_4d_mc(dst, &P.tmWo, 64 * j, 0, e - 32 - on, rank * 4, fb); }
          if (++bi == NB) { bi = 0; bph ^= 1; }
          if (eb == PFAT) {
            const int b = blockIdx.x;
            l2_prefetch((const uint8_t*)P.w1 + b * 14336, 14336);
            l2_prefetch((const uint8_t*)P.w2 + b * 14336, 14336);
            l2_prefetch((const uint8_t*)P.wo + b * 4096, 4096);
          }
        }
      }
    } else if (warp == 17) {
      cluster_wait();
      if (lane == 0) {
        for (int ea = 1; ea < 5; ea++) mbar_arrive(bars + 8 * (BAR_EMPTYA + ea));
        uint32_t aph = 0xE1;
        const int xa = typeB ? 0 : 9;
        unsigned ready = 0;
        for (int er = 4; er < 24 + on + xa; er++) {
          const int ai = a_slot(er);
          const int ea = er < 8 + xa ? (er == 16 ? 16 : er & 7) : er - xa;
          const uint32_t fb = bars + 8 * (BAR_FULLA + ai), dst = sbase + OFF_A + ai * SLOT;
          int ch = ea & 7, need = -1;
          if (ea >= 16 + on) { need = 8 + ea - 16 - on; ch = 20 + need; }
          else if (ea >= 19) ch = oh_chunk(j, ea - 16, need);
          if (need >= 0 && !((ready >> need) & 1)) {
            const unsigned* fp = need < 8 ? &g_flag_h[rb * 8 * FS] : need < 16 ? &g_flag_o[rb * 8 * FS] : &g_flag_e[rb * 8 * FS];
            const unsigned tgt = (need & 8) ? ep1 * 4 : ep1;
            do {
              unsigned v[8];
#pragma unroll
              for (int i = 0; i < 8; i++) v[i] = ld_relaxed(fp + i * FS);
#pragma unroll
              for (int i = 0; i < 8; i++) if ((int)(v[i] - tgt) >= 0) ready |= 1u << (i + (need & 24));
            } while (!((ready >> need) & 1) && clk32() - t0 < TIMEOUT);
            fence_async_global();
          }
          mbar_wait(bars + 8 * (BAR_EMPTYA + ai), (aph >> ai) & 1, t0);
          if (ea >= 16 && ea < 19) mbar_arrive(fb);
          else {
            mbar_arrive(bars + 8 * (BAR_EMPTYA + ai));
            mbar_expect_tx(fb, 16384);
            tma_load_2d(dst, ea < 16 ? &P.tmX : &P.tmHO, ch * 64, rb * 128, fb);
          }
          TR(24 + ea);
          aph ^= 1u << ai;
        }
      }
    } else {
      const int wg = warp - 18;
      cluster_wait();
      if (lane == 0 && wg == 0) {
        const uint32_t stg = bars + 8 * BAR_STG;
        mbar_wait(stg, 0, t0);
        for (int hh = 0; hh < 4; hh++) bulk_store(g_kv + ((size_t)(4 * j + hh) * SEQ + rb * 128) * 64, sbase + OFF_KV + hh * 8192, 8192);
        bulk_commit(); bulk_wait_all();
        flag_add(&g_flag_kv[(rb * 8 + j) * FS]);
        TR(21);
        if (!typeB) {
          mbar_wait(bars + 8 * BAR_STE, 0, t0);
          tma_store_2d(&P.tmHO, (24 + (j >> 1)) * 64, rb * 128, sbase + OFF_A + a_slot(16) * SLOT);
          bulk_commit(); bulk_wait_all();
          flag_add(&g_flag_e[(rb * 8 + j) * FS]);
          mbar_arrive(bars + 8 * (BAR_EMPTYA + a_slot(16)));
        }
        const int hg = typeB ? 16 : 25;
        mbar_wait(stg, 1, t0);
        for (int i = 0; i < 3; i++) tma_store_2d(&P.tmHO, (3 * j + i) * 64, rb * 128, sbase + OFF_A + a_slot(hg + i) * SLOT);
        bulk_commit(); bulk_wait_all();
        flag_add(&g_flag_h[(rb * 8 + j) * FS]);
        for (int i = 0; i < 3; i++) mbar_arrive(bars + 8 * (BAR_EMPTYA + a_slot(hg + i)));
        TR(22);
        {
          const unsigned old = atomicAdd(&g_done, 1u);
          if (old == gridDim.x - 1) { g_done = 0; *(volatile unsigned*)&g_epoch = ep1; }
        }
        mbar_wait(stg, 0, t0);
        bulk_store(g_part + (size_t)(rb * 8 + (j ^ 1)) * 16384, sbase + OFF_B + ((nb - 6) % NB) * SLOT, 16384);
        bulk_commit(); bulk_wait_all();
        flag_add(&g_flag_p[(rb * 8 + (j ^ 1)) * FS]);
        TR(23);
        flag_wait(&g_flag_p[(rb * 8 + j) * FS], ep1, t0);
        fence_async_global();
        mbar_expect_tx(bars + 8 * BAR_PIN, 16384);
        bulk_load(sbase + OFF_B + ((nb - 5) % NB) * SLOT, g_part + (size_t)(rb * 8 + j) * 16384, 16384, bars + 8 * BAR_PIN);
      } else if (lane == 0) {
        const int nblk = rb >= 2 ? 3 : rb + 1;
        const uint32_t kvbytes = nblk * 8192;
        const uint8_t* kvsrc = g_kv + ((size_t)(4 * j) * SEQ + (rb + 1 - nblk) * 128) * 64;
        const uint32_t kvdst = sbase + OFF_KV + (3 - nblk) * 8192;
        {
          const unsigned* f0 = &g_flag_kv[(rb * 8 + j) * FS];
          const unsigned* f1 = rb >= 1 ? f0 - 8 * FS : f0;
          const unsigned* f2 = rb >= 2 ? f0 - 16 * FS : f0;
          unsigned v0, v1, v2;
          do { v0 = ld_relaxed(f0); v1 = ld_relaxed(f1); v2 = ld_relaxed(f2); }
          while (((int)(v0 - ep1) < 0 || (int)(v1 - ep1) < 0 || (int)(v2 - ep1) < 0) && clk32() - t0 < TIMEOUT);
        }
        TR(11);
        mbar_wait(bars + 8 * BAR_GIN, 0, t0);
        fence_async_global();
        mbar_expect_tx(bars + 8 * BAR_KVFULL, kvbytes);
        bulk_load(kvdst, kvsrc, kvbytes, bars + 8 * BAR_KVFULL);
        mbar_expect_tx(bars + 8 * (BAR_KVFULL + 1), kvbytes);
        bulk_load(kvdst + KVBUF, kvsrc + (size_t)SEQ * 64, kvbytes, bars + 8 * (BAR_KVFULL + 1));
        for (int hh = 0; hh < 4; hh++) {
          for (int aw = 0; aw < 2; aw++) {
            mbar_wait(bars + 8 * (BAR_OST + aw), hh & 1, t0);
            tma_store_2d(&P.tmOs, DFF + hh * 128 + j * 16, rb * 128 + aw * 64, sbase + OFF_A + aw * 8192 + hh * 2048);
          }
          bulk_commit();
          if (hh < 2) {
            mbar_wait(bars + 8 * (BAR_KVEMPTY + hh), 0, t0);
            mbar_expect_tx(bars + 8 * (BAR_KVFULL + hh), kvbytes);
            bulk_load(kvdst + hh * KVBUF, kvsrc + (size_t)(hh + 2) * SEQ * 64, kvbytes, bars + 8 * (BAR_KVFULL + hh));
          }
          bulk_wait_all();
          flag_add(&g_flag_o[(rb * 8 + hh * 2 + (j >> 2)) * FS]);
          TR(12 + hh);
        }
      }
    }
  }
}

typedef CUresult (*EncodeFn)(CUtensorMap*, CUtensorMapDataType, cuuint32_t, void*, const cuuint64_t*, const cuuint64_t*, const cuuint32_t*,
                             const cuuint32_t*, CUtensorMapInterleave, CUtensorMapSwizzle, CUtensorMapL2promotion, CUtensorMapFloatOOBfill);

void make_map(EncodeFn enc, CUtensorMap* m, const void* ptr, int rank, const cuuint64_t* dims, const cuuint64_t* strides, const cuuint32_t* box,
              CUtensorMapSwizzle sw = CU_TENSOR_MAP_SWIZZLE_128B) {
  cuuint32_t es[4] = {1, 1, 1, 1};
  enc(m, CU_TENSOR_MAP_DATA_TYPE_BFLOAT16, rank, const_cast<void*>(ptr), dims, strides, box, es, CU_TENSOR_MAP_INTERLEAVE_NONE, sw,
      CU_TENSOR_MAP_L2_PROMOTION_L2_256B, CU_TENSOR_MAP_FLOAT_OOB_FILL_NONE);
}

}

extern "C" void kernel_launch(void* const* d_in, const int* in_sizes, int n_in, void* d_out, int out_size) {
  (void)in_sizes; (void)n_in; (void)out_size;
  static EncodeFn enc = nullptr;
  static void* ho_ptr = nullptr;
  if (!enc) {
    void* fn = nullptr; cudaDriverEntryPointQueryResult st;
    cudaGetDriverEntryPoint("cuTensorMapEncodeTiled", &fn, cudaEnableDefault, &st);
    enc = (EncodeFn)fn;
    cudaGetSymbolAddress(&ho_ptr, g_ho);
    cudaFuncSetAttribute(fused_kernel, cudaFuncAttributeMaxDynamicSharedMemorySize, SMEM_BYTES);
  }
  const __nv_bfloat16* x = (const __nv_bfloat16*)d_in[0];
  const __nv_bfloat16* wqkv = (const __nv_bfloat16*)d_in[1];
  const __nv_bfloat16* wo = (const __nv_bfloat16*)d_in[2];
  const __nv_bfloat16* w1 = (const __nv_bfloat16*)d_in[4];
  const __nv_bfloat16* w2 = (const __nv_bfloat16*)d_in[5];
  const __nv_bfloat16* gate_w = (const __nv_bfloat16*)d_in[6];
  Params P;
  { cuuint64_t d[2] = {DM, SEQ}, s[1] = {DM * 2}; cuuint32_t b[2] = {64, 128}; make_map(enc, &P.tmX, x, 2, d, s, b); }
  { cuuint64_t d[3] = {512, 512, 3}, s[2] = {1536 * 2, 512 * 2}; cuuint32_t b[3] = {64, 16, 3}; make_map(enc, &P.tmWqkv, wqkv, 3, d, s, b); }
  { cuuint64_t d[3] = {64, 512, 28}, s[2] = {DFF * 2, 128}; cuuint32_t b[3] = {64, 32, 1}; make_map(enc, &P.tmW1a, w1, 3, d, s, b);
    b[1] = 16; b[2] = 3; make_map(enc, &P.tmW1b, w1, 3, d, s, b); }
  { cuuint64_t d[3] = {64, DFF, 8}, s[2] = {DM * 2, 128}; cuuint32_t b[3] = {64, 32, 2}; make_map(enc, &P.tmW2, w2, 3, d, s, b); }
  { cuuint64_t d[4] = {DM, 16, 4, 8}, s[3] = {DM * 2, 16 * DM * 2, 64 * DM * 2}; cuuint32_t b[4] = {64, 16, 1, 4}; make_map(enc, &P.tmWo, wo, 4, d, s, b); }
  { cuuint64_t d[2] = {KHO, SEQ}, s[1] = {KHO * 2}; cuuint32_t b[2] = {64, 128}; make_map(enc, &P.tmHO, ho_ptr, 2, d, s, b);
    b[1] = 64; make_map(enc, &P.tmHOs, ho_ptr, 2, d, s, b);
    b[0] = 16; make_map(enc, &P.tmOs, ho_ptr, 2, d, s, b, CU_TENSOR_MAP_SWIZZLE_NONE); }
  { cuuint64_t d[2] = {DM, SEQ}, s[1] = {DM * 2}; cuuint32_t b[2] = {64, 16}; make_map(enc, &P.tmOut, d_out, 2, d, s, b); }
  P.x = x; P.gate_w = gate_w; P.w1 = w1; P.w2 = w2; P.wo = wo; P.out = (__nv_bfloat16*)d_out;
  fused_kernel<<<128, 640, SMEM_BYTES>>>(P);
}
```

```cpp
#include <cuda_runtime.h>
#include <cuda_bf16.h>
#include <cuda.h>
#include <stdint.h>

#define DEVI __device__ __forceinline__

namespace {

constexpr int SEQ = 2048, DM = 512, DFF = 1792, KHO = 2304;
constexpr int NA = 5, NB = 6, SLOT = 16384, KVBUF = 24576;
constexpr int NA2 = 8;
constexpr int OFF_B = 0, OFF_A = NB * SLOT, OFF_KV = OFF_A + NA * SLOT, OFF_BAR = OFF_KV + 2 * KVBUF;
constexpr int OFF_GST = OFF_BAR + 512;
constexpr int OFF_GIN = OFF_BAR + 1024;
constexpr int OFF_NM = OFF_BAR + 1536;
constexpr int SMEM_BYTES = OFF_BAR + 2560;
constexpr uint32_t TIMEOUT = 1u << 28;
#define WAIT_HINT_NS 20000u
#define PFAT 8
#define SH false
#define SHW 1
#define SHG 1
constexpr int FS = 8;

constexpr int BAR_FULLA = 0, BAR_EMPTYA = BAR_FULLA + NA2, BAR_FULLB = BAR_EMPTYA + NA2, BAR_EMPTYB = BAR_FULLB + NB,
              BAR_KVFULL = BAR_EMPTYB + NB, BAR_KVEMPTY = BAR_KVFULL + 2, BAR_STG = BAR_KVEMPTY + 2, BAR_PIN = BAR_STG + 2, BAR_GATE = BAR_PIN + 1, BAR_STE = BAR_GATE + 2, BAR_ATTDONE = BAR_STE + 2, BAR_GIN = BAR_ATTDONE + 1, BAR_OST = BAR_GIN + 1, BAR_QRDY = BAR_OST + 2, BAR_KVOK = BAR_QRDY + 2;

__device__ __align__(1024) uint8_t g_kv[32 * SEQ * 64];
__device__ __align__(1024) __nv_bfloat16 g_ho[SEQ * KHO];
__device__ __align__(1024) uint8_t g_part[128 * 16384];
__device__ __align__(128) float g_gate[SEQ];
__device__ unsigned g_flag_kv[128 * FS], g_flag_h[128 * FS], g_flag_o[128 * FS], g_flag_g[16 * FS], g_flag_p[128 * FS], g_flag_e[128 * FS];
__device__ unsigned g_epoch, g_done;
#define TR(i) do {} while (0)

struct Params {
  CUtensorMap tmX, tmWqkv, tmW1a, tmW1b, tmW2, tmWo, tmHO, tmHOs, tmOs, tmOut;
  const __nv_bfloat16* x;
  const __nv_bfloat16* gate_w;
  const __nv_bfloat16* w1;
  const __nv_bfloat16* w2;
  const __nv_bfloat16* wo;
  __nv_bfloat16* out;
};

DEVI uint32_t smem_u32(const void* p) { return (uint32_t)__cvta_generic_to_shared(p); }
DEVI uint32_t clk32() { uint32_t c; asm volatile("mov.u32 %0, %%clock;" : "=r"(c)); return c; }
DEVI void mbar_init(uint32_t bar, uint32_t cnt) { asm volatile("mbarrier.init.shared::cta.b64 [%0], %1;" ::"r"(bar), "r"(cnt)); }
DEVI void mbar_expect_tx(uint32_t bar, uint32_t bytes) { asm volatile("mbarrier.arrive.expect_tx.shared::cta.b64 _, [%0], %1;" ::"r"(bar), "r"(bytes) : "memory"); }
DEVI void mbar_arrive(uint32_t bar) { asm volatile("mbarrier.arrive.shared::cta.b64 _, [%0];" ::"r"(bar) : "memory"); }
DEVI void mbar_arrive_cluster(uint32_t bar, uint32_t cta) {
  asm volatile("{ .reg .b32 ra; mapa.shared::cluster.u32 ra, %0, %1; mbarrier.arrive.shared::cluster.b64 _, [ra]; }" ::"r"(bar), "r"(cta) : "memory");
}
DEVI void mbar_wait(uint32_t bar, uint32_t parity, uint32_t t0) {
  asm volatile("{ .reg .pred p; .reg .u32 c;\n"
               "mbarrier.try_wait.parity.shared::cta.b64 p, [%0], %1;\n"
               "@p bra DONE_%=;\n"
               "WAIT_%=:\n"
               "mbarrier.try_wait.parity.shared::cta.b64 p, [%0], %1, %4;\n"
               "@p bra DONE_%=;\n"
               "mov.u32 c, %%clock; sub.u32 c, c, %2; setp.lt.u32 p, c, %3;\n"
               "@p bra WAIT_%=;\n"
               "DONE_%=: }" ::"r"(bar), "r"(parity), "r"(t0), "n"(TIMEOUT), "r"(WAIT_HINT_NS) : "memory");
}
DEVI unsigned ld_relaxed(const unsigned* p) { unsigned v; asm volatile("ld.relaxed.gpu.global.u32 %0, [%1];" : "=r"(v) : "l"(p) : "memory"); return v; }
DEVI void flag_wait(const unsigned* p, unsigned target, uint32_t t0) {
  while ((int)(ld_relaxed(p) - target) < 0) { if (clk32() - t0 > TIMEOUT) break; }
}
DEVI void flag_add(unsigned* p) { asm volatile("red.relaxed.gpu.global.add.u32 [%0], 1;" ::"l"(p) : "memory"); }
DEVI void fence_async_smem() { asm volatile("fence.proxy.async.shared::cta;" ::: "memory"); }
DEVI void fence_async_global() { asm volatile("fence.proxy.async.global;" ::: "memory"); }
DEVI void tma_load_2d(uint32_t dst, const CUtensorMap* m, int c0, int c1, uint32_t bar) {
  asm volatile("cp.async.bulk.tensor.2d.shared::cluster.global.mbarrier::complete_tx::bytes [%0], [%1, {%3, %4}], [%2];" ::"r"(dst), "l"(m), "r"(bar), "r"(c0), "r"(c1) : "memory");
}
DEVI void tma_load_3d(uint32_t dst, const CUtensorMap* m, int c0, int c1, int c2, uint32_t bar) {
  asm volatile("cp.async.bulk.tensor.3d.shared::cluster.global.mbarrier::complete_tx::bytes [%0], [%1, {%3, %4, %5}], [%2];"
               ::"r"(dst), "l"(m), "r"(bar), "r"(c0), "r"(c1), "r"(c2) : "memory");
}
DEVI void tma_load_3d_mc(uint32_t dst, const CUtensorMap* m, int c0, int c1, int c2, uint32_t bar) {
  asm volatile("cp.async.bulk.tensor.3d.shared::cluster.global.mbarrier::complete_tx::bytes.multicast::cluster [%0], [%1, {%3, %4, %5}], [%2], %6;"
               ::"r"(dst), "l"(m), "r"(bar), "r"(c0), "r"(c1), "r"(c2), "h"((uint16_t)3) : "memory");
}
DEVI void tma_load_4d_mc(uint32_t dst, const CUtensorMap* m, int c0, int c1, int c2, int c3, uint32_t bar) {
  asm volatile("cp.async.bulk.tensor.4d.shared::cluster.global.mbarrier::complete_tx::bytes.multicast::cluster [%0], [%1, {%3, %4, %5, %6}], [%2], %7;"
               ::"r"(dst), "l"(m), "r"(bar), "r"(c0), "r"(c1), "r"(c2), "r"(c3), "h"((uint16_t)3) : "memory");
}
DEVI void tma_store_2d(const CUtensorMap* m, int c0, int c1, uint32_t src) {
  asm volatile("cp.async.bulk.tensor.2d.global.shared::cta.bulk_group [%0, {%1, %2}], [%3];" ::"l"(m), "r"(c0), "r"(c1), "r"(src) : "memory");
}
DEVI void bulk_store(void* dst, uint32_t src, uint32_t bytes) {
  asm volatile("cp.async.bulk.global.shared::cta.bulk_group [%0], [%1], %2;" ::"l"(dst), "r"(src), "r"(bytes) : "memory");
}
DEVI void bulk_load(uint32_t dst, const void* src, uint32_t bytes, uint32_t bar) {
  asm volatile("cp.async.bulk.shared::cluster.global.mbarrier::complete_tx::bytes [%0], [%1], %2, [%3];" ::"r"(dst), "l"(src), "r"(bytes), "r"(bar) : "memory");
}
DEVI void bulk_commit() { asm volatile("cp.async.bulk.commit_group;" ::: "memory"); }
DEVI void bulk_wait_all() { asm volatile("cp.async.bulk.wait_group 0;" ::: "memory"); }
DEVI void l2_prefetch(const void* p, uint32_t bytes) { asm volatile("cp.async.bulk.prefetch.L2.global [%0], %1;" ::"l"(p), "r"(bytes) : "memory"); }
DEVI void cluster_arrive() { asm volatile("barrier.cluster.arrive.relaxed.aligned;" ::: "memory"); }
DEVI void cluster_wait() { asm volatile("barrier.cluster.wait.aligned;" ::: "memory"); }
template <int ID> DEVI void named_bar(int n) { asm volatile("bar.sync %0, %1;" ::"n"(ID), "r"(n) : "memory"); }
DEVI void wg_bar(int wg) { if (wg == 0) named_bar<1>(128); else named_bar<2>(128); }
DEVI void wgmma_fence() { asm volatile("wgmma.fence.sync.aligned;" ::: "memory"); }
DEVI void wgmma_commit() { asm volatile("wgmma.commit_group.sync.aligned;" ::: "memory"); }
template <int N> DEVI void wgmma_wait() { asm volatile("wgmma.wait_group.sync.aligned %0;" ::"n"(N) : "memory"); }
template <uint32_t LBO> DEVI uint64_t desc_sw128(uint32_t a16) {
  return ((uint64_t)(0x40000000u | (1024 >> 4)) << 32) | (a16 + ((LBO >> 4) << 16));
}
DEVI uint64_t desc_sw64(uint32_t a16) {
  return ((uint64_t)(0x80000000u | (512 >> 4)) << 32) | (a16 + ((512 >> 4) << 16));
}
DEVI uint32_t pack_bf16(float lo, float hi) { uint32_t r; asm("cvt.rn.bf16x2.f32 %0, %1, %2;" : "=r"(r) : "f"(hi), "f"(lo)); return r; }
DEVI void stsm_x4(uint32_t addr, uint32_t r0, uint32_t r1, uint32_t r2, uint32_t r3) {
  asm volatile("stmatrix.sync.aligned.m8n8.x4.shared.b16 [%0], {%1, %2, %3, %4};" ::"r"(addr), "r"(r0), "r"(r1), "r"(r2), "r"(r3) : "memory");
}
DEVI void sts128(uint32_t addr, uint32_t r0, uint32_t r1, uint32_t r2, uint32_t r3) {
  asm volatile("st.shared.v4.b32 [%0], {%1, %2, %3, %4};" ::"r"(addr), "r"(r0), "r"(r1), "r"(r2), "r"(r3) : "memory");
}
DEVI uint4 lds128(uint32_t addr) {
  uint4 v; asm volatile("ld.shared.v4.b32 {%0, %1, %2, %3}, [%4];" : "=r"(v.x), "=r"(v.y), "=r"(v.z), "=r"(v.w) : "r"(addr) : "memory"); return v;
}
DEVI float ex2(float x) { float y; asm("ex2.approx.ftz.f32 %0, %1;" : "=f"(y) : "f"(x)); return y; }

DEVI void wgmma_ss_n64(float (&d)[32], uint64_t da, uint64_t db) {
  asm volatile("wgmma.mma_async.sync.aligned.m64n64k16.f32.bf16.bf16 {%0, %1, %2, %3, %4, %5, %6, %7, %8, %9, %10, %11, %12, %13, %14, %15, %16, %17, %18, %19, %20, %21, %22, %23, %24, %25, %26, %27, %28, %29, %30, %31}, %32, %33, 1, 1, 1, 0, 1;"
    : "+f"(d[0]), "+f"(d[1]), "+f"(d[2]), "+f"(d[3]), "+f"(d[4]), "+f"(d[5]), "+f"(d[6]), "+f"(d[7]), "+f"(d[8]), "+f"(d[9]), "+f"(d[10]), "+f"(d[11]), "+f"(d[12]), "+f"(d[13]), "+f"(d[14]), "+f"(d[15]), "+f"(d[16]), "+f"(d[17]), "+f"(d[18]), "+f"(d[19]), "+f"(d[20]), "+f"(d[21]), "+f"(d[22]), "+f"(d[23]), "+f"(d[24]), "+f"(d[25]), "+f"(d[26]), "+f"(d[27]), "+f"(d[28]), "+f"(d[29]), "+f"(d[30]), "+f"(d[31])
    : "l"(da), "l"(db));
}
DEVI void wgmma_ss_n128(float (&d)[64], uint64_t da, uint64_t db) {
  asm volatile("wgmma.mma_async.sync.aligned.m64n128k16.f32.bf16.bf16 {%0, %1, %2, %3, %4, %5, %6, %7, %8, %9, %10, %11, %12, %13, %14, %15, %16, %17, %18, %19, %20, %21, %22, %23, %24, %25, %26, %27, %28, %29, %30, %31, %32, %33, %34, %35, %36, %37, %38, %39, %40, %41, %42, %43, %44, %45, %46, %47, %48, %49, %50, %51, %52, %53, %54, %55, %56, %57, %58, %59, %60, %61, %62, %63}, %64, %65, 1, 1, 1, 0, 1;"
    : "+f"(d[0]), "+f"(d[1]), "+f"(d[2]), "+f"(d[3]), "+f"(d[4]), "+f"(d[5]), "+f"(d[6]), "+f"(d[7]), "+f"(d[8]), "+f"(d[9]), "+f"(d[10]), "+f"(d[11]), "+f"(d[12]), "+f"(d[13]), "+f"(d[14]), "+f"(d[15]), "+f"(d[16]), "+f"(d[17]), "+f"(d[18]), "+f"(d[19]), "+f"(d[20]), "+f"(d[21]), "+f"(d[22]), "+f"(d[23]), "+f"(d[24]), "+f"(d[25]), "+f"(d[26]), "+f"(d[27]), "+f"(d[28]), "+f"(d[29]), "+f"(d[30]), "+f"(d[31]), "+f"(d[32]), "+f"(d[33]), "+f"(d[34]), "+f"(d[35]), "+f"(d[36]), "+f"(d[37]), "+f"(d[38]), "+f"(d[39]), "+f"(d[40]), "+f"(d[41]), "+f"(d[42]), "+f"(d[43]), "+f"(d[44]), "+f"(d[45]), "+f"(d[46]), "+f"(d[47]), "+f"(d[48]), "+f"(d[49]), "+f"(d[50]), "+f"(d[51]), "+f"(d[52]), "+f"(d[53]), "+f"(d[54]), "+f"(d[55]), "+f"(d[56]), "+f"(d[57]), "+f"(d[58]), "+f"(d[59]), "+f"(d[60]), "+f"(d[61]), "+f"(d[62]), "+f"(d[63])
    : "l"(da), "l"(db));
}
DEVI void wgmma_qk64(float (&d)[32], uint32_t a0, uint32_t a1, uint32_t a2, uint32_t a3, uint64_t db) {
  asm volatile("wgmma.mma_async.sync.aligned.m64n64k16.f32.bf16.bf16 {%0, %1, %2, %3, %4, %5, %6, %7, %8, %9, %10, %11, %12, %13, %14, %15, %16, %17, %18, %19, %20, %21, %22, %23, %24, %25, %26, %27, %28, %29, %30, %31}, {%32, %33, %34, %35}, %36, 0, 1, 1, 0;"
    : "=f"(d[0]), "=f"(d[1]), "=f"(d[2]), "=f"(d[3]), "=f"(d[4]), "=f"(d[5]), "=f"(d[6]), "=f"(d[7]), "=f"(d[8]), "=f"(d[9]), "=f"(d[10]), "=f"(d[11]), "=f"(d[12]), "=f"(d[13]), "=f"(d[14]), "=f"(d[15]), "=f"(d[16]), "=f"(d[17]), "=f"(d[18]), "=f"(d[19]), "=f"(d[20]), "=f"(d[21]), "=f"(d[22]), "=f"(d[23]), "=f"(d[24]), "=f"(d[25]), "=f"(d[26]), "=f"(d[27]), "=f"(d[28]), "=f"(d[29]), "=f"(d[30]), "=f"(d[31])
    : "r"(a0), "r"(a1), "r"(a2), "r"(a3), "l"(db));
}
DEVI void wgmma_pv(float (&d)[8], uint32_t a0, uint32_t a1, uint32_t a2, uint32_t a3, uint64_t db) {
  asm volatile("wgmma.mma_async.sync.aligned.m64n16k16.f32.bf16.bf16 {%0, %1, %2, %3, %4, %5, %6, %7}, {%8, %9, %10, %11}, %12, 1, 1, 1, 1;"
    : "+f"(d[0]), "+f"(d[1]), "+f"(d[2]), "+f"(d[3]), "+f"(d[4]), "+f"(d[5]), "+f"(d[6]), "+f"(d[7])
    : "r"(a0), "r"(a1), "r"(a2), "r"(a3), "l"(db));
}
DEVI void wgmma_pv0(float (&d)[8], uint32_t a0, uint32_t a1, uint32_t a2, uint32_t a3, uint64_t db) {
  asm volatile("wgmma.mma_async.sync.aligned.m64n16k16.f32.bf16.bf16 {%0, %1, %2, %3, %4, %5, %6, %7}, {%8, %9, %10, %11}, %12, 0, 1, 1, 1;"
    : "=f"(d[0]), "=f"(d[1]), "=f"(d[2]), "=f"(d[3]), "=f"(d[4]), "=f"(d[5]), "=f"(d[6]), "=f"(d[7])
    : "r"(a0), "r"(a1), "r"(a2), "r"(a3), "l"(db));
}

template <int N> struct Acc { float a[64]; float b[(N - 128) / 2]; DEVI float& operator[](int i) { return i < 64 ? a[i] : b[i - 64]; } };
template <> struct Acc<128> { float a[64]; DEVI float& operator[](int i) { return a[i]; } };
template <int N> DEVI void wgmma_ss(Acc<N>& d, uint64_t da, uint64_t db) {
  wgmma_ss_n128(d.a, da, db);
  if constexpr (N == 192) wgmma_ss_n64(d.b, da, db + 256);
  if constexpr (N == 256) wgmma_ss_n128(d.b, da, db + 256);
}

DEVI int oh_chunk(int j, int i, int& need) {
  if (i >= 3 && i < 5) { const int e = (j & 1) * 2 + i - 3; need = 16 + 2 * e; return 24 + e; }
  if (i >= 5) i -= 2;
  int o, r;
  if (i >= 12) { o = (j + 5) & 7; r = i - 11; }
  else { const int g = i / 3; o = (j + 2 * g) & 7; r = i - 3 * g; }
  need = o;
  return 3 * o + r;
}

DEVI int a_slot(int e, int) { return 1 + (e & 3); }

struct Ctx {
  uint32_t sbase, bars, peer, t0, a16, b16;
  int wg, lane;
  int ai, bi; uint32_t aph, bph;
  int brem, ae;
  int pa, pb;
};

DEVI void release_prev(Ctx& c) {
  if (c.pb >= 0) {
    if (c.lane == 0) mbar_arrive(c.bars + 8 * (BAR_EMPTYB + c.pb));
    if (c.lane == 1) mbar_arrive_cluster(c.bars + 8 * (BAR_EMPTYB + c.pb), c.peer);
  }
  if (c.pa >= 0 && c.lane == 2) mbar_arrive(c.bars + 8 * (BAR_EMPTYA + c.pa));
}

DEVI void gemm_wait(Ctx& c) {
  asm volatile("{ .reg .pred p, q; .reg .u32 c;\n"
               "mbarrier.try_wait.parity.shared::cta.b64 p, [%0], %1;\n"
               "mbarrier.try_wait.parity.shared::cta.b64 q, [%2], %3;\n"
               "and.pred p, p, q;\n"
               "@p bra DONE_%=;\n"
               "WAIT_%=:\n"
               "mbarrier.try_wait.parity.shared::cta.b64 p, [%0], %1, %6;\n"
               "mbarrier.try_wait.parity.shared::cta.b64 q, [%2], %3, %6;\n"
               "and.pred p, p, q;\n"
               "@p bra DONE_%=;\n"
               "mov.u32 c, %%clock; sub.u32 c, c, %4; setp.lt.u32 p, c, %5;\n"
               "@p bra WAIT_%=;\n"
               "DONE_%=: }" ::"r"(c.bars + 8 * (BAR_FULLA + c.ai)), "r"((c.aph >> c.ai) & 1), "r"(c.bars + 8 * (BAR_FULLB + c.bi)), "r"(c.bph), "r"(c.t0),
               "n"(TIMEOUT), "r"(WAIT_HINT_NS) : "memory");
}
template <int N, bool SHALLOW>
DEVI void gemm_group(Acc<N>& acc, Ctx& c, int g, int& npa, int& npb) {
  const uint32_t a16 = c.a16 + c.ai * (SLOT >> 4);
  const uint32_t b16 = c.b16 + c.bi * (SLOT >> 4);
  bool adv;
  if constexpr (N >= 192) {
    const uint32_t a2 = a16 + (g & 1) * 4;
    wgmma_ss<N>(acc, desc_sw128<16>(a2), desc_sw128<2048>(b16));
    if (SHALLOW) { wgmma_commit(); wgmma_wait<SHW>(); }
    wgmma_ss<N>(acc, desc_sw128<16>(a2 + 2), desc_sw128<2048>(b16 + 512));
    adv = g & 1;
  } else {
#pragma unroll
    for (int s = 0; s < 4; s++) {
      wgmma_ss<N>(acc, desc_sw128<16>(a16 + s * 2), desc_sw128<4096>(b16 + (s >> 1) * 512 + (s & 1) * 128));
      if (SHALLOW && s < 3 && (SHG == 1 || s == 1)) { wgmma_commit(); wgmma_wait<SHW>(); }
    }
    adv = true;
  }
  wgmma_commit();
  npb = c.brem > 0 ? c.bi : -1;
  c.brem--;
  if (++c.bi == NB) { c.bi = 0; c.bph ^= 1; }
  npa = -1;
  if (adv) { npa = c.ai; c.aph ^= 1u << c.ai; c.ae++; c.ai = 1 + (c.ae & 3); }
}

template <int N, bool SHALLOW = false>
DEVI void bare_groups(Acc<N>& acc, Ctx& c, int g0, int g1) {
  for (int g = g0; g < g1; g++) {
    int npa, npb;
    gemm_wait(c);
    wgmma_fence();
    gemm_group<N, SHALLOW>(acc, c, g, npa, npb);
    wgmma_wait<SHALLOW ? SHW : 1>();
    release_prev(c);
    c.pa = npa; c.pb = npb;
  }
}
DEVI void drain(Ctx& c) {
  wgmma_wait<0>();
  release_prev(c);
  c.pa = c.pb = -1;
}

constexpr float SC = 0.25f * 1.4426950408889634f;

#define ONCE _Pragma("unroll 1") for (unsigned once_ = 0; once_ < gridDim.y; once_++)

struct Gate { float g0, g1; };

DEVI void kill32(float (&S)[32]) {
#pragma unroll
  for (int i = 0; i < 32; i++) S[i] = __int_as_float(0xff800000);
}
DEVI void row_max(const float (&S)[32], float& x0, float& x1) {
  float y0 = S[1], y1 = S[3];
  x0 = fmaxf(x0, S[0]); x1 = fmaxf(x1, S[2]);
#pragma unroll
  for (int n = 1; n < 8; n++) {
    x0 = fmaxf(x0, S[4 * n]); y0 = fmaxf(y0, S[4 * n + 1]); x1 = fmaxf(x1, S[4 * n + 2]); y1 = fmaxf(y1, S[4 * n + 3]);
  }
  x0 = fmaxf(x0, y0); x1 = fmaxf(x1, y1);
}
DEVI void quad_max(float& x0, float& x1) {
  x0 = fmaxf(x0, __shfl_xor_sync(0xffffffffu, x0, 1)); x1 = fmaxf(x1, __shfl_xor_sync(0xffffffffu, x1, 1));
  x0 = fmaxf(x0, __shfl_xor_sync(0xffffffffu, x0, 2)); x1 = fmaxf(x1, __shfl_xor_sync(0xffffffffu, x1, 2));
}
DEVI void exp32(const float (&S)[32], float (&E)[32], float n0, float n1, float (&l)[4]) {
#pragma unroll
  for (int i = 0; i < 32; i++) { E[i] = ex2(fmaf(S[i], SC, (i & 2) ? n1 : n0)); l[i & 3] += E[i]; }
}
DEVI void pack32(const float (&E)[32], uint32_t (&P)[16]) {
#pragma unroll
  for (int i = 0; i < 16; i++) P[i] = pack_bf16(E[2 * i], E[2 * i + 1]);
}
template <bool FIRST> DEVI void pv4(float (&O)[8], const uint32_t (&P)[16], uint32_t v16) {
  if (FIRST) wgmma_pv0(O, P[0], P[1], P[2], P[3], desc_sw64(v16)); else wgmma_pv(O, P[0], P[1], P[2], P[3], desc_sw64(v16));
#pragma unroll
  for (int k = 1; k < 4; k++) wgmma_pv(O, P[4 * k], P[4 * k + 1], P[4 * k + 2], P[4 * k + 3], desc_sw64(v16 + k * 64));
}
DEVI bool wg_any(int wg, bool v) {
  uint32_t r;
  if (wg == 0) asm volatile("{ .reg .pred p, q; setp.ne.u32 p, %1, 0; bar.red.or.pred q, 4, 128, p; selp.u32 %0, 1, 0, q; }" : "=r"(r) : "r"((uint32_t)v) : "memory");
  else asm volatile("{ .reg .pred p, q; setp.ne.u32 p, %1, 0; bar.red.or.pred q, 5, 128, p; selp.u32 %0, 1, 0, q; }" : "=r"(r) : "r"((uint32_t)v) : "memory");
  return r != 0;
}
DEVI void get_gate(Gate& g, uint32_t sbase, int row16, int lane, uint32_t t0) {
  mbar_wait(sbase + OFF_BAR + 8 * BAR_GIN, 0, t0);
  const uint32_t a = sbase + OFF_GIN + (row16 * 16 + (lane >> 2)) * 4;
  asm volatile("ld.shared.f32 %0, [%1];" : "=f"(g.g0) : "r"(a) : "memory");
  asm volatile("ld.shared.f32 %0, [%1];" : "=f"(g.g1) : "r"(a + 32) : "memory");
}

DEVI void attention(uint32_t sbase, int aw, int wi, int lane, int rb, uint32_t t0) {
  const uint32_t bars = sbase + OFF_BAR;
  const uint32_t kvb = ((sbase & 0x3FFFF) + OFF_KV + aw * 4096) >> 4;
  const int cmin = 4 - 2 * rb - aw;
  const int rowc = wi * 16 + (lane >> 2) - (lane & 3) * 2;
  const uint32_t qst = sbase + OFF_A + aw * 8192;
  const float NINF = __int_as_float(0xff800000);
  const int tlo = max(cmin, 1);
#pragma unroll 1
  for (int h = 0; h < 4; h++) {
    const uint32_t kb = kvb + (h & 1) * (KVBUF >> 4);
    const uint4 q = lds128(qst + h * 2048 + (wi * 32 + lane) * 16);
    float O[8], l0, l1;
    uint32_t nm;
    asm volatile("ld.shared.u32 %0, [%1];" : "=r"(nm) : "r"(sbase + OFF_NM + ((aw * 4 + wi) * 32 + (lane & 28) + h) * 4) : "memory");
    float n0 = __uint_as_float(nm << 16), n1 = __uint_as_float(nm & 0xffff0000u);
    mbar_wait(bars + 8 * (BAR_KVFULL + (h & 1)), h >> 1, t0);
#pragma unroll 1
    for (int attempt = 0; attempt < 2; attempt++) {
      float l[4] = {0.f, 0.f, 0.f, 0.f};
      uint32_t P[16];
      {
        float S[32], F[32];
        wgmma_fence();
        wgmma_qk64(S, q.x, q.y, q.z, q.w, desc_sw64(kb + 4 * 256));
        wgmma_qk64(F, q.x, q.y, q.z, q.w, desc_sw64(kb));
        wgmma_commit();
        wgmma_wait<0>();
        for (int r = 0; r < (cmin > 0 ? 1 : 0); r++) kill32(F);
        float M[32];
#pragma unroll
        for (int i = 0; i < 32; i++) M[i] = ((i >> 2) * 8 + (i & 1) > rowc + (i & 2) * 4) ? F[i] : S[i];
        for (int r = 0; r < attempt; r++) {
          row_max(M, n0, n1);
          quad_max(n0, n1);
          n0 *= -SC; n1 *= -SC;
        }
        exp32(M, M, n0, n1, l);
        pack32(M, P);
        uint32_t PF[16];
#pragma unroll
        for (int i = 0; i < 16; i++) {
          const int col = (i >> 1) * 8, r = rowc + (i & 1) * 8;
          const uint32_t m = (col > r ? 0xFFFFu : 0u) | (col + 1 > r ? 0xFFFF0000u : 0u);
          PF[i] = P[i] & m; P[i] &= ~m;
        }
        wgmma_fence();
        pv4<true>(O, PF, kb + 2);
        wgmma_commit();
        wgmma_wait<0>();
      }
      int t = 3;
#pragma unroll 1
      for (; t >= tlo; t--) {
        float S[32];
        wgmma_fence();
        wgmma_qk64(S, q.x, q.y, q.z, q.w, desc_sw64(kb + t * 256));
        wgmma_commit();
        pv4<false>(O, P, kb + (t + 1) * 256 + 2);
        wgmma_commit();
        wgmma_wait<1>();
        ONCE { exp32(S, S, n0, n1, l); }
        wgmma_wait<0>();
        pack32(S, P);
      }
      wgmma_fence();
      pv4<false>(O, P, kb + (t + 1) * 256 + 2);
      wgmma_commit();
      l0 = l[0] + l[1]; l1 = l[2] + l[3];
      l0 += __shfl_xor_sync(0xffffffffu, l0, 1); l1 += __shfl_xor_sync(0xffffffffu, l1, 1);
      l0 += __shfl_xor_sync(0xffffffffu, l0, 2); l1 += __shfl_xor_sync(0xffffffffu, l1, 2);
      const bool redo = wg_any(aw, attempt == 0 && !(l0 > 1e-6f && l0 < 1e18f && l1 > 1e-6f && l1 < 1e18f));
      wgmma_wait<0>();
      if (!redo) break;
      n0 = NINF; n1 = NINF;
#pragma unroll 1
      for (int u = 3; u >= tlo; u--) {
        float S[32];
        wgmma_fence();
        wgmma_qk64(S, q.x, q.y, q.z, q.w, desc_sw64(kb + u * 256));
        wgmma_commit();
        wgmma_wait<0>();
        row_max(S, n0, n1);
      }
    }
    if (lane == 0) mbar_arrive(bars + 8 * (BAR_KVEMPTY + (h & 1)));
    Gate g;
    get_gate(g, sbase, aw * 4 + wi, lane, t0);
    const float c0 = __fdividef(g.g0, l0), c1 = __fdividef(g.g1, l1);
    const int mi = lane >> 3;
    const int srow = wi * 16 + (lane & 7) + 8 * (mi & 1);
    stsm_x4(qst + h * 2048 + srow * 32 + (mi >> 1) * 16, pack_bf16(O[0] * c0, O[1] * c0), pack_bf16(O[2] * c1, O[3] * c1),
            pack_bf16(O[4] * c0, O[5] * c0), pack_bf16(O[6] * c1, O[7] * c1));
    fence_async_smem();
    __syncwarp();
    if (lane == 0) mbar_arrive(bars + 8 * (BAR_OST + aw));
  }
}

template <int CH, int N>
DEVI void store_h_chunk(Acc<N>& acc, uint32_t base  , int lane, float s0, float s1) {
  const int mi = lane >> 3;
#pragma unroll
  for (int tp = 0; tp < 4; tp++) {
    const int t = CH * 8 + tp * 2;
    const uint32_t r0 = pack_bf16(fmaxf(acc[4 * t + 0], 0.f) * s0, fmaxf(acc[4 * t + 1], 0.f) * s0);
    const uint32_t r1 = pack_bf16(fmaxf(acc[4 * t + 2], 0.f) * s1, fmaxf(acc[4 * t + 3], 0.f) * s1);
    const uint32_t r2 = pack_bf16(fmaxf(acc[4 * t + 4], 0.f) * s0, fmaxf(acc[4 * t + 5], 0.f) * s0);
    const uint32_t r3 = pack_bf16(fmaxf(acc[4 * t + 6], 0.f) * s1, fmaxf(acc[4 * t + 7], 0.f) * s1);
    stsm_x4(base + (((tp * 2 + (mi >> 1)) ^ (lane & 7)) << 4), r0, r1, r2, r3);
  }
}

template <int N>
DEVI void phase_q(Ctx& c, int warp) {
  Acc<N> acc;
#pragma unroll
  for (int i = 0; i < N / 2; i++) acc[i] = 0.f;
  bare_groups<N>(acc, c, 0, 16);
  drain(c);
  const int lane = c.lane, mi = lane >> 3;
  const int row = warp * 16 + (lane & 7) + 8 * (mi & 1);
  const int sw = (row >> 1) & 3;
#pragma unroll
  for (int hh = 0; hh < 4; hh++) {
    const uint32_t base = c.sbase + OFF_KV + hh * 8192 + row * 64;
#pragma unroll
    for (int kv = 0; kv < 2; kv++) {
      const int t = 8 + kv * 8 + 2 * hh;
      stsm_x4(base + (((kv * 2 + (mi >> 1)) ^ sw) << 4),
              pack_bf16(acc[4 * t + 0], acc[4 * t + 1]), pack_bf16(acc[4 * t + 2], acc[4 * t + 3]),
              pack_bf16(acc[4 * t + 4], acc[4 * t + 5]), pack_bf16(acc[4 * t + 6], acc[4 * t + 7]));
    }
  }
  fence_async_smem();
  __syncwarp();
  if (lane == 0) mbar_arrive(c.bars + 8 * BAR_STG);
#pragma unroll
  for (int hh = 0; hh < 4; hh++)
    sts128(c.sbase + OFF_A + c.wg * 8192 + hh * 2048 + ((warp & 3) * 32 + lane) * 16,
           pack_bf16(acc[8 * hh], acc[8 * hh + 1]), pack_bf16(acc[8 * hh + 2], acc[8 * hh + 3]),
           pack_bf16(acc[8 * hh + 4], acc[8 * hh + 5]), pack_bf16(acc[8 * hh + 6], acc[8 * hh + 7]));
#pragma unroll
  for (int hh = 0; hh < 4; hh++) {
    const int q = 8 * hh, k = 32 + 8 * hh;
    float d0 = acc[q] * acc[k] + acc[q + 1] * acc[k + 1] + acc[q + 4] * acc[k + 4] + acc[q + 5] * acc[k + 5];
    float d1 = acc[q + 2] * acc[k + 2] + acc[q + 3] * acc[k + 3] + acc[q + 6] * acc[k + 6] + acc[q + 7] * acc[k + 7];
    d0 += __shfl_xor_sync(0xffffffffu, d0, 1); d1 += __shfl_xor_sync(0xffffffffu, d1, 1);
    d0 += __shfl_xor_sync(0xffffffffu, d0, 2); d1 += __shfl_xor_sync(0xffffffffu, d1, 2);
    if ((lane & 3) == hh)
      asm volatile("st.shared.u32 [%0], %1;" ::"r"(c.sbase + OFF_NM + (warp * 32 + lane) * 4), "r"(pack_bf16(-d0 * SC, -d1 * SC)) : "memory");
  }
  __syncwarp();
  if (lane == 0) mbar_arrive(c.bars + 8 * (BAR_QRDY + c.wg));
  if constexpr (N == 256) {
    Gate g;
    get_gate(g, c.sbase, warp, lane, c.t0);
    store_h_chunk<3>(acc, c.sbase + OFF_KV + 32768 + row * 128, lane, 1.f - g.g0, 1.f - g.g1);
    fence_async_smem();
    __syncwarp();
    if (lane == 0) mbar_arrive(c.bars + 8 * BAR_STE);
  }
}

DEVI void first_loads(const Params& P, uint32_t sbase, int e, int j, int rb) {
  const uint32_t bars = sbase + OFF_BAR, fb = bars + 8 * (BAR_FULLB + e), fa = bars + 8 * (BAR_FULLA + 1 + e);
  mbar_expect_tx(fa, 16384);
  mbar_expect_tx(fb, (j & 1) ? 12288 : 16384);
  if (e == 0) tma_load_2d(sbase + OFF_A + SLOT, &P.tmX, 0, rb * 128, fa);
#pragma unroll
  for (int r = 0; r < 2; r++) {
    tma_load_3d(sbase + OFF_B + e * SLOT + r * 8192, &P.tmWqkv, 64 * j, e * 32 + r * 16, 0, fb);
    if (!(j & 1)) tma_load_3d(sbase + OFF_B + e * SLOT + r * 8192 + 6144, &P.tmW1a, 0, e * 32 + r * 16, 24 + (j >> 1), fb);
  }
  if (e == 1) tma_load_2d(sbase + OFF_A + 2 * SLOT, &P.tmX, 64, rb * 128, fa);
}

__global__ void __cluster_dims__(2, 1, 1) __launch_bounds__(640, 1) fused_kernel(const __grid_constant__ Params P) {
  extern __shared__ __align__(1024) uint8_t smem_raw[];
  const uint32_t sbase = smem_u32(smem_raw);
  const uint32_t bars = sbase + OFF_BAR;
  const int tid = threadIdx.x, warp = tid >> 5, lane = tid & 31;
  const uint32_t rank = blockIdx.x & 1, peer = rank ^ 1;
  const int j = (blockIdx.x >> 1) & 7, rb = ((blockIdx.x >> 4) << 1) | rank;
  const uint32_t t0 = clk32();

  const int typeB = j & 1;
  if (tid == 544) {
    for (int s = 0; s < NA2; s++) mbar_init(bars + 8 * (BAR_FULLA + s), 1);
    for (int s = 0; s < NB; s++) mbar_init(bars + 8 * (BAR_FULLB + s), 1);
    fence_async_smem();
  } else if (tid < 10) {
    asm volatile("prefetch.tensormap [%0];" ::"l"(&P.tmX + tid) : "memory");
  } else if (tid == 512) {
    for (int s = 0; s < NA2; s++) mbar_init(bars + 8 * (BAR_EMPTYA + s), 9);
    for (int s = 0; s < NB; s++) mbar_init(bars + 8 * (BAR_EMPTYB + s), 16);
  } else if (tid == 576) {
    for (int s = 0; s < 2; s++) { mbar_init(bars + 8 * (BAR_KVFULL + s), 1); mbar_init(bars + 8 * (BAR_KVEMPTY + s), 8); mbar_init(bars + 8 * (BAR_OST + s), 4); mbar_init(bars + 8 * (BAR_QRDY + s), 4); }
    mbar_init(bars + 8 * BAR_STG, 8); mbar_init(bars + 8 * BAR_STE, 8); mbar_init(bars + 8 * BAR_KVOK, 1);
    mbar_init(bars + 8 * BAR_PIN, 1); mbar_init(bars + 8 * BAR_ATTDONE, 8); mbar_init(bars + 8 * BAR_GIN, 1);
  }
  if (tid >= 512 && lane == 0) asm volatile("fence.mbarrier_init.release.cluster;" ::: "memory");
  const unsigned ep1 = ld_relaxed(&g_epoch) + 1;
  __syncwarp();
  cluster_arrive();
  if (tid == 544) { first_loads(P, sbase, 0, j, rb); first_loads(P, sbase, 1, j, rb); }
  __syncwarp();

  const int on = 12 + 4 * typeB;

  if (warp < 8) {
    asm volatile("setmaxnreg.inc.sync.aligned.u32 160;");
    cluster_wait();
    const int wg = __shfl_sync(0xffffffffu, warp >> 2, 0), wi = warp & 3;
    Ctx c{sbase, bars, peer, t0, ((sbase & 0x3FFFF) + OFF_A + wg * 8192) >> 4, ((sbase & 0x3FFFF) + OFF_B) >> 4, wg, lane, 1, 0, 0u, 0u, 32 + on + 4 - NB, 0, -1, -1};
    if (tid == 0) TR(0);
    if (typeB) phase_q<192>(c, warp);
    else phase_q<256>(c, warp);
    asm volatile("setmaxnreg.dec.sync.aligned.u32 128;");
    if (tid == 0) TR(2);
    {
      Acc<192> acc;
#pragma unroll
      for (int i = 0; i < 96; i++) acc[i] = 0.f;
      bare_groups<192, SH>(acc, c, 0, 16);
      Gate at;
      get_gate(at, sbase, warp, lane, t0);
      drain(c);
      if (tid == 0) TR(1);
      const uint32_t rowoff = (warp * 16 + (lane & 7) + 8 * ((lane >> 3) & 1)) * 128;
      const float s0 = 1.f - at.g0, s1 = 1.f - at.g1;
      constexpr int e0 = 1, e1 = 2, e2 = 3;
      mbar_wait(bars + 8 * (BAR_FULLA + e0), 0, t0);
      store_h_chunk<0>(acc, sbase + OFF_A + e0 * SLOT + rowoff, lane, s0, s1);
      mbar_wait(bars + 8 * (BAR_FULLA + e1), 0, t0);
      store_h_chunk<1>(acc, sbase + OFF_A + e1 * SLOT + rowoff, lane, s0, s1);
      mbar_wait(bars + 8 * (BAR_FULLA + e2), 0, t0);
      store_h_chunk<2>(acc, sbase + OFF_A + e2 * SLOT + rowoff, lane, s0, s1);
    }
    fence_async_smem();
    wg_bar(wg);
    if (lane == 0) mbar_arrive(bars + 8 * BAR_STG);
    if (tid == 0) TR(4);
    float own[32];
    {
      Acc<128> acc;
#pragma unroll
      for (int i = 0; i < 64; i++) acc[i] = 0.f;
      bare_groups<128, SH>(acc, c, 0, on);
      drain(c);
      if (tid == 0) TR(5);
      named_bar<3>(256);
      const uint32_t pst = sbase + OFF_B + ((30 + on) % NB) * SLOT + wg * 8192 + (tid & 127) * 16;
#pragma unroll
      for (int i = 0; i < 4; i++) {
        uint32_t r[4];
#pragma unroll
        for (int k = 0; k < 4; k++) {
          const int idx = 8 * i + 2 * k;
          const float lo = typeB ? acc[idx] : acc[32 + idx], hi = typeB ? acc[idx + 1] : acc[32 + idx + 1];
          r[k] = pack_bf16(lo, hi);
        }
        sts128(pst + i * 2048, r[0], r[1], r[2], r[3]);
      }
#pragma unroll
      for (int i = 0; i < 32; i++) own[i] = typeB ? acc[32 + i] : acc[i];
      fence_async_smem();
      __syncwarp();
      if (lane == 0) mbar_arrive(bars + 8 * BAR_STG);
    }
    for (int g = 0; g < 8; g++) {
      const uint32_t a16 = c.a16 + c.ai * (SLOT >> 4);
      const uint32_t b16 = c.b16 + c.bi * (SLOT >> 4) + (g & 1) * 512;
      gemm_wait(c);
      wgmma_fence();
#pragma unroll
      for (int s = 0; s < 4; s++) wgmma_ss_n64(own, desc_sw128<16>(a16 + s * 2), desc_sw128<2048>(b16 + s * 128));
      wgmma_commit();
      wgmma_wait<1>();
      release_prev(c);
      c.pa = c.ai; c.aph ^= 1u << c.ai;
      c.ae++; c.ai = a_slot(c.ae, 0);
      if (g & 1) { if (++c.bi == NB) { c.bi = 0; c.bph ^= 1; } }
    }
    wgmma_wait<0>();
    if (tid == 0) TR(6);
    mbar_wait(bars + 8 * BAR_PIN, 0, t0);
    if (tid == 0) TR(7);
    {
      const uint32_t pin = sbase + OFF_B + ((31 + on) % NB) * SLOT + wg * 8192 + (tid & 127) * 16;
      wg_bar(wg);
      const uint32_t ob = sbase + OFF_A + SLOT + wg * 8192;
      const uint32_t orow = ob + (wi * 16 + (lane & 7) + 8 * ((lane >> 3) & 1)) * 128;
#pragma unroll
      for (int i = 0; i < 4; i++) {
        const uint4 v = lds128(pin + i * 2048);
        const uint32_t r[4] = {v.x, v.y, v.z, v.w};
        uint32_t o[4];
#pragma unroll
        for (int k = 0; k < 4; k++) {
          const int idx = 8 * i + 2 * k;
          o[k] = pack_bf16(own[idx] + __uint_as_float(r[k] << 16), own[idx + 1] + __uint_as_float(r[k] & 0xffff0000u));
        }
        stsm_x4(orow + (((i * 2 + (lane >> 4)) ^ (lane & 7)) << 4), o[0], o[1], o[2], o[3]);
      }
      fence_async_smem();
      __syncwarp();
      if (lane == 0) {
        tma_store_2d(&P.tmOut, j * 64, rb * 128 + warp * 16, ob + wi * 2048);
        bulk_commit();
        asm volatile("cp.async.bulk.wait_group.read 0;" ::: "memory");
      }
    }
    if (tid == 0) TR(8);
  } else if (warp < 16) {
    asm volatile("setmaxnreg.dec.sync.aligned.u32 56;");
    cluster_wait();
    const int aw = __shfl_sync(0xffffffffu, (warp >> 2) & 1, 0);
    {
      const int rowg = rb * 128 + j * 16 + (warp - 8) * 2;
      const uint4* gw = (const uint4*)P.gate_w;
      const uint4* xr = (const uint4*)(P.x + (size_t)rowg * DM);
      mbar_wait(bars + 8 * (BAR_FULLB + 1), 0, t0);
      const uint4 w0 = __ldg(gw + lane), w1 = __ldg(gw + 32 + lane);
      const uint4 xa0 = __ldg(xr + lane), xa1 = __ldg(xr + 32 + lane), xb0 = __ldg(xr + 64 + lane), xb1 = __ldg(xr + 96 + lane);
#pragma unroll
      for (int i = 0; i < 4; i++) sts128(sbase + OFF_KV + 32768 + i * 4096 + (tid - 256) * 16, 0u, 0u, 0u, 0u);
      const uint32_t wa[8] = {w0.x, w0.y, w0.z, w0.w, w1.x, w1.y, w1.z, w1.w};
      const uint32_t xa[8] = {xa0.x, xa0.y, xa0.z, xa0.w, xa1.x, xa1.y, xa1.z, xa1.w};
      const uint32_t xb[8] = {xb0.x, xb0.y, xb0.z, xb0.w, xb1.x, xb1.y, xb1.z, xb1.w};
      float za = 0.f, zb = 0.f;
#pragma unroll
      for (int e = 0; e < 8; e++) {
        const float wl = __uint_as_float(wa[e] << 16), wh = __uint_as_float(wa[e] & 0xffff0000u);
        za = fmaf(__uint_as_float(xa[e] << 16), wl, za); za = fmaf(__uint_as_float(xa[e] & 0xffff0000u), wh, za);
        zb = fmaf(__uint_as_float(xb[e] << 16), wl, zb); zb = fmaf(__uint_as_float(xb[e] & 0xffff0000u), wh, zb);
      }
#pragma unroll
      for (int o = 16; o > 0; o >>= 1) { za += __shfl_xor_sync(0xffffffffu, za, o); zb += __shfl_xor_sync(0xffffffffu, zb, o); }
      if (lane < 2) asm volatile("st.shared.f32 [%0], %1;" ::"r"(sbase + OFF_GST + (warp - 8) * 8 + lane * 4), "f"(1.f / (1.f + __expf(-(lane ? zb : za)))) : "memory");
      fence_async_smem();
      named_bar<6>(256);
      if (tid == 256) {
        bulk_store(&g_gate[rb * 128 + j * 16], sbase + OFF_GST, 64);
        bulk_commit(); bulk_wait_all();
        flag_add(&g_flag_g[rb * FS]);
        flag_wait(&g_flag_g[rb * FS], ep1 * 8, t0);
        fence_async_global();
        mbar_expect_tx(bars + 8 * BAR_GIN, 512);
        bulk_load(sbase + OFF_GIN, &g_gate[rb * 128], 512, bars + 8 * BAR_GIN);
        TR(10);
      }
      __syncwarp();
    }
    mbar_wait(bars + 8 * (BAR_QRDY + aw), 0, t0);
    asm volatile("setmaxnreg.inc.sync.aligned.u32 96;");
    attention(sbase, aw, warp & 3, lane, rb, t0);
    if (tid == 256) TR(3);
  } else {
    asm volatile("setmaxnreg.dec.sync.aligned.u32 32;");
    if (warp == 16) {
      __syncwarp();
      cluster_wait();
      if (lane == 0) {
        int bi = 2; uint32_t bph = 1;
        const int nb = 32 + on + 4;
        for (int eb = 2; eb < nb; eb++) {
          if (eb == 4 || eb == 6) {
            const int ea = eb >> 1;
            mbar_expect_tx(bars + 8 * (BAR_FULLA + 1 + ea), 16384);
            tma_load_2d(sbase + OFF_A + (1 + ea) * SLOT, &P.tmX, ea * 64, rb * 128, bars + 8 * (BAR_FULLA + 1 + ea));
          }
          const uint32_t fb = bars + 8 * (BAR_FULLB + bi), dst = sbase + OFF_B + bi * SLOT + rank * 8192;
          mbar_wait(bars + 8 * (BAR_EMPTYB + bi), bph, t0);
          if (eb < 16) {
            mbar_expect_tx(fb, typeB ? 12288 : 16384);
            tma_load_3d_mc(dst, &P.tmWqkv, 64 * j, eb * 32 + rank * 16, 0, fb);
            if (!typeB) tma_load_3d_mc(dst + 6144, &P.tmW1a, 0, eb * 32 + rank * 16, 24 + (j >> 1), fb);
          }
          else if (eb < 32) { mbar_expect_tx(fb, 12288); tma_load_3d_mc(dst, &P.tmW1b, 0, (eb - 16) * 32 + rank * 16, 3 * j, fb); }
          else if (eb < 32 + on) { int ow; const int ch = oh_chunk(j, eb - 32, ow); mbar_expect_tx(fb, 16384); tma_load_3d_mc(dst, &P.tmW2, 0, ch * 64 + rank * 32, (j >> 1) * 2, fb); }
          else { mbar_expect_tx(fb, 16384); tma_load_4d_mc(dst, &P.tmWo, 64 * j, 0, eb - 32 - on, rank * 4, fb); }
          if (++bi == NB) { bi = 0; bph ^= 1; }
          if (eb == PFAT) {
            const int b = blockIdx.x;
            l2_prefetch((const uint8_t*)P.w1 + b * 14336, 14336);
            l2_prefetch((const uint8_t*)P.w2 + b * 14336, 14336);
            l2_prefetch((const uint8_t*)P.wo + b * 4096, 4096);
          }
        }
      }
    } else if (warp == 17) {
      cluster_wait();
      if (lane == 0) {
        for (int ea = 1; ea < 5; ea++) mbar_arrive(bars + 8 * (BAR_EMPTYA + ea));
        uint32_t aph = 0xE1;
        const int na = 16 + on + 8;
        unsigned ready = 0;
        for (int ea = 4; ea < na; ea++) {
          const int ai = a_slot(ea, 20 + on);
          const uint32_t fb = bars + 8 * (BAR_FULLA + ai), dst = sbase + OFF_A + ai * SLOT;
          int ch = ea & 7, need = -1;
          if (ea >= 16 + on) { need = 8 + ea - 16 - on; ch = 20 + need; }
          else if (ea >= 19) ch = oh_chunk(j, ea - 16, need);
          if (need >= 0 && !((ready >> need) & 1)) {
            const unsigned* fp = need < 8 ? &g_flag_h[rb * 8 * FS] : need < 16 ? &g_flag_o[rb * 8 * FS] : &g_flag_e[rb * 8 * FS];
            const unsigned tgt = (need & 8) ? ep1 * 4 : ep1;
            do {
              unsigned v[8];
#pragma unroll
              for (int i = 0; i < 8; i++) v[i] = ld_relaxed(fp + i * FS);
#pragma unroll
              for (int i = 0; i < 8; i++) if ((int)(v[i] - tgt) >= 0) ready |= 1u << (i + (need & 24));
            } while (!((ready >> need) & 1) && clk32() - t0 < TIMEOUT);
            fence_async_global();
          }
          mbar_wait(bars + 8 * (BAR_EMPTYA + ai), (aph >> ai) & 1, t0);
          if (ea >= 16 && ea < 19) mbar_arrive(fb);
          else {
            mbar_arrive(bars + 8 * (BAR_EMPTYA + ai));
            mbar_expect_tx(fb, 16384);
            tma_load_2d(dst, ea < 16 ? &P.tmX : &P.tmHO, ch * 64, rb * 128, fb);
          }
          TR(24 + ea);
          aph ^= 1u << ai;
        }
      }
    } else {
      const int wg = warp - 18;
      cluster_wait();
      if (lane == 0 && wg == 0) {
        const uint32_t stg = bars + 8 * BAR_STG;
        mbar_wait(stg, 0, t0);
        for (int hh = 0; hh < 4; hh++) bulk_store(g_kv + ((size_t)(4 * j + hh) * SEQ + rb * 128) * 64, sbase + OFF_KV + hh * 8192, 8192);
        bulk_commit(); bulk_wait_all();
        flag_add(&g_flag_kv[(rb * 8 + j) * FS]);
        TR(21);
        if (!typeB) {
          mbar_wait(bars + 8 * BAR_STE, 0, t0);
          tma_store_2d(&P.tmHO, (24 + (j >> 1)) * 64, rb * 128, sbase + OFF_KV + 32768);
          bulk_commit(); bulk_wait_all();
          flag_add(&g_flag_e[(rb * 8 + j) * FS]);
        }
        mbar_arrive(bars + 8 * BAR_KVOK);
        mbar_wait(stg, 1, t0);
        for (int i = 0; i < 3; i++) tma_store_2d(&P.tmHO, (3 * j + i) * 64, rb * 128, sbase + OFF_A + (1 + i) * SLOT);
        bulk_commit(); bulk_wait_all();
        flag_add(&g_flag_h[(rb * 8 + j) * FS]);
        for (int i = 0; i < 3; i++) mbar_arrive(bars + 8 * (BAR_EMPTYA + 1 + i));
        TR(22);
        {
          const unsigned old = atomicAdd(&g_done, 1u);
          if (old == gridDim.x - 1) { g_done = 0; *(volatile unsigned*)&g_epoch = ep1; }
        }
        mbar_wait(stg, 0, t0);
        bulk_store(g_part + (size_t)(rb * 8 + (j ^ 1)) * 16384, sbase + OFF_B + ((30 + on) % NB) * SLOT, 16384);
        bulk_commit(); bulk_wait_all();
        flag_add(&g_flag_p[(rb * 8 + (j ^ 1)) * FS]);
        TR(23);
        flag_wait(&g_flag_p[(rb * 8 + j) * FS], ep1, t0);
        fence_async_global();
        mbar_expect_tx(bars + 8 * BAR_PIN, 16384);
        bulk_load(sbase + OFF_B + ((31 + on) % NB) * SLOT, g_part + (size_t)(rb * 8 + j) * 16384, 16384, bars + 8 * BAR_PIN);
      } else if (lane == 0) {
        const int nblk = rb >= 2 ? 3 : rb + 1;
        const uint32_t kvbytes = nblk * 8192;
        const uint8_t* kvsrc = g_kv + ((size_t)(4 * j) * SEQ + (rb + 1 - nblk) * 128) * 64;
        const uint32_t kvdst = sbase + OFF_KV + (3 - nblk) * 8192;
        {
          const unsigned* f0 = &g_flag_kv[(rb * 8 + j) * FS];
          const unsigned* f1 = rb >= 1 ? f0 - 8 * FS : f0;
          const unsigned* f2 = rb >= 2 ? f0 - 16 * FS : f0;
          unsigned v0, v1, v2;
          do { v0 = ld_relaxed(f0); v1 = ld_relaxed(f1); v2 = ld_relaxed(f2); }
          while (((int)(v0 - ep1) < 0 || (int)(v1 - ep1) < 0 || (int)(v2 - ep1) < 0) && clk32() - t0 < TIMEOUT);
        }
        TR(11);
        mbar_wait(bars + 8 * BAR_GIN, 0, t0);
        fence_async_global();
        mbar_expect_tx(bars + 8 * BAR_KVFULL, kvbytes);
        bulk_load(kvdst, kvsrc, kvbytes, bars + 8 * BAR_KVFULL);
        mbar_wait(bars + 8 * BAR_KVOK, 0, t0);
        mbar_expect_tx(bars + 8 * (BAR_KVFULL + 1), kvbytes);
        bulk_load(kvdst + KVBUF, kvsrc + (size_t)SEQ * 64, kvbytes, bars + 8 * (BAR_KVFULL + 1));
        for (int hh = 0; hh < 4; hh++) {
          for (int aw = 0; aw < 2; aw++) {
            mbar_wait(bars + 8 * (BAR_OST + aw), hh & 1, t0);
            tma_store_2d(&P.tmOs, DFF + hh * 128 + j * 16, rb * 128 + aw * 64, sbase + OFF_A + aw * 8192 + hh * 2048);
          }
          bulk_commit();
          if (hh < 2) {
            mbar_wait(bars + 8 * (BAR_KVEMPTY + hh), 0, t0);
            mbar_expect_tx(bars + 8 * (BAR_KVFULL + hh), kvbytes);
            bulk_load(kvdst + hh * KVBUF, kvsrc + (size_t)(hh + 2) * SEQ * 64, kvbytes, bars + 8 * (BAR_KVFULL + hh));
          }
          bulk_wait_all();
          flag_add(&g_flag_o[(rb * 8 + hh * 2 + (j >> 2)) * FS]);
          TR(12 + hh);
        }
      }
    }
  }
}

typedef CUresult (*EncodeFn)(CUtensorMap*, CUtensorMapDataType, cuuint32_t, void*, const cuuint64_t*, const cuuint64_t*, const cuuint32_t*,
                             const cuuint32_t*, CUtensorMapInterleave, CUtensorMapSwizzle, CUtensorMapL2promotion, CUtensorMapFloatOOBfill);

void make_map(EncodeFn enc, CUtensorMap* m, const void* ptr, int rank, const cuuint64_t* dims, const cuuint64_t* strides, const cuuint32_t* box,
              CUtensorMapSwizzle sw = CU_TENSOR_MAP_SWIZZLE_128B) {
  cuuint32_t es[4] = {1, 1, 1, 1};
  enc(m, CU_TENSOR_MAP_DATA_TYPE_BFLOAT16, rank, const_cast<void*>(ptr), dims, strides, box, es, CU_TENSOR_MAP_INTERLEAVE_NONE, sw,
      CU_TENSOR_MAP_L2_PROMOTION_L2_256B, CU_TENSOR_MAP_FLOAT_OOB_FILL_NONE);
}

}

extern "C" void kernel_launch(void* const* d_in, const int* in_sizes, int n_in, void* d_out, int out_size) {
  (void)in_sizes; (void)n_in; (void)out_size;
  static EncodeFn enc = nullptr;
  static void* ho_ptr = nullptr;
  if (!enc) {
    void* fn = nullptr; cudaDriverEntryPointQueryResult st;
    cudaGetDriverEntryPoint("cuTensorMapEncodeTiled", &fn, cudaEnableDefault, &st);
    enc = (EncodeFn)fn;
    cudaGetSymbolAddress(&ho_ptr, g_ho);
    cudaFuncSetAttribute(fused_kernel, cudaFuncAttributeMaxDynamicSharedMemorySize, SMEM_BYTES);
  }
  const __nv_bfloat16* x = (const __nv_bfloat16*)d_in[0];
  const __nv_bfloat16* wqkv = (const __nv_bfloat16*)d_in[1];
  const __nv_bfloat16* wo = (const __nv_bfloat16*)d_in[2];
  const __nv_bfloat16* w1 = (const __nv_bfloat16*)d_in[4];
  const __nv_bfloat16* w2 = (const __nv_bfloat16*)d_in[5];
  const __nv_bfloat16* gate_w = (const __nv_bfloat16*)d_in[6];
  Params P;
  { cuuint64_t d[2] = {DM, SEQ}, s[1] = {DM * 2}; cuuint32_t b[2] = {64, 128}; make_map(enc, &P.tmX, x, 2, d, s, b); }
  { cuuint64_t d[3] = {512, 512, 3}, s[2] = {1536 * 2, 512 * 2}; cuuint32_t b[3] = {64, 16, 3}; make_map(enc, &P.tmWqkv, wqkv, 3, d, s, b); }
  { cuuint64_t d[3] = {64, 512, 28}, s[2] = {DFF * 2, 128}; cuuint32_t b[3] = {64, 16, 1}; make_map(enc, &P.tmW1a, w1, 3, d, s, b);
    b[2] = 3; make_map(enc, &P.tmW1b, w1, 3, d, s, b); }
  { cuuint64_t d[3] = {64, DFF, 8}, s[2] = {DM * 2, 128}; cuuint32_t b[3] = {64, 32, 2}; make_map(enc, &P.tmW2, w2, 3, d, s, b); }
  { cuuint64_t d[4] = {DM, 16, 4, 8}, s[3] = {DM * 2, 16 * DM * 2, 64 * DM * 2}; cuuint32_t b[4] = {64, 16, 1, 4}; make_map(enc, &P.tmWo, wo, 4, d, s, b); }
  { cuuint64_t d[2] = {KHO, SEQ}, s[1] = {KHO * 2}; cuuint32_t b[2] = {64, 128}; make_map(enc, &P.tmHO, ho_ptr, 2, d, s, b);
    b[1] = 64; make_map(enc, &P.tmHOs, ho_ptr, 2, d, s, b);
    b[0] = 16; make_map(enc, &P.tmOs, ho_ptr, 2, d, s, b, CU_TENSOR_MAP_SWIZZLE_NONE); }
  { cuuint64_t d[2] = {DM, SEQ}, s[1] = {DM * 2}; cuuint32_t b[2] = {64, 16}; make_map(enc, &P.tmOut, d_out, 2, d, s, b); }
  P.x = x; P.gate_w = gate_w; P.w1 = w1; P.w2 = w2; P.wo = wo; P.out = (__nv_bfloat16*)d_out;
  fused_kernel<<<128, 640, SMEM_BYTES>>>(P);
}
```

```cpp
#include <cuda_runtime.h>
#include <cuda_bf16.h>
#include <cuda.h>
#include <stdint.h>

#define DEVI __device__ __forceinline__

namespace {

constexpr int SEQ = 2048, DM = 512, DFF = 1792, KHO = 2304;
constexpr int NA = 5, NB = 6, SLOT = 16384, KVBUF = 24576;
constexpr int NA2 = 8;
constexpr int OFF_B = 0, OFF_A = NB * SLOT, OFF_KV = OFF_A + NA * SLOT, OFF_BAR = OFF_KV + 2 * KVBUF;
constexpr int OFF_GST = OFF_BAR + 512;
constexpr int OFF_GIN = OFF_BAR + 1024;
constexpr int OFF_NM = OFF_BAR + 1536;
constexpr int SMEM_BYTES = OFF_BAR + 2560;
constexpr uint32_t TIMEOUT = 1u << 28;
#define WAIT_HINT_NS 20000u
#define PFAT 8
#define SH false
#define SHW 1
#define SHG 1
constexpr int FS = 8;

constexpr int BAR_FULLA = 0, BAR_EMPTYA = BAR_FULLA + NA2, BAR_FULLB = BAR_EMPTYA + NA2, BAR_EMPTYB = BAR_FULLB + NB,
              BAR_KVFULL = BAR_EMPTYB + NB, BAR_KVEMPTY = BAR_KVFULL + 2, BAR_STG = BAR_KVEMPTY + 2, BAR_PIN = BAR_STG + 2, BAR_GATE = BAR_PIN + 1, BAR_STE = BAR_GATE + 2, BAR_ATTDONE = BAR_STE + 2, BAR_GIN = BAR_ATTDONE + 1, BAR_OST = BAR_GIN + 1, BAR_QRDY = BAR_OST + 2, BAR_KVOK = BAR_QRDY + 2;

__device__ __align__(1024) uint8_t g_kv[32 * SEQ * 64];
__device__ __align__(1024) __nv_bfloat16 g_ho[SEQ * KHO];
__device__ __align__(1024) uint8_t g_part[128 * 16384];
__device__ __align__(128) float g_gate[SEQ];
__device__ unsigned g_flag_kv[128 * FS], g_flag_h[128 * FS], g_flag_o[128 * FS], g_flag_g[16 * FS], g_flag_p[128 * FS], g_flag_e[128 * FS];
__device__ unsigned g_epoch, g_done;
#define TR(i) do {} while (0)

struct Params {
  CUtensorMap tmX, tmWqkv, tmW1a, tmW1b, tmW2, tmWo, tmHO, tmHOs, tmOs, tmOut;
  const __nv_bfloat16* x;
  const __nv_bfloat16* gate_w;
  const __nv_bfloat16* w1;
  const __nv_bfloat16* w2;
  const __nv_bfloat16* wo;
  __nv_bfloat16* out;
};

DEVI uint32_t smem_u32(const void* p) { return (uint32_t)__cvta_generic_to_shared(p); }
DEVI uint32_t clk32() { uint32_t c; asm volatile("mov.u32 %0, %%clock;" : "=r"(c)); return c; }
DEVI void mbar_init(uint32_t bar, uint32_t cnt) { asm volatile("mbarrier.init.shared::cta.b64 [%0], %1;" ::"r"(bar), "r"(cnt)); }
DEVI void mbar_expect_tx(uint32_t bar, uint32_t bytes) { asm volatile("mbarrier.arrive.expect_tx.shared::cta.b64 _, [%0], %1;" ::"r"(bar), "r"(bytes) : "memory"); }
DEVI void mbar_arrive(uint32_t bar) { asm volatile("mbarrier.arrive.shared::cta.b64 _, [%0];" ::"r"(bar) : "memory"); }
DEVI void mbar_arrive_cluster(uint32_t bar, uint32_t cta) {
  asm volatile("{ .reg .b32 ra; mapa.shared::cluster.u32 ra, %0, %1; mbarrier.arrive.shared::cluster.b64 _, [ra]; }" ::"r"(bar), "r"(cta) : "memory");
}
DEVI void mbar_wait(uint32_t bar, uint32_t parity, uint32_t t0) {
  asm volatile("{ .reg .pred p; .reg .u32 c;\n"
               "mbarrier.try_wait.parity.shared::cta.b64 p, [%0], %1;\n"
               "@p bra DONE_%=;\n"
               "WAIT_%=:\n"
               "mbarrier.try_wait.parity.shared::cta.b64 p, [%0], %1, %4;\n"
               "@p bra DONE_%=;\n"
               "mov.u32 c, %%clock; sub.u32 c, c, %2; setp.lt.u32 p, c, %3;\n"
               "@p bra WAIT_%=;\n"
               "DONE_%=: }" ::"r"(bar), "r"(parity), "r"(t0), "n"(TIMEOUT), "r"(WAIT_HINT_NS) : "memory");
}
DEVI unsigned ld_relaxed(const unsigned* p) { unsigned v; asm volatile("ld.relaxed.gpu.global.u32 %0, [%1];" : "=r"(v) : "l"(p) : "memory"); return v; }
DEVI void flag_wait(const unsigned* p, unsigned target, uint32_t t0) {
  while ((int)(ld_relaxed(p) - target) < 0) { if (clk32() - t0 > TIMEOUT) break; }
}
DEVI void flag_add(unsigned* p) { asm volatile("red.relaxed.gpu.global.add.u32 [%0], 1;" ::"l"(p) : "memory"); }
DEVI void fence_async_smem() { asm volatile("fence.proxy.async.shared::cta;" ::: "memory"); }
DEVI void fence_async_global() { asm volatile("fence.proxy.async.global;" ::: "memory"); }
DEVI void tma_load_2d(uint32_t dst, const CUtensorMap* m, int c0, int c1, uint32_t bar) {
  asm volatile("cp.async.bulk.tensor.2d.shared::cluster.global.mbarrier::complete_tx::bytes [%0], [%1, {%3, %4}], [%2];" ::"r"(dst), "l"(m), "r"(bar), "r"(c0), "r"(c1) : "memory");
}
DEVI void tma_load_3d(uint32_t dst, const CUtensorMap* m, int c0, int c1, int c2, uint32_t bar) {
  asm volatile("cp.async.bulk.tensor.3d.shared::cluster.global.mbarrier::complete_tx::bytes [%0], [%1, {%3, %4, %5}], [%2];"
               ::"r"(dst), "l"(m), "r"(bar), "r"(c0), "r"(c1), "r"(c2) : "memory");
}
DEVI void tma_load_3d_mc(uint32_t dst, const CUtensorMap* m, int c0, int c1, int c2, uint32_t bar) {
  asm volatile("cp.async.bulk.tensor.3d.shared::cluster.global.mbarrier::complete_tx::bytes.multicast::cluster [%0], [%1, {%3, %4, %5}], [%2], %6;"
               ::"r"(dst), "l"(m), "r"(bar), "r"(c0), "r"(c1), "r"(c2), "h"((uint16_t)3) : "memory");
}
DEVI void tma_load_4d_mc(uint32_t dst, const CUtensorMap* m, int c0, int c1, int c2, int c3, uint32_t bar) {
  asm volatile("cp.async.bulk.tensor.4d.shared::cluster.global.mbarrier::complete_tx::bytes.multicast::cluster [%0], [%1, {%3, %4, %5, %6}], [%2], %7;"
               ::"r"(dst), "l"(m), "r"(bar), "r"(c0), "r"(c1), "r"(c2), "r"(c3), "h"((uint16_t)3) : "memory");
}
DEVI void tma_store_2d(const CUtensorMap* m, int c0, int c1, uint32_t src) {
  asm volatile("cp.async.bulk.tensor.2d.global.shared::cta.bulk_group [%0, {%1, %2}], [%3];" ::"l"(m), "r"(c0), "r"(c1), "r"(src) : "memory");
}
DEVI void bulk_store(void* dst, uint32_t src, uint32_t bytes) {
  asm volatile("cp.async.bulk.global.shared::cta.bulk_group [%0], [%1], %2;" ::"l"(dst), "r"(src), "r"(bytes) : "memory");
}
DEVI void bulk_load(uint32_t dst, const void* src, uint32_t bytes, uint32_t bar) {
  asm volatile("cp.async.bulk.shared::cluster.global.mbarrier::complete_tx::bytes [%0], [%1], %2, [%3];" ::"r"(dst), "l"(src), "r"(bytes), "r"(bar) : "memory");
}
DEVI void bulk_commit() { asm volatile("cp.async.bulk.commit_group;" ::: "memory"); }
DEVI void bulk_wait_all() { asm volatile("cp.async.bulk.wait_group 0;" ::: "memory"); }
DEVI void l2_prefetch(const void* p, uint32_t bytes) { asm volatile("cp.async.bulk.prefetch.L2.global [%0], %1;" ::"l"(p), "r"(bytes) : "memory"); }
DEVI void cluster_arrive() { asm volatile("barrier.cluster.arrive.relaxed.aligned;" ::: "memory"); }
DEVI void cluster_wait() { asm volatile("barrier.cluster.wait.aligned;" ::: "memory"); }
template <int ID> DEVI void named_bar(int n) { asm volatile("bar.sync %0, %1;" ::"n"(ID), "r"(n) : "memory"); }
DEVI void wg_bar(int wg) { if (wg == 0) named_bar<1>(128); else named_bar<2>(128); }
DEVI void wgmma_fence() { asm volatile("wgmma.fence.sync.aligned;" ::: "memory"); }
DEVI void wgmma_commit() { asm volatile("wgmma.commit_group.sync.aligned;" ::: "memory"); }
template <int N> DEVI void wgmma_wait() { asm volatile("wgmma.wait_group.sync.aligned %0;" ::"n"(N) : "memory"); }
template <uint32_t LBO> DEVI uint64_t desc_sw128(uint32_t a16) {
  return ((uint64_t)(0x40000000u | (1024 >> 4)) << 32) | (a16 + ((LBO >> 4) << 16));
}
DEVI uint64_t desc_sw64(uint32_t a16) {
  return ((uint64_t)(0x80000000u | (512 >> 4)) << 32) | (a16 + ((512 >> 4) << 16));
}
DEVI uint32_t pack_bf16(float lo, float hi) { uint32_t r; asm("cvt.rn.bf16x2.f32 %0, %1, %2;" : "=r"(r) : "f"(hi), "f"(lo)); return r; }
DEVI void stsm_x4(uint32_t addr, uint32_t r0, uint32_t r1, uint32_t r2, uint32_t r3) {
  asm volatile("stmatrix.sync.aligned.m8n8.x4.shared.b16 [%0], {%1, %2, %3, %4};" ::"r"(addr), "r"(r0), "r"(r1), "r"(r2), "r"(r3) : "memory");
}
DEVI void sts128(uint32_t addr, uint32_t r0, uint32_t r1, uint32_t r2, uint32_t r3) {
  asm volatile("st.shared.v4.b32 [%0], {%1, %2, %3, %4};" ::"r"(addr), "r"(r0), "r"(r1), "r"(r2), "r"(r3) : "memory");
}
DEVI uint4 lds128(uint32_t addr) {
  uint4 v; asm volatile("ld.shared.v4.b32 {%0, %1, %2, %3}, [%4];" : "=r"(v.x), "=r"(v.y), "=r"(v.z), "=r"(v.w) : "r"(addr) : "memory"); return v;
}
DEVI float ex2(float x) { float y; asm("ex2.approx.ftz.f32 %0, %1;" : "=f"(y) : "f"(x)); return y; }

DEVI void wgmma_ss_n64(float (&d)[32], uint64_t da, uint64_t db) {
  asm volatile("wgmma.mma_async.sync.aligned.m64n64k16.f32.bf16.bf16 {%0, %1, %2, %3, %4, %5, %6, %7, %8, %9, %10, %11, %12, %13, %14, %15, %16, %17, %18, %19, %20, %21, %22, %23, %24, %25, %26, %27, %28, %29, %30, %31}, %32, %33, 1, 1, 1, 0, 1;"
    : "+f"(d[0]), "+f"(d[1]), "+f"(d[2]), "+f"(d[3]), "+f"(d[4]), "+f"(d[5]), "+f"(d[6]), "+f"(d[7]), "+f"(d[8]), "+f"(d[9]), "+f"(d[10]), "+f"(d[11]), "+f"(d[12]), "+f"(d[13]), "+f"(d[14]), "+f"(d[15]), "+f"(d[16]), "+f"(d[17]), "+f"(d[18]), "+f"(d[19]), "+f"(d[20]), "+f"(d[21]), "+f"(d[22]), "+f"(d[23]), "+f"(d[24]), "+f"(d[25]), "+f"(d[26]), "+f"(d[27]), "+f"(d[28]), "+f"(d[29]), "+f"(d[30]), "+f"(d[31])
    : "l"(da), "l"(db));
}
DEVI void wgmma_ss_n128(float (&d)[64], uint64_t da, uint64_t db) {
  asm volatile("wgmma.mma_async.sync.aligned.m64n128k16.f32.bf16.bf16 {%0, %1, %2, %3, %4, %5, %6, %7, %8, %9, %10, %11, %12, %13, %14, %15, %16, %17, %18, %19, %20, %21, %22, %23, %24, %25, %26, %27, %28, %29, %30, %31, %32, %33, %34, %35, %36, %37, %38, %39, %40, %41, %42, %43, %44, %45, %46, %47, %48, %49, %50, %51, %52, %53, %54, %55, %56, %57, %58, %59, %60, %61, %62, %63}, %64, %65, 1, 1, 1, 0, 1;"
    : "+f"(d[0]), "+f"(d[1]), "+f"(d[2]), "+f"(d[3]), "+f"(d[4]), "+f"(d[5]), "+f"(d[6]), "+f"(d[7]), "+f"(d[8]), "+f"(d[9]), "+f"(d[10]), "+f"(d[11]), "+f"(d[12]), "+f"(d[13]), "+f"(d[14]), "+f"(d[15]), "+f"(d[16]), "+f"(d[17]), "+f"(d[18]), "+f"(d[19]), "+f"(d[20]), "+f"(d[21]), "+f"(d[22]), "+f"(d[23]), "+f"(d[24]), "+f"(d[25]), "+f"(d[26]), "+f"(d[27]), "+f"(d[28]), "+f"(d[29]), "+f"(d[30]), "+f"(d[31]), "+f"(d[32]), "+f"(d[33]), "+f"(d[34]), "+f"(d[35]), "+f"(d[36]), "+f"(d[37]), "+f"(d[38]), "+f"(d[39]), "+f"(d[40]), "+f"(d[41]), "+f"(d[42]), "+f"(d[43]), "+f"(d[44]), "+f"(d[45]), "+f"(d[46]), "+f"(d[47]), "+f"(d[48]), "+f"(d[49]), "+f"(d[50]), "+f"(d[51]), "+f"(d[52]), "+f"(d[53]), "+f"(d[54]), "+f"(d[55]), "+f"(d[56]), "+f"(d[57]), "+f"(d[58]), "+f"(d[59]), "+f"(d[60]), "+f"(d[61]), "+f"(d[62]), "+f"(d[63])
    : "l"(da), "l"(db));
}
DEVI void wgmma_qk64(float (&d)[32], uint32_t a0, uint32_t a1, uint32_t a2, uint32_t a3, uint64_t db) {
  asm volatile("wgmma.mma_async.sync.aligned.m64n64k16.f32.bf16.bf16 {%0, %1, %2, %3, %4, %5, %6, %7, %8, %9, %10, %11, %12, %13, %14, %15, %16, %17, %18, %19, %20, %21, %22, %23, %24, %25, %26, %27, %28, %29, %30, %31}, {%32, %33, %34, %35}, %36, 0, 1, 1, 0;"
    : "=f"(d[0]), "=f"(d[1]), "=f"(d[2]), "=f"(d[3]), "=f"(d[4]), "=f"(d[5]), "=f"(d[6]), "=f"(d[7]), "=f"(d[8]), "=f"(d[9]), "=f"(d[10]), "=f"(d[11]), "=f"(d[12]), "=f"(d[13]), "=f"(d[14]), "=f"(d[15]), "=f"(d[16]), "=f"(d[17]), "=f"(d[18]), "=f"(d[19]), "=f"(d[20]), "=f"(d[21]), "=f"(d[22]), "=f"(d[23]), "=f"(d[24]), "=f"(d[25]), "=f"(d[26]), "=f"(d[27]), "=f"(d[28]), "=f"(d[29]), "=f"(d[30]), "=f"(d[31])
    : "r"(a0), "r"(a1), "r"(a2), "r"(a3), "l"(db));
}
DEVI void wgmma_pv(float (&d)[8], uint32_t a0, uint32_t a1, uint32_t a2, uint32_t a3, uint64_t db) {
  asm volatile("wgmma.mma_async.sync.aligned.m64n16k16.f32.bf16.bf16 {%0, %1, %2, %3, %4, %5, %6, %7}, {%8, %9, %10, %11}, %12, 1, 1, 1, 1;"
    : "+f"(d[0]), "+f"(d[1]), "+f"(d[2]), "+f"(d[3]), "+f"(d[4]), "+f"(d[5]), "+f"(d[6]), "+f"(d[7])
    : "r"(a0), "r"(a1), "r"(a2), "r"(a3), "l"(db));
}

DEVI void wgmma_pvp(float (&d)[8], uint32_t a0, uint32_t a1, uint32_t a2, uint32_t a3, uint64_t db, int acc) {
  asm volatile("{ .reg .pred p; setp.ne.b32 p, %13, 0;\n"
    "wgmma.mma_async.sync.aligned.m64n16k16.f32.bf16.bf16 {%0, %1, %2, %3, %4, %5, %6, %7}, {%8, %9, %10, %11}, %12, p, 1, 1, 1; }"
    : "+f"(d[0]), "+f"(d[1]), "+f"(d[2]), "+f"(d[3]), "+f"(d[4]), "+f"(d[5]), "+f"(d[6]), "+f"(d[7])
    : "r"(a0), "r"(a1), "r"(a2), "r"(a3), "l"(db), "r"(acc));
}

template <int N> struct Acc { float a[64]; float b[(N - 128) / 2]; DEVI float& operator[](int i) { return i < 64 ? a[i] : b[i - 64]; } };
template <> struct Acc<128> { float a[64]; DEVI float& operator[](int i) { return a[i]; } };
template <int N> DEVI void wgmma_ss(Acc<N>& d, uint64_t da, uint64_t db) {
  wgmma_ss_n128(d.a, da, db);
  if constexpr (N == 192) wgmma_ss_n64(d.b, da, db + 256);
  if constexpr (N == 256) wgmma_ss_n128(d.b, da, db + 256);
}

DEVI int oh_chunk(int j, int i, int& need) {
  if (i >= 3 && i < 5) { const int e = (j & 1) * 2 + i - 3; need = 16 + 2 * e; return 24 + e; }
  if (i >= 5) i -= 2;
  int o, r;
  if (i >= 12) { o = (j + 5) & 7; r = i - 11; }
  else { const int g = i / 3; o = (j + 2 * g) & 7; r = i - 3 * g; }
  need = o;
  return 3 * o + r;
}

DEVI int a_slot(int e, int) { return 1 + (e & 3); }

struct Ctx {
  uint32_t sbase, bars, peer, t0, a16, b16;
  int wg, lane;
  int ai, bi; uint32_t aph, bph;
  int brem, ae;
  int pa, pb;
};

DEVI void release_prev(Ctx& c) {
  if (c.pb >= 0) {
    if (c.lane == 0) mbar_arrive(c.bars + 8 * (BAR_EMPTYB + c.pb));
    if (c.lane == 1) mbar_arrive_cluster(c.bars + 8 * (BAR_EMPTYB + c.pb), c.peer);
  }
  if (c.pa >= 0 && c.lane == 2) mbar_arrive(c.bars + 8 * (BAR_EMPTYA + c.pa));
}

DEVI void gemm_wait(Ctx& c) {
  asm volatile("{ .reg .pred p, q; .reg .u32 c;\n"
               "mbarrier.try_wait.parity.shared::cta.b64 p, [%0], %1;\n"
               "mbarrier.try_wait.parity.shared::cta.b64 q, [%2], %3;\n"
               "and.pred p, p, q;\n"
               "@p bra DONE_%=;\n"
               "WAIT_%=:\n"
               "mbarrier.try_wait.parity.shared::cta.b64 p, [%0], %1, %6;\n"
               "mbarrier.try_wait.parity.shared::cta.b64 q, [%2], %3, %6;\n"
               "and.pred p, p, q;\n"
               "@p bra DONE_%=;\n"
               "mov.u32 c, %%clock; sub.u32 c, c, %4; setp.lt.u32 p, c, %5;\n"
               "@p bra WAIT_%=;\n"
               "DONE_%=: }" ::"r"(c.bars + 8 * (BAR_FULLA + c.ai)), "r"((c.aph >> c.ai) & 1), "r"(c.bars + 8 * (BAR_FULLB + c.bi)), "r"(c.bph), "r"(c.t0),
               "n"(TIMEOUT), "r"(WAIT_HINT_NS) : "memory");
}
template <int N, bool SHALLOW>
DEVI void gemm_group(Acc<N>& acc, Ctx& c, int g, int& npa, int& npb) {
  const uint32_t a16 = c.a16 + c.ai * (SLOT >> 4);
  const uint32_t b16 = c.b16 + c.bi * (SLOT >> 4);
  bool adv;
  if constexpr (N >= 192) {
    const uint32_t a2 = a16 + (g & 1) * 4;
    wgmma_ss<N>(acc, desc_sw128<16>(a2), desc_sw128<2048>(b16));
    if (SHALLOW) { wgmma_commit(); wgmma_wait<SHW>(); }
    wgmma_ss<N>(acc, desc_sw128<16>(a2 + 2), desc_sw128<2048>(b16 + 512));
    adv = g & 1;
  } else {
#pragma unroll
    for (int s = 0; s < 4; s++) {
      wgmma_ss<N>(acc, desc_sw128<16>(a16 + s * 2), desc_sw128<4096>(b16 + (s >> 1) * 512 + (s & 1) * 128));
      if (SHALLOW && s < 3 && (SHG == 1 || s == 1)) { wgmma_commit(); wgmma_wait<SHW>(); }
    }
    adv = true;
  }
  wgmma_commit();
  npb = c.brem > 0 ? c.bi : -1;
  c.brem--;
  if (++c.bi == NB) { c.bi = 0; c.bph ^= 1; }
  npa = -1;
  if (adv) { npa = c.ai; c.aph ^= 1u << c.ai; c.ae++; c.ai = 1 + (c.ae & 3); }
}

template <int N, bool SHALLOW = false>
DEVI void bare_groups(Acc<N>& acc, Ctx& c, int g0, int g1) {
  for (int g = g0; g < g1; g++) {
    int npa, npb;
    gemm_wait(c);
    wgmma_fence();
    gemm_group<N, SHALLOW>(acc, c, g, npa, npb);
    wgmma_wait<SHALLOW ? SHW : 1>();
    release_prev(c);
    c.pa = npa; c.pb = npb;
  }
}
DEVI void drain(Ctx& c) {
  wgmma_wait<0>();
  release_prev(c);
  c.pa = c.pb = -1;
}

constexpr float SC = 0.25f * 1.4426950408889634f;

#define ONCE _Pragma("unroll 1") for (unsigned once_ = 0; once_ < gridDim.y; once_++)

struct Gate { float g0, g1; };

DEVI void row_max(const float (&S)[32], float& x0, float& x1) {
  float y0 = S[1], y1 = S[3];
  x0 = fmaxf(x0, S[0]); x1 = fmaxf(x1, S[2]);
#pragma unroll
  for (int n = 1; n < 8; n++) {
    x0 = fmaxf(x0, S[4 * n]); y0 = fmaxf(y0, S[4 * n + 1]); x1 = fmaxf(x1, S[4 * n + 2]); y1 = fmaxf(y1, S[4 * n + 3]);
  }
  x0 = fmaxf(x0, y0); x1 = fmaxf(x1, y1);
}
DEVI void quad_max(float& x0, float& x1) {
  x0 = fmaxf(x0, __shfl_xor_sync(0xffffffffu, x0, 1)); x1 = fmaxf(x1, __shfl_xor_sync(0xffffffffu, x1, 1));
  x0 = fmaxf(x0, __shfl_xor_sync(0xffffffffu, x0, 2)); x1 = fmaxf(x1, __shfl_xor_sync(0xffffffffu, x1, 2));
}
DEVI void exp32(const float (&S)[32], float (&E)[32], float n0, float n1, float (&l)[4]) {
#pragma unroll
  for (int i = 0; i < 32; i++) { E[i] = ex2(fmaf(S[i], SC, (i & 2) ? n1 : n0)); l[i & 3] += E[i]; }
}
DEVI void pack32(const float (&E)[32], uint32_t (&P)[16]) {
#pragma unroll
  for (int i = 0; i < 16; i++) P[i] = pack_bf16(E[2 * i], E[2 * i + 1]);
}
DEVI void pv4(float (&O)[8], const uint32_t (&P)[16], uint32_t v16, int acc) {
  wgmma_pvp(O, P[0], P[1], P[2], P[3], desc_sw64(v16), acc);
#pragma unroll
  for (int k = 1; k < 4; k++) wgmma_pv(O, P[4 * k], P[4 * k + 1], P[4 * k + 2], P[4 * k + 3], desc_sw64(v16 + k * 64));
}
DEVI void mask32(float (&S)[32], int rowc, bool diag) {
#pragma unroll
  for (int i = 0; i < 32; i++)
    if (((i >> 2) * 8 + (i & 1) > rowc + (i & 2) * 4) == diag) S[i] = __int_as_float(0xff800000);
}
DEVI bool wg_any(int wg, bool v) {
  uint32_t r;
  if (wg == 0) asm volatile("{ .reg .pred p, q; setp.ne.u32 p, %1, 0; bar.red.or.pred q, 4, 128, p; selp.u32 %0, 1, 0, q; }" : "=r"(r) : "r"((uint32_t)v) : "memory");
  else asm volatile("{ .reg .pred p, q; setp.ne.u32 p, %1, 0; bar.red.or.pred q, 5, 128, p; selp.u32 %0, 1, 0, q; }" : "=r"(r) : "r"((uint32_t)v) : "memory");
  return r != 0;
}
DEVI void get_gate(Gate& g, uint32_t sbase, int row16, int lane, uint32_t t0) {
  mbar_wait(sbase + OFF_BAR + 8 * BAR_GIN, 0, t0);
  const uint32_t a = sbase + OFF_GIN + (row16 * 16 + (lane >> 2)) * 4;
  asm volatile("ld.shared.f32 %0, [%1];" : "=f"(g.g0) : "r"(a) : "memory");
  asm volatile("ld.shared.f32 %0, [%1];" : "=f"(g.g1) : "r"(a + 32) : "memory");
}

DEVI void store_o(uint32_t sbase, int aw, int wi, int lane, int h, const float (&O)[8], float l0, float l1, uint32_t t0) {
  const uint32_t bars = sbase + OFF_BAR;
  if (lane == 0) mbar_arrive(bars + 8 * (BAR_KVEMPTY + (h & 1)));
  Gate g;
  get_gate(g, sbase, aw * 4 + wi, lane, t0);
  const float c0 = __fdividef(g.g0, l0), c1 = __fdividef(g.g1, l1);
  const int mi = lane >> 3;
  const int srow = wi * 16 + (lane & 7) + 8 * (mi & 1);
  stsm_x4(sbase + OFF_A + aw * 8192 + h * 2048 + srow * 32 + (mi >> 1) * 16, pack_bf16(O[0] * c0, O[1] * c0), pack_bf16(O[2] * c1, O[3] * c1),
          pack_bf16(O[4] * c0, O[5] * c0), pack_bf16(O[6] * c1, O[7] * c1));
  fence_async_smem();
  __syncwarp();
  if (lane == 0) mbar_arrive(bars + 8 * (BAR_OST + aw));
}

DEVI void attention(uint32_t sbase, int aw, int wi, int lane, int rb, uint32_t t0) {
  const uint32_t bars = sbase + OFF_BAR;
  const uint32_t kvb = ((sbase & 0x3FFFF) + OFF_KV + aw * 4096) >> 4;
  const int tlo = max(4 - 2 * rb - aw, 0);
  const int rowc = wi * 16 + (lane >> 2) - (lane & 3) * 2;
  float O[8], lp0 = 1.f, lp1 = 1.f;
  uint32_t P[16], vprev = kvb + 4 * 256 + 2;
  int pacc = 0;
#pragma unroll
  for (int i = 0; i < 8; i++) O[i] = 0.f;
#pragma unroll
  for (int i = 0; i < 16; i++) P[i] = 0u;
#pragma unroll 1
  for (int h = 0; h < 4; h++) {
    const uint32_t kb = kvb + (h & 1) * (KVBUF >> 4);
    const uint4 q = lds128(sbase + OFF_A + aw * 8192 + h * 2048 + (wi * 32 + lane) * 16);
    uint32_t nm;
    asm volatile("ld.shared.u32 %0, [%1];" : "=r"(nm) : "r"(sbase + OFF_NM + ((aw * 4 + wi) * 32 + (lane & 28) + h) * 4) : "memory");
    float n0 = __uint_as_float(nm << 16), n1 = __uint_as_float(nm & 0xffff0000u);
    mbar_wait(bars + 8 * (BAR_KVFULL + (h & 1)), h >> 1, t0);
#pragma unroll 1
    for (int attempt = 0; attempt < 2; attempt++) {
      float l[4] = {0.f, 0.f, 0.f, 0.f};
#pragma unroll 1
      for (int t = 4; t >= tlo; t--) {
        float S[32];
        wgmma_fence();
        wgmma_qk64(S, q.x, q.y, q.z, q.w, desc_sw64(kb + t * 256));
        wgmma_commit();
        pv4(O, P, vprev, pacc);
        wgmma_commit();
        wgmma_wait<1>();
        for (int r = 0; r < ((t & 3) == 0 ? 1 : 0); r++) mask32(S, rowc, t == 4);
        ONCE { exp32(S, S, n0, n1, l); }
        wgmma_wait<0>();
        if (t == 4 && h > 0 && attempt == 0) store_o(sbase, aw, wi, lane, h - 1, O, lp0, lp1, t0);
        pack32(S, P);
        vprev = kb + t * 256 + 2;
        pacc = t != 4;
      }
      lp0 = l[0] + l[1]; lp1 = l[2] + l[3];
      lp0 += __shfl_xor_sync(0xffffffffu, lp0, 1); lp1 += __shfl_xor_sync(0xffffffffu, lp1, 1);
      lp0 += __shfl_xor_sync(0xffffffffu, lp0, 2); lp1 += __shfl_xor_sync(0xffffffffu, lp1, 2);
      if (!wg_any(aw, attempt == 0 && !(lp0 > 1e-6f && lp0 < 1e18f && lp1 > 1e-6f && lp1 < 1e18f))) break;
      n0 = __int_as_float(0xff800000); n1 = n0;
#pragma unroll 1
      for (int u = 4; u >= tlo; u--) {
        float S[32];
        wgmma_fence();
        wgmma_qk64(S, q.x, q.y, q.z, q.w, desc_sw64(kb + u * 256));
        wgmma_commit();
        wgmma_wait<0>();
        if ((u & 3) == 0) mask32(S, rowc, u == 4);
        row_max(S, n0, n1);
      }
      quad_max(n0, n1);
      n0 *= -SC; n1 *= -SC;
    }
  }
  wgmma_fence();
  pv4(O, P, vprev, pacc);
  wgmma_commit();
  wgmma_wait<0>();
  store_o(sbase, aw, wi, lane, 3, O, lp0, lp1, t0);
}

template <int CH, int N>
DEVI void store_h_chunk(Acc<N>& acc, uint32_t base  , int lane, float s0, float s1) {
  const int mi = lane >> 3;
#pragma unroll
  for (int tp = 0; tp < 4; tp++) {
    const int t = CH * 8 + tp * 2;
    const uint32_t r0 = pack_bf16(fmaxf(acc[4 * t + 0], 0.f) * s0, fmaxf(acc[4 * t + 1], 0.f) * s0);
    const uint32_t r1 = pack_bf16(fmaxf(acc[4 * t + 2], 0.f) * s1, fmaxf(acc[4 * t + 3], 0.f) * s1);
    const uint32_t r2 = pack_bf16(fmaxf(acc[4 * t + 4], 0.f) * s0, fmaxf(acc[4 * t + 5], 0.f) * s0);
    const uint32_t r3 = pack_bf16(fmaxf(acc[4 * t + 6], 0.f) * s1, fmaxf(acc[4 * t + 7], 0.f) * s1);
    stsm_x4(base + (((tp * 2 + (mi >> 1)) ^ (lane & 7)) << 4), r0, r1, r2, r3);
  }
}

template <int N>
DEVI void phase_q(Ctx& c, int warp) {
  Acc<N> acc;
#pragma unroll
  for (int i = 0; i < N / 2; i++) acc[i] = 0.f;
  bare_groups<N>(acc, c, 0, 16);
  drain(c);
  const int lane = c.lane, mi = lane >> 3;
  const int row = warp * 16 + (lane & 7) + 8 * (mi & 1);
  const int sw = (row >> 1) & 3;
#pragma unroll
  for (int hh = 0; hh < 4; hh++) {
    const uint32_t base = c.sbase + OFF_KV + hh * 8192 + row * 64;
#pragma unroll
    for (int kv = 0; kv < 2; kv++) {
      const int t = 8 + kv * 8 + 2 * hh;
      stsm_x4(base + (((kv * 2 + (mi >> 1)) ^ sw) << 4),
              pack_bf16(acc[4 * t + 0], acc[4 * t + 1]), pack_bf16(acc[4 * t + 2], acc[4 * t + 3]),
              pack_bf16(acc[4 * t + 4], acc[4 * t + 5]), pack_bf16(acc[4 * t + 6], acc[4 * t + 7]));
    }
  }
  fence_async_smem();
  __syncwarp();
  if (lane == 0) mbar_arrive(c.bars + 8 * BAR_STG);
#pragma unroll
  for (int hh = 0; hh < 4; hh++)
    sts128(c.sbase + OFF_A + c.wg * 8192 + hh * 2048 + ((warp & 3) * 32 + lane) * 16,
           pack_bf16(acc[8 * hh], acc[8 * hh + 1]), pack_bf16(acc[8 * hh + 2], acc[8 * hh + 3]),
           pack_bf16(acc[8 * hh + 4], acc[8 * hh + 5]), pack_bf16(acc[8 * hh + 6], acc[8 * hh + 7]));
#pragma unroll
  for (int hh = 0; hh < 4; hh++) {
    const int q = 8 * hh, k = 32 + 8 * hh;
    float d0 = acc[q] * acc[k] + acc[q + 1] * acc[k + 1] + acc[q + 4] * acc[k + 4] + acc[q + 5] * acc[k + 5];
    float d1 = acc[q + 2] * acc[k + 2] + acc[q + 3] * acc[k + 3] + acc[q + 6] * acc[k + 6] + acc[q + 7] * acc[k + 7];
    d0 += __shfl_xor_sync(0xffffffffu, d0, 1); d1 += __shfl_xor_sync(0xffffffffu, d1, 1);
    d0 += __shfl_xor_sync(0xffffffffu, d0, 2); d1 += __shfl_xor_sync(0xffffffffu, d1, 2);
    if ((lane & 3) == hh)
      asm volatile("st.shared.u32 [%0], %1;" ::"r"(c.sbase + OFF_NM + (warp * 32 + lane) * 4), "r"(pack_bf16(-d0 * SC, -d1 * SC)) : "memory");
  }
  __syncwarp();
  if (lane == 0) mbar_arrive(c.bars + 8 * (BAR_QRDY + c.wg));
  if constexpr (N == 256) {
    Gate g;
    get_gate(g, c.sbase, warp, lane, c.t0);
    store_h_chunk<3>(acc, c.sbase + OFF_KV + 32768 + row * 128, lane, 1.f - g.g0, 1.f - g.g1);
    fence_async_smem();
    __syncwarp();
    if (lane == 0) mbar_arrive(c.bars + 8 * BAR_STE);
  }
}

DEVI void first_loads(const Params& P, uint32_t sbase, int e, int j, int rb) {
  const uint32_t bars = sbase + OFF_BAR, fb = bars + 8 * (BAR_FULLB + e), fa = bars + 8 * (BAR_FULLA + 1 + e);
  mbar_expect_tx(fa, 16384);
  mbar_expect_tx(fb, (j & 1) ? 12288 : 16384);
  if (e == 0) tma_load_2d(sbase + OFF_A + SLOT, &P.tmX, 0, rb * 128, fa);
#pragma unroll
  for (int r = 0; r < 2; r++) {
    tma_load_3d(sbase + OFF_B + e * SLOT + r * 8192, &P.tmWqkv, 64 * j, e * 32 + r * 16, 0, fb);
    if (!(j & 1)) tma_load_3d(sbase + OFF_B + e * SLOT + r * 8192 + 6144, &P.tmW1a, 0, e * 32 + r * 16, 24 + (j >> 1), fb);
  }
  if (e == 1) tma_load_2d(sbase + OFF_A + 2 * SLOT, &P.tmX, 64, rb * 128, fa);
}

__global__ void __cluster_dims__(2, 1, 1) __launch_bounds__(640, 1) fused_kernel(const __grid_constant__ Params P) {
  extern __shared__ __align__(1024) uint8_t smem_raw[];
  const uint32_t sbase = smem_u32(smem_raw);
  const uint32_t bars = sbase + OFF_BAR;
  const int tid = threadIdx.x, warp = tid >> 5, lane = tid & 31;
  const uint32_t rank = blockIdx.x & 1, peer = rank ^ 1;
  const int j = (blockIdx.x >> 1) & 7, rb = ((blockIdx.x >> 4) << 1) | rank;
  const uint32_t t0 = clk32();

  const int typeB = j & 1;
  if (tid == 544) {
    for (int s = 0; s < NA2; s++) mbar_init(bars + 8 * (BAR_FULLA + s), 1);
    for (int s = 0; s < NB; s++) mbar_init(bars + 8 * (BAR_FULLB + s), 1);
    fence_async_smem();
  } else if (tid < 10) {
    asm volatile("prefetch.tensormap [%0];" ::"l"(&P.tmX + tid) : "memory");
  } else if (tid == 512) {
    for (int s = 0; s < NA2; s++) mbar_init(bars + 8 * (BAR_EMPTYA + s), 9);
    for (int s = 0; s < NB; s++) mbar_init(bars + 8 * (BAR_EMPTYB + s), 16);
  } else if (tid == 576) {
    for (int s = 0; s < 2; s++) { mbar_init(bars + 8 * (BAR_KVFULL + s), 1); mbar_init(bars + 8 * (BAR_KVEMPTY + s), 8); mbar_init(bars + 8 * (BAR_OST + s), 4); mbar_init(bars + 8 * (BAR_QRDY + s), 4); }
    mbar_init(bars + 8 * BAR_STG, 8); mbar_init(bars + 8 * BAR_STE, 8); mbar_init(bars + 8 * BAR_KVOK, 1);
    mbar_init(bars + 8 * BAR_PIN, 1); mbar_init(bars + 8 * BAR_ATTDONE, 8); mbar_init(bars + 8 * BAR_GIN, 1);
  }
  if (tid >= 512 && lane == 0) asm volatile("fence.mbarrier_init.release.cluster;" ::: "memory");
  const unsigned ep1 = ld_relaxed(&g_epoch) + 1;
  __syncwarp();
  cluster_arrive();
  if (tid == 544) { first_loads(P, sbase, 0, j, rb); first_loads(P, sbase, 1, j, rb); }
  __syncwarp();

  const int on = 12 + 4 * typeB;

  if (warp < 8) {
    asm volatile("setmaxnreg.inc.sync.aligned.u32 160;");
    cluster_wait();
    const int wg = __shfl_sync(0xffffffffu, warp >> 2, 0), wi = warp & 3;
    Ctx c{sbase, bars, peer, t0, ((sbase & 0x3FFFF) + OFF_A + wg * 8192) >> 4, ((sbase & 0x3FFFF) + OFF_B) >> 4, wg, lane, 1, 0, 0u, 0u, 32 + on + 4 - NB, 0, -1, -1};
    if (tid == 0) TR(0);
    if (typeB) phase_q<192>(c, warp);
    else phase_q<256>(c, warp);
    asm volatile("setmaxnreg.dec.sync.aligned.u32 128;");
    if (tid == 0) TR(2);
    {
      Acc<192> acc;
#pragma unroll
      for (int i = 0; i < 96; i++) acc[i] = 0.f;
      bare_groups<192, SH>(acc, c, 0, 16);
      Gate at;
      get_gate(at, sbase, warp, lane, t0);
      drain(c);
      if (tid == 0) TR(1);
      const uint32_t rowoff = (warp * 16 + (lane & 7) + 8 * ((lane >> 3) & 1)) * 128;
      const float s0 = 1.f - at.g0, s1 = 1.f - at.g1;
      constexpr int e0 = 1, e1 = 2, e2 = 3;
      mbar_wait(bars + 8 * (BAR_FULLA + e0), 0, t0);
      store_h_chunk<0>(acc, sbase + OFF_A + e0 * SLOT + rowoff, lane, s0, s1);
      mbar_wait(bars + 8 * (BAR_FULLA + e1), 0, t0);
      store_h_chunk<1>(acc, sbase + OFF_A + e1 * SLOT + rowoff, lane, s0, s1);
      mbar_wait(bars + 8 * (BAR_FULLA + e2), 0, t0);
      store_h_chunk<2>(acc, sbase + OFF_A + e2 * SLOT + rowoff, lane, s0, s1);
    }
    fence_async_smem();
    wg_bar(wg);
    if (lane == 0) mbar_arrive(bars + 8 * BAR_STG);
    if (tid == 0) TR(4);
    float own[32];
    {
      Acc<128> acc;
#pragma unroll
      for (int i = 0; i < 64; i++) acc[i] = 0.f;
      bare_groups<128, SH>(acc, c, 0, on);
      drain(c);
      if (tid == 0) TR(5);
      named_bar<3>(256);
      const uint32_t pst = sbase + OFF_B + ((30 + on) % NB) * SLOT + wg * 8192 + (tid & 127) * 16;
#pragma unroll
      for (int i = 0; i < 4; i++) {
        uint32_t r[4];
#pragma unroll
        for (int k = 0; k < 4; k++) {
          const int idx = 8 * i + 2 * k;
          const float lo = typeB ? acc[idx] : acc[32 + idx], hi = typeB ? acc[idx + 1] : acc[32 + idx + 1];
          r[k] = pack_bf16(lo, hi);
        }
        sts128(pst + i * 2048, r[0], r[1], r[2], r[3]);
      }
#pragma unroll
      for (int i = 0; i < 32; i++) own[i] = typeB ? acc[32 + i] : acc[i];
      fence_async_smem();
      __syncwarp();
      if (lane == 0) mbar_arrive(bars + 8 * BAR_STG);
    }
    for (int g = 0; g < 8; g++) {
      const uint32_t a16 = c.a16 + c.ai * (SLOT >> 4);
      const uint32_t b16 = c.b16 + c.bi * (SLOT >> 4) + (g & 1) * 512;
      gemm_wait(c);
      wgmma_fence();
#pragma unroll
      for (int s = 0; s < 4; s++) wgmma_ss_n64(own, desc_sw128<16>(a16 + s * 2), desc_sw128<2048>(b16 + s * 128));
      wgmma_commit();
      wgmma_wait<1>();
      release_prev(c);
      c.pa = c.ai; c.aph ^= 1u << c.ai;
      c.ae++; c.ai = a_slot(c.ae, 0);
      if (g & 1) { if (++c.bi == NB) { c.bi = 0; c.bph ^= 1; } }
    }
    wgmma_wait<0>();
    if (tid == 0) TR(6);
    mbar_wait(bars + 8 * BAR_PIN, 0, t0);
    if (tid == 0) TR(7);
    {
      const uint32_t pin = sbase + OFF_B + ((31 + on) % NB) * SLOT + wg * 8192 + (tid & 127) * 16;
      wg_bar(wg);
      const uint32_t ob = sbase + OFF_A + SLOT + wg * 8192;
      const uint32_t orow = ob + (wi * 16 + (lane & 7) + 8 * ((lane >> 3) & 1)) * 128;
#pragma unroll
      for (int i = 0; i < 4; i++) {
        const uint4 v = lds128(pin + i * 2048);
        const uint32_t r[4] = {v.x, v.y, v.z, v.w};
        uint32_t o[4];
#pragma unroll
        for (int k = 0; k < 4; k++) {
          const int idx = 8 * i + 2 * k;
          o[k] = pack_bf16(own[idx] + __uint_as_float(r[k] << 16), own[idx + 1] + __uint_as_float(r[k] & 0xffff0000u));
        }
        stsm_x4(orow + (((i * 2 + (lane >> 4)) ^ (lane & 7)) << 4), o[0], o[1], o[2], o[3]);
      }
      fence_async_smem();
      __syncwarp();
      if (lane == 0) {
        tma_store_2d(&P.tmOut, j * 64, rb * 128 + warp * 16, ob + wi * 2048);
        bulk_commit();
        asm volatile("cp.async.bulk.wait_group.read 0;" ::: "memory");
      }
    }
    if (tid == 0) TR(8);
  } else if (warp < 16) {
    asm volatile("setmaxnreg.dec.sync.aligned.u32 56;");
    cluster_wait();
    const int aw = __shfl_sync(0xffffffffu, (warp >> 2) & 1, 0);
    {
      const int rowg = rb * 128 + j * 16 + (warp - 8) * 2;
      const uint4* gw = (const uint4*)P.gate_w;
      const uint4* xr = (const uint4*)(P.x + (size_t)rowg * DM);
      mbar_wait(bars + 8 * (BAR_FULLB + 1), 0, t0);
      const uint4 w0 = __ldg(gw + lane), w1 = __ldg(gw + 32 + lane);
      const uint4 xa0 = __ldg(xr + lane), xa1 = __ldg(xr + 32 + lane), xb0 = __ldg(xr + 64 + lane), xb1 = __ldg(xr + 96 + lane);
      const uint32_t wa[8] = {w0.x, w0.y, w0.z, w0.w, w1.x, w1.y, w1.z, w1.w};
      const uint32_t xa[8] = {xa0.x, xa0.y, xa0.z, xa0.w, xa1.x, xa1.y, xa1.z, xa1.w};
      const uint32_t xb[8] = {xb0.x, xb0.y, xb0.z, xb0.w, xb1.x, xb1.y, xb1.z, xb1.w};
      float za = 0.f, zb = 0.f;
#pragma unroll
      for (int e = 0; e < 8; e++) {
        const float wl = __uint_as_float(wa[e] << 16), wh = __uint_as_float(wa[e] & 0xffff0000u);
        za = fmaf(__uint_as_float(xa[e] << 16), wl, za); za = fmaf(__uint_as_float(xa[e] & 0xffff0000u), wh, za);
        zb = fmaf(__uint_as_float(xb[e] << 16), wl, zb); zb = fmaf(__uint_as_float(xb[e] & 0xffff0000u), wh, zb);
      }
#pragma unroll
      for (int o = 16; o > 0; o >>= 1) { za += __shfl_xor_sync(0xffffffffu, za, o); zb += __shfl_xor_sync(0xffffffffu, zb, o); }
      if (lane < 2) asm volatile("st.shared.f32 [%0], %1;" ::"r"(sbase + OFF_GST + (warp - 8) * 8 + lane * 4), "f"(1.f / (1.f + __expf(-(lane ? zb : za)))) : "memory");
      fence_async_smem();
      named_bar<6>(256);
      if (tid == 256) {
        bulk_store(&g_gate[rb * 128 + j * 16], sbase + OFF_GST, 64);
        bulk_commit(); bulk_wait_all();
        flag_add(&g_flag_g[rb * FS]);
        flag_wait(&g_flag_g[rb * FS], ep1 * 8, t0);
        fence_async_global();
        mbar_expect_tx(bars + 8 * BAR_GIN, 512);
        bulk_load(sbase + OFF_GIN, &g_gate[rb * 128], 512, bars + 8 * BAR_GIN);
        TR(10);
      }
      __syncwarp();
    }
    mbar_wait(bars + 8 * (BAR_QRDY + aw), 0, t0);
    asm volatile("setmaxnreg.inc.sync.aligned.u32 96;");
    attention(sbase, aw, warp & 3, lane, rb, t0);
    if (tid == 256) TR(3);
  } else {
    asm volatile("setmaxnreg.dec.sync.aligned.u32 32;");
    if (warp == 16) {
      __syncwarp();
      cluster_wait();
      if (lane == 0) {
        int bi = 2; uint32_t bph = 1;
        const int nb = 32 + on + 4;
        for (int eb = 2; eb < nb; eb++) {
          if (eb == 4 || eb == 6) {
            const int ea = eb >> 1;
            mbar_expect_tx(bars + 8 * (BAR_FULLA + 1 + ea), 16384);
            tma_load_2d(sbase + OFF_A + (1 + ea) * SLOT, &P.tmX, ea * 64, rb * 128, bars + 8 * (BAR_FULLA + 1 + ea));
          }
          const uint32_t fb = bars + 8 * (BAR_FULLB + bi), dst = sbase + OFF_B + bi * SLOT + rank * 8192;
          mbar_wait(bars + 8 * (BAR_EMPTYB + bi), bph, t0);
          if (eb < 16) {
            mbar_expect_tx(fb, typeB ? 12288 : 16384);
            tma_load_3d_mc(dst, &P.tmWqkv, 64 * j, eb * 32 + rank * 16, 0, fb);
            if (!typeB) tma_load_3d_mc(dst + 6144, &P.tmW1a, 0, eb * 32 + rank * 16, 24 + (j >> 1), fb);
          }
          else if (eb < 32) { mbar_expect_tx(fb, 12288); tma_load_3d_mc(dst, &P.tmW1b, 0, (eb - 16) * 32 + rank * 16, 3 * j, fb); }
          else if (eb < 32 + on) { int ow; const int ch = oh_chunk(j, eb - 32, ow); mbar_expect_tx(fb, 16384); tma_load_3d_mc(dst, &P.tmW2, 0, ch * 64 + rank * 32, (j >> 1) * 2, fb); }
          else { mbar_expect_tx(fb, 16384); tma_load_4d_mc(dst, &P.tmWo, 64 * j, 0, eb - 32 - on, rank * 4, fb); }
          if (++bi == NB) { bi = 0; bph ^= 1; }
          if (eb == PFAT) {
            const int b = blockIdx.x;
            l2_prefetch((const uint8_t*)P.w1 + b * 14336, 14336);
            l2_prefetch((const uint8_t*)P.w2 + b * 14336, 14336);
            l2_prefetch((const uint8_t*)P.wo + b * 4096, 4096);
          }
        }
      }
    } else if (warp == 17) {
      cluster_wait();
      if (lane == 0) {
        for (int ea = 1; ea < 5; ea++) mbar_arrive(bars + 8 * (BAR_EMPTYA + ea));
        uint32_t aph = 0xE1;
        const int na = 16 + on + 8;
        unsigned ready = 0;
        for (int ea = 4; ea < na; ea++) {
          const int ai = a_slot(ea, 20 + on);
          const uint32_t fb = bars + 8 * (BAR_FULLA + ai), dst = sbase + OFF_A + ai * SLOT;
          int ch = ea & 7, need = -1;
          if (ea >= 16 + on) { need = 8 + ea - 16 - on; ch = 20 + need; }
          else if (ea >= 19) ch = oh_chunk(j, ea - 16, need);
          if (need >= 0 && !((ready >> need) & 1)) {
            const unsigned* fp = need < 8 ? &g_flag_h[rb * 8 * FS] : need < 16 ? &g_flag_o[rb * 8 * FS] : &g_flag_e[rb * 8 * FS];
            const unsigned tgt = (need & 8) ? ep1 * 4 : ep1;
            do {
              unsigned v[8];
#pragma unroll
              for (int i = 0; i < 8; i++) v[i] = ld_relaxed(fp + i * FS);
#pragma unroll
              for (int i = 0; i < 8; i++) if ((int)(v[i] - tgt) >= 0) ready |= 1u << (i + (need & 24));
            } while (!((ready >> need) & 1) && clk32() - t0 < TIMEOUT);
            fence_async_global();
          }
          mbar_wait(bars + 8 * (BAR_EMPTYA + ai), (aph >> ai) & 1, t0);
          if (ea >= 16 && ea < 19) mbar_arrive(fb);
          else {
            mbar_arrive(bars + 8 * (BAR_EMPTYA + ai));
            mbar_expect_tx(fb, 16384);
            tma_load_2d(dst, ea < 16 ? &P.tmX : &P.tmHO, ch * 64, rb * 128, fb);
          }
          TR(24 + ea);
          aph ^= 1u << ai;
        }
      }
    } else {
      const int wg = warp - 18;
      cluster_wait();
      if (lane == 0 && wg == 0) {
        const uint32_t stg = bars + 8 * BAR_STG;
        mbar_wait(stg, 0, t0);
        for (int hh = 0; hh < 4; hh++) bulk_store(g_kv + ((size_t)(4 * j + hh) * SEQ + rb * 128) * 64, sbase + OFF_KV + hh * 8192, 8192);
        bulk_commit(); bulk_wait_all();
        flag_add(&g_flag_kv[(rb * 8 + j) * FS]);
        TR(21);
        if (!typeB) {
          mbar_wait(bars + 8 * BAR_STE, 0, t0);
          tma_store_2d(&P.tmHO, (24 + (j >> 1)) * 64, rb * 128, sbase + OFF_KV + 32768);
          bulk_commit(); bulk_wait_all();
          flag_add(&g_flag_e[(rb * 8 + j) * FS]);
        }
        mbar_arrive(bars + 8 * BAR_KVOK);
        mbar_wait(stg, 1, t0);
        for (int i = 0; i < 3; i++) tma_store_2d(&P.tmHO, (3 * j + i) * 64, rb * 128, sbase + OFF_A + (1 + i) * SLOT);
        bulk_commit(); bulk_wait_all();
        flag_add(&g_flag_h[(rb * 8 + j) * FS]);
        for (int i = 0; i < 3; i++) mbar_arrive(bars + 8 * (BAR_EMPTYA + 1 + i));
        TR(22);
        {
          const unsigned old = atomicAdd(&g_done, 1u);
          if (old == gridDim.x - 1) { g_done = 0; *(volatile unsigned*)&g_epoch = ep1; }
        }
        mbar_wait(stg, 0, t0);
        bulk_store(g_part + (size_t)(rb * 8 + (j ^ 1)) * 16384, sbase + OFF_B + ((30 + on) % NB) * SLOT, 16384);
        bulk_commit(); bulk_wait_all();
        flag_add(&g_flag_p[(rb * 8 + (j ^ 1)) * FS]);
        TR(23);
        flag_wait(&g_flag_p[(rb * 8 + j) * FS], ep1, t0);
        fence_async_global();
        mbar_expect_tx(bars + 8 * BAR_PIN, 16384);
        bulk_load(sbase + OFF_B + ((31 + on) % NB) * SLOT, g_part + (size_t)(rb * 8 + j) * 16384, 16384, bars + 8 * BAR_PIN);
      } else if (lane == 0) {
        const int nblk = rb >= 2 ? 3 : rb + 1;
        const uint32_t kvbytes = nblk * 8192;
        const uint8_t* kvsrc = g_kv + ((size_t)(4 * j) * SEQ + (rb + 1 - nblk) * 128) * 64;
        const uint32_t kvdst = sbase + OFF_KV + (3 - nblk) * 8192;
        {
          const unsigned* f0 = &g_flag_kv[(rb * 8 + j) * FS];
          const unsigned* f1 = rb >= 1 ? f0 - 8 * FS : f0;
          const unsigned* f2 = rb >= 2 ? f0 - 16 * FS : f0;
          unsigned v0, v1, v2;
          do { v0 = ld_relaxed(f0); v1 = ld_relaxed(f1); v2 = ld_relaxed(f2); }
          while (((int)(v0 - ep1) < 0 || (int)(v1 - ep1) < 0 || (int)(v2 - ep1) < 0) && clk32() - t0 < TIMEOUT);
        }
        TR(11);
        fence_async_global();
        mbar_expect_tx(bars + 8 * BAR_KVFULL, kvbytes);
        bulk_load(kvdst, kvsrc, kvbytes, bars + 8 * BAR_KVFULL);
        mbar_wait(bars + 8 * BAR_KVOK, 0, t0);
        mbar_expect_tx(bars + 8 * (BAR_KVFULL + 1), kvbytes);
        bulk_load(kvdst + KVBUF, kvsrc + (size_t)SEQ * 64, kvbytes, bars + 8 * (BAR_KVFULL + 1));
        for (int hh = 0; hh < 4; hh++) {
          for (int aw = 0; aw < 2; aw++) {
            mbar_wait(bars + 8 * (BAR_OST + aw), hh & 1, t0);
            tma_store_2d(&P.tmOs, DFF + hh * 128 + j * 16, rb * 128 + aw * 64, sbase + OFF_A + aw * 8192 + hh * 2048);
          }
          bulk_commit();
          if (hh < 2) {
            mbar_wait(bars + 8 * (BAR_KVEMPTY + hh), 0, t0);
            mbar_expect_tx(bars + 8 * (BAR_KVFULL + hh), kvbytes);
            bulk_load(kvdst + hh * KVBUF, kvsrc + (size_t)(hh + 2) * SEQ * 64, kvbytes, bars + 8 * (BAR_KVFULL + hh));
          }
          bulk_wait_all();
          flag_add(&g_flag_o[(rb * 8 + hh * 2 + (j >> 2)) * FS]);
          TR(12 + hh);
        }
      }
    }
  }
}

typedef CUresult (*EncodeFn)(CUtensorMap*, CUtensorMapDataType, cuuint32_t, void*, const cuuint64_t*, const cuuint64_t*, const cuuint32_t*,
                             const cuuint32_t*, CUtensorMapInterleave, CUtensorMapSwizzle, CUtensorMapL2promotion, CUtensorMapFloatOOBfill);

void make_map(EncodeFn enc, CUtensorMap* m, const void* ptr, int rank, const cuuint64_t* dims, const cuuint64_t* strides, const cuuint32_t* box,
              CUtensorMapSwizzle sw = CU_TENSOR_MAP_SWIZZLE_128B) {
  cuuint32_t es[4] = {1, 1, 1, 1};
  enc(m, CU_TENSOR_MAP_DATA_TYPE_BFLOAT16, rank, const_cast<void*>(ptr), dims, strides, box, es, CU_TENSOR_MAP_INTERLEAVE_NONE, sw,
      CU_TENSOR_MAP_L2_PROMOTION_L2_256B, CU_TENSOR_MAP_FLOAT_OOB_FILL_NONE);
}

}

extern "C" void kernel_launch(void* const* d_in, const int* in_sizes, int n_in, void* d_out, int out_size) {
  (void)in_sizes; (void)n_in; (void)out_size;
  static EncodeFn enc = nullptr;
  static void* ho_ptr = nullptr;
  if (!enc) {
    void* fn = nullptr; cudaDriverEntryPointQueryResult st;
    cudaGetDriverEntryPoint("cuTensorMapEncodeTiled", &fn, cudaEnableDefault, &st);
    enc = (EncodeFn)fn;
    cudaGetSymbolAddress(&ho_ptr, g_ho);
    cudaFuncSetAttribute(fused_kernel, cudaFuncAttributeMaxDynamicSharedMemorySize, SMEM_BYTES);
  }
  const __nv_bfloat16* x = (const __nv_bfloat16*)d_in[0];
  const __nv_bfloat16* wqkv = (const __nv_bfloat16*)d_in[1];
  const __nv_bfloat16* wo = (const __nv_bfloat16*)d_in[2];
  const __nv_bfloat16* w1 = (const __nv_bfloat16*)d_in[4];
  const __nv_bfloat16* w2 = (const __nv_bfloat16*)d_in[5];
  const __nv_bfloat16* gate_w = (const __nv_bfloat16*)d_in[6];
  Params P;
  { cuuint64_t d[2] = {DM, SEQ}, s[1] = {DM * 2}; cuuint32_t b[2] = {64, 128}; make_map(enc, &P.tmX, x, 2, d, s, b); }
  { cuuint64_t d[3] = {512, 512, 3}, s[2] = {1536 * 2, 512 * 2}; cuuint32_t b[3] = {64, 16, 3}; make_map(enc, &P.tmWqkv, wqkv, 3, d, s, b); }
  { cuuint64_t d[3] = {64, 512, 28}, s[2] = {DFF * 2, 128}; cuuint32_t b[3] = {64, 16, 1}; make_map(enc, &P.tmW1a, w1, 3, d, s, b);
    b[2] = 3; make_map(enc, &P.tmW1b, w1, 3, d, s, b); }
  { cuuint64_t d[3] = {64, DFF, 8}, s[2] = {DM * 2, 128}; cuuint32_t b[3] = {64, 32, 2}; make_map(enc, &P.tmW2, w2, 3, d, s, b); }
  { cuuint64_t d[4] = {DM, 16, 4, 8}, s[3] = {DM * 2, 16 * DM * 2, 64 * DM * 2}; cuuint32_t b[4] = {64, 16, 1, 4}; make_map(enc, &P.tmWo, wo, 4, d, s, b); }
  { cuuint64_t d[2] = {KHO, SEQ}, s[1] = {KHO * 2}; cuuint32_t b[2] = {64, 128}; make_map(enc, &P.tmHO, ho_ptr, 2, d, s, b);
    b[1] = 64; make_map(enc, &P.tmHOs, ho_ptr, 2, d, s, b);
    b[0] = 16; make_map(enc, &P.tmOs, ho_ptr, 2, d, s, b, CU_TENSOR_MAP_SWIZZLE_NONE); }
  { cuuint64_t d[2] = {DM, SEQ}, s[1] = {DM * 2}; cuuint32_t b[2] = {64, 16}; make_map(enc, &P.tmOut, d_out, 2, d, s, b); }
  P.x = x; P.gate_w = gate_w; P.w1 = w1; P.w2 = w2; P.wo = wo; P.out = (__nv_bfloat16*)d_out;
  fused_kernel<<<128, 640, SMEM_BYTES>>>(P);
}
```

```cpp
#include <cuda_runtime.h>
#include <cuda_bf16.h>
#include <cuda.h>
#include <stdint.h>

#define DEVI __device__ __forceinline__

namespace {

constexpr int SEQ = 2048, DM = 512, DFF = 1792, KHO = 2304;
constexpr int NA = 5, NB = 6, SLOT = 16384, KVBUF = 24576;
constexpr int NA2 = 8;
constexpr int OFF_B = 0, OFF_A = NB * SLOT, OFF_KV = OFF_A + NA * SLOT, OFF_BAR = OFF_KV + 2 * KVBUF;
constexpr int OFF_GST = OFF_BAR + 512;
constexpr int OFF_GIN = OFF_BAR + 1024;
constexpr int OFF_NM = OFF_BAR + 1536;
constexpr int SMEM_BYTES = OFF_BAR + 2560;
constexpr uint32_t TIMEOUT = 1u << 28;
#define WAIT_HINT_NS 20000u
#define PFAT 8
#define SH true
#define SHW 0
#define SHG 1
#define PF0 0
#define SHO true
#define SHS 6
constexpr int FS = 8;

constexpr int BAR_FULLA = 0, BAR_EMPTYA = BAR_FULLA + NA2, BAR_FULLB = BAR_EMPTYA + NA2, BAR_EMPTYB = BAR_FULLB + NB,
              BAR_KVFULL = BAR_EMPTYB + NB, BAR_KVEMPTY = BAR_KVFULL + 2, BAR_STG = BAR_KVEMPTY + 2, BAR_PIN = BAR_STG + 2, BAR_GATE = BAR_PIN + 1, BAR_STE = BAR_GATE + 2, BAR_ATTDONE = BAR_STE + 2, BAR_GIN = BAR_ATTDONE + 1, BAR_OST = BAR_GIN + 1, BAR_QRDY = BAR_OST + 2, BAR_KVOK = BAR_QRDY + 2;

__device__ __align__(1024) uint8_t g_kv[32 * SEQ * 64];
__device__ __align__(1024) __nv_bfloat16 g_ho[SEQ * KHO];
__device__ __align__(1024) uint8_t g_part[128 * 16384];
__device__ __align__(128) float g_gate[SEQ];
__device__ unsigned g_flag_kv[128 * FS], g_flag_h[128 * FS], g_flag_o[128 * FS], g_flag_g[16 * FS], g_flag_p[128 * FS], g_flag_e[128 * FS];
__device__ unsigned g_epoch, g_done;
#define TR(i) do {} while (0)

struct Params {
  CUtensorMap tmX, tmWqkv, tmW1a, tmW1b, tmW2, tmWo, tmHO, tmOs;
  const __nv_bfloat16* x;
  const __nv_bfloat16* gate_w;
  const __nv_bfloat16* w1;
  const __nv_bfloat16* w2;
  const __nv_bfloat16* wo;
  const __nv_bfloat16* wqkv;
  __nv_bfloat16* out;
};

DEVI uint32_t smem_u32(const void* p) { return (uint32_t)__cvta_generic_to_shared(p); }
DEVI uint32_t clk32() { uint32_t c; asm volatile("mov.u32 %0, %%clock;" : "=r"(c)); return c; }
DEVI void mbar_init(uint32_t bar, uint32_t cnt) { asm volatile("mbarrier.init.shared::cta.b64 [%0], %1;" ::"r"(bar), "r"(cnt)); }
DEVI void mbar_expect_tx(uint32_t bar, uint32_t bytes) { asm volatile("mbarrier.arrive.expect_tx.shared::cta.b64 _, [%0], %1;" ::"r"(bar), "r"(bytes) : "memory"); }
DEVI void mbar_arrive(uint32_t bar) { asm volatile("mbarrier.arrive.shared::cta.b64 _, [%0];" ::"r"(bar) : "memory"); }
DEVI void mbar_arrive_cluster(uint32_t bar, uint32_t cta) {
  asm volatile("{ .reg .b32 ra; mapa.shared::cluster.u32 ra, %0, %1; mbarrier.arrive.shared::cluster.b64 _, [ra]; }" ::"r"(bar), "r"(cta) : "memory");
}
DEVI void mbar_wait(uint32_t bar, uint32_t parity, uint32_t t0) {
  asm volatile("{ .reg .pred p; .reg .u32 c;\n"
               "mbarrier.try_wait.parity.shared::cta.b64 p, [%0], %1;\n"
               "@p bra DONE_%=;\n"
               "WAIT_%=:\n"
               "mbarrier.try_wait.parity.shared::cta.b64 p, [%0], %1, %4;\n"
               "@p bra DONE_%=;\n"
               "mov.u32 c, %%clock; sub.u32 c, c, %2; setp.lt.u32 p, c, %3;\n"
               "@p bra WAIT_%=;\n"
               "DONE_%=: }" ::"r"(bar), "r"(parity), "r"(t0), "n"(TIMEOUT), "r"(WAIT_HINT_NS) : "memory");
}
DEVI unsigned ld_relaxed(const unsigned* p) { unsigned v; asm volatile("ld.relaxed.gpu.global.u32 %0, [%1];" : "=r"(v) : "l"(p) : "memory"); return v; }
DEVI void flag_wait(const unsigned* p, unsigned target, uint32_t t0) {
  while ((int)(ld_relaxed(p) - target) < 0) { if (clk32() - t0 > TIMEOUT) break; }
}
DEVI void flag_add(unsigned* p) { asm volatile("red.relaxed.gpu.global.add.u32 [%0], 1;" ::"l"(p) : "memory"); }
DEVI void fence_async_smem() { asm volatile("fence.proxy.async.shared::cta;" ::: "memory"); }
DEVI void fence_async_global() { asm volatile("fence.proxy.async.global;" ::: "memory"); }
DEVI void tma_load_2d(uint32_t dst, const CUtensorMap* m, int c0, int c1, uint32_t bar) {
  asm volatile("cp.async.bulk.tensor.2d.shared::cluster.global.mbarrier::complete_tx::bytes [%0], [%1, {%3, %4}], [%2];" ::"r"(dst), "l"(m), "r"(bar), "r"(c0), "r"(c1) : "memory");
}
DEVI void tma_load_3d(uint32_t dst, const CUtensorMap* m, int c0, int c1, int c2, uint32_t bar) {
  asm volatile("cp.async.bulk.tensor.3d.shared::cluster.global.mbarrier::complete_tx::bytes [%0], [%1, {%3, %4, %5}], [%2];"
               ::"r"(dst), "l"(m), "r"(bar), "r"(c0), "r"(c1), "r"(c2) : "memory");
}
DEVI void tma_load_3d_mc(uint32_t dst, const CUtensorMap* m, int c0, int c1, int c2, uint32_t bar) {
  asm volatile("cp.async.bulk.tensor.3d.shared::cluster.global.mbarrier::complete_tx::bytes.multicast::cluster [%0], [%1, {%3, %4, %5}], [%2], %6;"
               ::"r"(dst), "l"(m), "r"(bar), "r"(c0), "r"(c1), "r"(c2), "h"((uint16_t)3) : "memory");
}
DEVI void tma_load_4d_mc(uint32_t dst, const CUtensorMap* m, int c0, int c1, int c2, int c3, uint32_t bar) {
  asm volatile("cp.async.bulk.tensor.4d.shared::cluster.global.mbarrier::complete_tx::bytes.multicast::cluster [%0], [%1, {%3, %4, %5, %6}], [%2], %7;"
               ::"r"(dst), "l"(m), "r"(bar), "r"(c0), "r"(c1), "r"(c2), "r"(c3), "h"((uint16_t)3) : "memory");
}
DEVI void tma_store_2d(const CUtensorMap* m, int c0, int c1, uint32_t src) {
  asm volatile("cp.async.bulk.tensor.2d.global.shared::cta.bulk_group [%0, {%1, %2}], [%3];" ::"l"(m), "r"(c0), "r"(c1), "r"(src) : "memory");
}
DEVI void bulk_store(void* dst, uint32_t src, uint32_t bytes) {
  asm volatile("cp.async.bulk.global.shared::cta.bulk_group [%0], [%1], %2;" ::"l"(dst), "r"(src), "r"(bytes) : "memory");
}
DEVI void bulk_load(uint32_t dst, const void* src, uint32_t bytes, uint32_t bar) {
  asm volatile("cp.async.bulk.shared::cluster.global.mbarrier::complete_tx::bytes [%0], [%1], %2, [%3];" ::"r"(dst), "l"(src), "r"(bytes), "r"(bar) : "memory");
}
DEVI void bulk_commit() { asm volatile("cp.async.bulk.commit_group;" ::: "memory"); }
DEVI void bulk_wait_all() { asm volatile("cp.async.bulk.wait_group 0;" ::: "memory"); }
DEVI void l2_prefetch(const void* p, uint32_t bytes) { asm volatile("cp.async.bulk.prefetch.L2.global [%0], %1;" ::"l"(p), "r"(bytes) : "memory"); }
DEVI void cluster_arrive() { asm volatile("barrier.cluster.arrive.relaxed.aligned;" ::: "memory"); }
DEVI void cluster_wait() { asm volatile("barrier.cluster.wait.aligned;" ::: "memory"); }
template <int ID> DEVI void named_bar(int n) { asm volatile("bar.sync %0, %1;" ::"n"(ID), "r"(n) : "memory"); }
DEVI void wg_bar(int wg) { if (wg == 0) named_bar<1>(128); else named_bar<2>(128); }
DEVI void wgmma_fence() { asm volatile("wgmma.fence.sync.aligned;" ::: "memory"); }
DEVI void wgmma_commit() { asm volatile("wgmma.commit_group.sync.aligned;" ::: "memory"); }
template <int N> DEVI void wgmma_wait() { asm volatile("wgmma.wait_group.sync.aligned %0;" ::"n"(N) : "memory"); }
template <uint32_t LBO> DEVI uint64_t desc_sw128(uint32_t a16) {
  return ((uint64_t)(0x40000000u | (1024 >> 4)) << 32) | (a16 + ((LBO >> 4) << 16));
}
DEVI uint64_t desc_sw64(uint32_t a16) {
  return ((uint64_t)(0x80000000u | (512 >> 4)) << 32) | (a16 + ((512 >> 4) << 16));
}
DEVI uint32_t pack_bf16(float lo, float hi) { uint32_t r; asm("cvt.rn.bf16x2.f32 %0, %1, %2;" : "=r"(r) : "f"(hi), "f"(lo)); return r; }
DEVI void stsm_x4(uint32_t addr, uint32_t r0, uint32_t r1, uint32_t r2, uint32_t r3) {
  asm volatile("stmatrix.sync.aligned.m8n8.x4.shared.b16 [%0], {%1, %2, %3, %4};" ::"r"(addr), "r"(r0), "r"(r1), "r"(r2), "r"(r3) : "memory");
}
DEVI void sts128(uint32_t addr, uint32_t r0, uint32_t r1, uint32_t r2, uint32_t r3) {
  asm volatile("st.shared.v4.b32 [%0], {%1, %2, %3, %4};" ::"r"(addr), "r"(r0), "r"(r1), "r"(r2), "r"(r3) : "memory");
}
DEVI uint4 lds128(uint32_t addr) {
  uint4 v; asm volatile("ld.shared.v4.b32 {%0, %1, %2, %3}, [%4];" : "=r"(v.x), "=r"(v.y), "=r"(v.z), "=r"(v.w) : "r"(addr) : "memory"); return v;
}
DEVI float ex2(float x) { float y; asm("ex2.approx.ftz.f32 %0, %1;" : "=f"(y) : "f"(x)); return y; }

DEVI void wgmma_ss_n64(float (&d)[32], uint64_t da, uint64_t db) {
  asm volatile("wgmma.mma_async.sync.aligned.m64n64k16.f32.bf16.bf16 {%0, %1, %2, %3, %4, %5, %6, %7, %8, %9, %10, %11, %12, %13, %14, %15, %16, %17, %18, %19, %20, %21, %22, %23, %24, %25, %26, %27, %28, %29, %30, %31}, %32, %33, 1, 1, 1, 0, 1;"
    : "+f"(d[0]), "+f"(d[1]), "+f"(d[2]), "+f"(d[3]), "+f"(d[4]), "+f"(d[5]), "+f"(d[6]), "+f"(d[7]), "+f"(d[8]), "+f"(d[9]), "+f"(d[10]), "+f"(d[11]), "+f"(d[12]), "+f"(d[13]), "+f"(d[14]), "+f"(d[15]), "+f"(d[16]), "+f"(d[17]), "+f"(d[18]), "+f"(d[19]), "+f"(d[20]), "+f"(d[21]), "+f"(d[22]), "+f"(d[23]), "+f"(d[24]), "+f"(d[25]), "+f"(d[26]), "+f"(d[27]), "+f"(d[28]), "+f"(d[29]), "+f"(d[30]), "+f"(d[31])
    : "l"(da), "l"(db));
}
DEVI void wgmma_ss_n128(float (&d)[64], uint64_t da, uint64_t db) {
  asm volatile("wgmma.mma_async.sync.aligned.m64n128k16.f32.bf16.bf16 {%0, %1, %2, %3, %4, %5, %6, %7, %8, %9, %10, %11, %12, %13, %14, %15, %16, %17, %18, %19, %20, %21, %22, %23, %24, %25, %26, %27, %28, %29, %30, %31, %32, %33, %34, %35, %36, %37, %38, %39, %40, %41, %42, %43, %44, %45, %46, %47, %48, %49, %50, %51, %52, %53, %54, %55, %56, %57, %58, %59, %60, %61, %62, %63}, %64, %65, 1, 1, 1, 0, 1;"
    : "+f"(d[0]), "+f"(d[1]), "+f"(d[2]), "+f"(d[3]), "+f"(d[4]), "+f"(d[5]), "+f"(d[6]), "+f"(d[7]), "+f"(d[8]), "+f"(d[9]), "+f"(d[10]), "+f"(d[11]), "+f"(d[12]), "+f"(d[13]), "+f"(d[14]), "+f"(d[15]), "+f"(d[16]), "+f"(d[17]), "+f"(d[18]), "+f"(d[19]), "+f"(d[20]), "+f"(d[21]), "+f"(d[22]), "+f"(d[23]), "+f"(d[24]), "+f"(d[25]), "+f"(d[26]), "+f"(d[27]), "+f"(d[28]), "+f"(d[29]), "+f"(d[30]), "+f"(d[31]), "+f"(d[32]), "+f"(d[33]), "+f"(d[34]), "+f"(d[35]), "+f"(d[36]), "+f"(d[37]), "+f"(d[38]), "+f"(d[39]), "+f"(d[40]), "+f"(d[41]), "+f"(d[42]), "+f"(d[43]), "+f"(d[44]), "+f"(d[45]), "+f"(d[46]), "+f"(d[47]), "+f"(d[48]), "+f"(d[49]), "+f"(d[50]), "+f"(d[51]), "+f"(d[52]), "+f"(d[53]), "+f"(d[54]), "+f"(d[55]), "+f"(d[56]), "+f"(d[57]), "+f"(d[58]), "+f"(d[59]), "+f"(d[60]), "+f"(d[61]), "+f"(d[62]), "+f"(d[63])
    : "l"(da), "l"(db));
}
DEVI void wgmma_qk64(float (&d)[32], uint32_t a0, uint32_t a1, uint32_t a2, uint32_t a3, uint64_t db) {
  asm volatile("wgmma.mma_async.sync.aligned.m64n64k16.f32.bf16.bf16 {%0, %1, %2, %3, %4, %5, %6, %7, %8, %9, %10, %11, %12, %13, %14, %15, %16, %17, %18, %19, %20, %21, %22, %23, %24, %25, %26, %27, %28, %29, %30, %31}, {%32, %33, %34, %35}, %36, 0, 1, 1, 0;"
    : "=f"(d[0]), "=f"(d[1]), "=f"(d[2]), "=f"(d[3]), "=f"(d[4]), "=f"(d[5]), "=f"(d[6]), "=f"(d[7]), "=f"(d[8]), "=f"(d[9]), "=f"(d[10]), "=f"(d[11]), "=f"(d[12]), "=f"(d[13]), "=f"(d[14]), "=f"(d[15]), "=f"(d[16]), "=f"(d[17]), "=f"(d[18]), "=f"(d[19]), "=f"(d[20]), "=f"(d[21]), "=f"(d[22]), "=f"(d[23]), "=f"(d[24]), "=f"(d[25]), "=f"(d[26]), "=f"(d[27]), "=f"(d[28]), "=f"(d[29]), "=f"(d[30]), "=f"(d[31])
    : "r"(a0), "r"(a1), "r"(a2), "r"(a3), "l"(db));
}
DEVI void wgmma_pv(float (&d)[8], uint32_t a0, uint32_t a1, uint32_t a2, uint32_t a3, uint64_t db) {
  asm volatile("wgmma.mma_async.sync.aligned.m64n16k16.f32.bf16.bf16 {%0, %1, %2, %3, %4, %5, %6, %7}, {%8, %9, %10, %11}, %12, 1, 1, 1, 1;"
    : "+f"(d[0]), "+f"(d[1]), "+f"(d[2]), "+f"(d[3]), "+f"(d[4]), "+f"(d[5]), "+f"(d[6]), "+f"(d[7])
    : "r"(a0), "r"(a1), "r"(a2), "r"(a3), "l"(db));
}
DEVI void wgmma_pv0(float (&d)[8], uint32_t a0, uint32_t a1, uint32_t a2, uint32_t a3, uint64_t db) {
  asm volatile("wgmma.mma_async.sync.aligned.m64n16k16.f32.bf16.bf16 {%0, %1, %2, %3, %4, %5, %6, %7}, {%8, %9, %10, %11}, %12, 0, 1, 1, 1;"
    : "=f"(d[0]), "=f"(d[1]), "=f"(d[2]), "=f"(d[3]), "=f"(d[4]), "=f"(d[5]), "=f"(d[6]), "=f"(d[7])
    : "r"(a0), "r"(a1), "r"(a2), "r"(a3), "l"(db));
}

template <int N> struct Acc { float a[64]; float b[(N - 128) / 2]; DEVI float& operator[](int i) { return i < 64 ? a[i] : b[i - 64]; } };
template <> struct Acc<128> { float a[64]; DEVI float& operator[](int i) { return a[i]; } };
template <int N> DEVI void wgmma_ss(Acc<N>& d, uint64_t da, uint64_t db) {
  wgmma_ss_n128(d.a, da, db);
  if constexpr (N == 192) wgmma_ss_n64(d.b, da, db + 256);
  if constexpr (N == 256) wgmma_ss_n128(d.b, da, db + 256);
}

DEVI int oh_chunk(int j, int i, int& need) {
  if (i >= 3 && i < 5) { const int e = (j & 1) * 2 + i - 3; need = 16 + 2 * e; return 24 + e; }
  if (i >= 5) i -= 2;
  int o, r;
  if (i >= 12) { o = (j + 5) & 7; r = i - 11; }
  else { const int g = i / 3; o = (j + 2 * g) & 7; r = i - 3 * g; }
  need = o;
  return 3 * o + r;
}

DEVI int a_slot(int e, int) { return 1 + (e & 3); }

struct Ctx {
  uint32_t sbase, bars, peer, t0, a16, b16;
  int wg, lane;
  int ai, bi; uint32_t aph, bph;
  int brem, ae;
  int pa, pb;
};

DEVI void release_prev(Ctx& c) {
  if (c.pb >= 0) {
    if (c.lane == 0) mbar_arrive(c.bars + 8 * (BAR_EMPTYB + c.pb));
    if (c.lane == 1) mbar_arrive_cluster(c.bars + 8 * (BAR_EMPTYB + c.pb), c.peer);
  }
  if (c.pa >= 0 && c.lane == 2) mbar_arrive(c.bars + 8 * (BAR_EMPTYA + c.pa));
}

DEVI void gemm_wait(Ctx& c) {
  asm volatile("{ .reg .pred p, q; .reg .u32 c;\n"
               "mbarrier.try_wait.parity.shared::cta.b64 p, [%0], %1;\n"
               "mbarrier.try_wait.parity.shared::cta.b64 q, [%2], %3;\n"
               "and.pred p, p, q;\n"
               "@p bra DONE_%=;\n"
               "WAIT_%=:\n"
               "mbarrier.try_wait.parity.shared::cta.b64 p, [%0], %1, %6;\n"
               "mbarrier.try_wait.parity.shared::cta.b64 q, [%2], %3, %6;\n"
               "and.pred p, p, q;\n"
               "@p bra DONE_%=;\n"
               "mov.u32 c, %%clock; sub.u32 c, c, %4; setp.lt.u32 p, c, %5;\n"
               "@p bra WAIT_%=;\n"
               "DONE_%=: }" ::"r"(c.bars + 8 * (BAR_FULLA + c.ai)), "r"((c.aph >> c.ai) & 1), "r"(c.bars + 8 * (BAR_FULLB + c.bi)), "r"(c.bph), "r"(c.t0),
               "n"(TIMEOUT), "r"(WAIT_HINT_NS) : "memory");
}
template <int N, bool SHALLOW>
DEVI void gemm_group(Acc<N>& acc, Ctx& c, int g, int& npa, int& npb) {
  const uint32_t a16 = c.a16 + c.ai * (SLOT >> 4);
  const uint32_t b16 = c.b16 + c.bi * (SLOT >> 4);
  bool adv;
  if constexpr (N >= 192) {
    const uint32_t a2 = a16 + (g & 1) * 4;
    wgmma_ss<N>(acc, desc_sw128<16>(a2), desc_sw128<2048>(b16));
    if (SHALLOW) { wgmma_commit(); wgmma_wait<SHW>(); }
    wgmma_ss<N>(acc, desc_sw128<16>(a2 + 2), desc_sw128<2048>(b16 + 512));
    adv = g & 1;
  } else {
#pragma unroll
    for (int s = 0; s < 4; s++) {
      wgmma_ss<N>(acc, desc_sw128<16>(a16 + s * 2), desc_sw128<4096>(b16 + (s >> 1) * 512 + (s & 1) * 128));
      if (SHALLOW && s < 3 && (SHG == 1 || s == 1)) { wgmma_commit(); wgmma_wait<SHW>(); }
    }
    adv = true;
  }
  wgmma_commit();
  npb = c.brem > 0 ? c.bi : -1;
  c.brem--;
  if (++c.bi == NB) { c.bi = 0; c.bph ^= 1; }
  npa = -1;
  if (adv) { npa = c.ai; c.aph ^= 1u << c.ai; c.ae++; c.ai = 1 + (c.ae & 3); }
}

template <int N, bool SHALLOW = false>
DEVI void bare_groups(Acc<N>& acc, Ctx& c, int g0, int g1) {
  for (int g = g0; g < g1; g++) {
    int npa, npb;
    gemm_wait(c);
    wgmma_fence();
    gemm_group<N, SHALLOW>(acc, c, g, npa, npb);
    wgmma_wait<SHALLOW ? SHW : 1>();
    release_prev(c);
    c.pa = npa; c.pb = npb;
  }
}
DEVI void drain(Ctx& c) {
  wgmma_wait<0>();
  release_prev(c);
  c.pa = c.pb = -1;
}

constexpr float SC = 0.25f * 1.4426950408889634f;

#define ONCE _Pragma("unroll 1") for (unsigned once_ = 0; once_ < gridDim.y; once_++)

struct Gate { float g0, g1; };

DEVI void kill32(float (&S)[32]) {
#pragma unroll
  for (int i = 0; i < 32; i++) S[i] = __int_as_float(0xff800000);
}
DEVI void row_max(const float (&S)[32], float& x0, float& x1) {
  float y0 = S[1], y1 = S[3];
  x0 = fmaxf(x0, S[0]); x1 = fmaxf(x1, S[2]);
#pragma unroll
  for (int n = 1; n < 8; n++) {
    x0 = fmaxf(x0, S[4 * n]); y0 = fmaxf(y0, S[4 * n + 1]); x1 = fmaxf(x1, S[4 * n + 2]); y1 = fmaxf(y1, S[4 * n + 3]);
  }
  x0 = fmaxf(x0, y0); x1 = fmaxf(x1, y1);
}
DEVI void quad_max(float& x0, float& x1) {
  x0 = fmaxf(x0, __shfl_xor_sync(0xffffffffu, x0, 1)); x1 = fmaxf(x1, __shfl_xor_sync(0xffffffffu, x1, 1));
  x0 = fmaxf(x0, __shfl_xor_sync(0xffffffffu, x0, 2)); x1 = fmaxf(x1, __shfl_xor_sync(0xffffffffu, x1, 2));
}
DEVI void exp32(const float (&S)[32], float (&E)[32], float n0, float n1, float (&l)[4]) {
#pragma unroll
  for (int i = 0; i < 32; i++) { E[i] = ex2(fmaf(S[i], SC, (i & 2) ? n1 : n0)); l[i & 3] += E[i]; }
}
DEVI void pack32(const float (&E)[32], uint32_t (&P)[16]) {
#pragma unroll
  for (int i = 0; i < 16; i++) P[i] = pack_bf16(E[2 * i], E[2 * i + 1]);
}
template <bool FIRST> DEVI void pv4(float (&O)[8], const uint32_t (&P)[16], uint32_t v16) {
  if (FIRST) wgmma_pv0(O, P[0], P[1], P[2], P[3], desc_sw64(v16)); else wgmma_pv(O, P[0], P[1], P[2], P[3], desc_sw64(v16));
#pragma unroll
  for (int k = 1; k < 4; k++) wgmma_pv(O, P[4 * k], P[4 * k + 1], P[4 * k + 2], P[4 * k + 3], desc_sw64(v16 + k * 64));
}
DEVI bool wg_any(int wg, bool v) {
  uint32_t r;
  if (wg == 0) asm volatile("{ .reg .pred p, q; setp.ne.u32 p, %1, 0; bar.red.or.pred q, 4, 128, p; selp.u32 %0, 1, 0, q; }" : "=r"(r) : "r"((uint32_t)v) : "memory");
  else asm volatile("{ .reg .pred p, q; setp.ne.u32 p, %1, 0; bar.red.or.pred q, 5, 128, p; selp.u32 %0, 1, 0, q; }" : "=r"(r) : "r"((uint32_t)v) : "memory");
  return r != 0;
}
DEVI void get_gate(Gate& g, uint32_t sbase, int row16, int lane, uint32_t t0) {
  mbar_wait(sbase + OFF_BAR + 8 * BAR_GIN, 0, t0);
  const uint32_t a = sbase + OFF_GIN + (row16 * 16 + (lane >> 2)) * 4;
  asm volatile("ld.shared.f32 %0, [%1];" : "=f"(g.g0) : "r"(a) : "memory");
  asm volatile("ld.shared.f32 %0, [%1];" : "=f"(g.g1) : "r"(a + 32) : "memory");
}

DEVI void attention(uint32_t sbase, int aw, int wi, int lane, int rb, uint32_t t0) {
  const uint32_t bars = sbase + OFF_BAR;
  const uint32_t kvb = ((sbase & 0x3FFFF) + OFF_KV + aw * 4096) >> 4;
  const int cmin = 4 - 2 * rb - aw;
  const int rowc = wi * 16 + (lane >> 2) - (lane & 3) * 2;
  const uint32_t qst = sbase + OFF_A + aw * 8192;
  const float NINF = __int_as_float(0xff800000);
  const int tlo = max(cmin, 1);
#pragma unroll 1
  for (int h = 0; h < 4; h++) {
    const uint32_t kb = kvb + (h & 1) * (KVBUF >> 4);
    const uint4 q = lds128(qst + h * 2048 + (wi * 32 + lane) * 16);
    float O[8], l0, l1;
    uint32_t nm;
    asm volatile("ld.shared.u32 %0, [%1];" : "=r"(nm) : "r"(sbase + OFF_NM + ((aw * 4 + wi) * 32 + (lane & 28) + h) * 4) : "memory");
    float n0 = __uint_as_float(nm << 16), n1 = __uint_as_float(nm & 0xffff0000u);
    mbar_wait(bars + 8 * (BAR_KVFULL + (h & 1)), h >> 1, t0);
#pragma unroll 1
    for (int attempt = 0; attempt < 2; attempt++) {
      float l[4] = {0.f, 0.f, 0.f, 0.f};
      uint32_t P[16];
      {
        float S[32], F[32];
        wgmma_fence();
        wgmma_qk64(S, q.x, q.y, q.z, q.w, desc_sw64(kb + 4 * 256));
        wgmma_qk64(F, q.x, q.y, q.z, q.w, desc_sw64(kb));
        wgmma_commit();
        wgmma_wait<0>();
        for (int r = 0; r < (cmin > 0 ? 1 : 0); r++) kill32(F);
        float M[32];
#pragma unroll
        for (int i = 0; i < 32; i++) M[i] = ((i >> 2) * 8 + (i & 1) > rowc + (i & 2) * 4) ? F[i] : S[i];
        for (int r = 0; r < attempt; r++) {
          row_max(M, n0, n1);
          quad_max(n0, n1);
          n0 *= -SC; n1 *= -SC;
        }
        exp32(M, M, n0, n1, l);
        pack32(M, P);
        uint32_t PF[16];
#pragma unroll
        for (int i = 0; i < 16; i++) {
          const int col = (i >> 1) * 8, r = rowc + (i & 1) * 8;
          const uint32_t m = (col > r ? 0xFFFFu : 0u) | (col + 1 > r ? 0xFFFF0000u : 0u);
          PF[i] = P[i] & m; P[i] &= ~m;
        }
        wgmma_fence();
        pv4<true>(O, PF, kb + 2);
        wgmma_commit();
        wgmma_wait<0>();
      }
      int t = 3;
#pragma unroll 1
      for (; t >= tlo; t--) {
        float S[32];
        wgmma_fence();
        wgmma_qk64(S, q.x, q.y, q.z, q.w, desc_sw64(kb + t * 256));
        wgmma_commit();
        pv4<false>(O, P, kb + (t + 1) * 256 + 2);
        wgmma_commit();
        wgmma_wait<1>();
        ONCE { exp32(S, S, n0, n1, l); }
        wgmma_wait<0>();
        pack32(S, P);
      }
      wgmma_fence();
      pv4<false>(O, P, kb + (t + 1) * 256 + 2);
      wgmma_commit();
      l0 = l[0] + l[1]; l1 = l[2] + l[3];
      l0 += __shfl_xor_sync(0xffffffffu, l0, 1); l1 += __shfl_xor_sync(0xffffffffu, l1, 1);
      l0 += __shfl_xor_sync(0xffffffffu, l0, 2); l1 += __shfl_xor_sync(0xffffffffu, l1, 2);
      const bool redo = wg_any(aw, attempt == 0 && !(l0 > 1e-6f && l0 < 1e18f && l1 > 1e-6f && l1 < 1e18f));
      wgmma_wait<0>();
      if (!redo) break;
      n0 = NINF; n1 = NINF;
#pragma unroll 1
      for (int u = 3; u >= tlo; u--) {
        float S[32];
        wgmma_fence();
        wgmma_qk64(S, q.x, q.y, q.z, q.w, desc_sw64(kb + u * 256));
        wgmma_commit();
        wgmma_wait<0>();
        row_max(S, n0, n1);
      }
    }
    if (lane == 0) mbar_arrive(bars + 8 * (BAR_KVEMPTY + (h & 1)));
    Gate g;
    get_gate(g, sbase, aw * 4 + wi, lane, t0);
    const float c0 = __fdividef(g.g0, l0), c1 = __fdividef(g.g1, l1);
    const int mi = lane >> 3;
    const int srow = wi * 16 + (lane & 7) + 8 * (mi & 1);
    stsm_x4(qst + h * 2048 + srow * 32 + (mi >> 1) * 16, pack_bf16(O[0] * c0, O[1] * c0), pack_bf16(O[2] * c1, O[3] * c1),
            pack_bf16(O[4] * c0, O[5] * c0), pack_bf16(O[6] * c1, O[7] * c1));
    fence_async_smem();
    __syncwarp();
    if (lane == 0) mbar_arrive(bars + 8 * (BAR_OST + aw));
  }
}

template <int CH, int N>
DEVI void store_h_chunk(Acc<N>& acc, uint32_t base  , int lane, float s0, float s1) {
  const int mi = lane >> 3;
#pragma unroll
  for (int tp = 0; tp < 4; tp++) {
    const int t = CH * 8 + tp * 2;
    const uint32_t r0 = pack_bf16(fmaxf(acc[4 * t + 0], 0.f) * s0, fmaxf(acc[4 * t + 1], 0.f) * s0);
    const uint32_t r1 = pack_bf16(fmaxf(acc[4 * t + 2], 0.f) * s1, fmaxf(acc[4 * t + 3], 0.f) * s1);
    const uint32_t r2 = pack_bf16(fmaxf(acc[4 * t + 4], 0.f) * s0, fmaxf(acc[4 * t + 5], 0.f) * s0);
    const uint32_t r3 = pack_bf16(fmaxf(acc[4 * t + 6], 0.f) * s1, fmaxf(acc[4 * t + 7], 0.f) * s1);
    stsm_x4(base + (((tp * 2 + (mi >> 1)) ^ (lane & 7)) << 4), r0, r1, r2, r3);
  }
}

template <int N>
DEVI void phase_q(Ctx& c, int warp) {
  Acc<N> acc;
#pragma unroll
  for (int i = 0; i < N / 2; i++) acc[i] = 0.f;
  bare_groups<N>(acc, c, 0, 16);
  drain(c);
  const int lane = c.lane, mi = lane >> 3;
  const int row = warp * 16 + (lane & 7) + 8 * (mi & 1);
  const int sw = (row >> 1) & 3;
#pragma unroll
  for (int hh = 0; hh < 4; hh++) {
    const uint32_t base = c.sbase + OFF_KV + hh * 8192 + row * 64;
#pragma unroll
    for (int kv = 0; kv < 2; kv++) {
      const int t = 8 + kv * 8 + 2 * hh;
      stsm_x4(base + (((kv * 2 + (mi >> 1)) ^ sw) << 4),
              pack_bf16(acc[4 * t + 0], acc[4 * t + 1]), pack_bf16(acc[4 * t + 2], acc[4 * t + 3]),
              pack_bf16(acc[4 * t + 4], acc[4 * t + 5]), pack_bf16(acc[4 * t + 6], acc[4 * t + 7]));
    }
  }
  fence_async_smem();
  __syncwarp();
  if (lane == 0) mbar_arrive(c.bars + 8 * BAR_STG);
#pragma unroll
  for (int hh = 0; hh < 4; hh++)
    sts128(c.sbase + OFF_A + c.wg * 8192 + hh * 2048 + ((warp & 3) * 32 + lane) * 16,
           pack_bf16(acc[8 * hh], acc[8 * hh + 1]), pack_bf16(acc[8 * hh + 2], acc[8 * hh + 3]),
           pack_bf16(acc[8 * hh + 4], acc[8 * hh + 5]), pack_bf16(acc[8 * hh + 6], acc[8 * hh + 7]));
#pragma unroll
  for (int hh = 0; hh < 4; hh++) {
    const int q = 8 * hh, k = 32 + 8 * hh;
    float d0 = acc[q] * acc[k] + acc[q + 1] * acc[k + 1] + acc[q + 4] * acc[k + 4] + acc[q + 5] * acc[k + 5];
    float d1 = acc[q + 2] * acc[k + 2] + acc[q + 3] * acc[k + 3] + acc[q + 6] * acc[k + 6] + acc[q + 7] * acc[k + 7];
    d0 += __shfl_xor_sync(0xffffffffu, d0, 1); d1 += __shfl_xor_sync(0xffffffffu, d1, 1);
    d0 += __shfl_xor_sync(0xffffffffu, d0, 2); d1 += __shfl_xor_sync(0xffffffffu, d1, 2);
    if ((lane & 3) == hh)
      asm volatile("st.shared.u32 [%0], %1;" ::"r"(c.sbase + OFF_NM + (warp * 32 + lane) * 4), "r"(pack_bf16(-d0 * SC, -d1 * SC)) : "memory");
  }
  __syncwarp();
  if (lane == 0) mbar_arrive(c.bars + 8 * (BAR_QRDY + c.wg));
  if constexpr (N == 256) {
    Gate g;
    get_gate(g, c.sbase, warp, lane, c.t0);
    store_h_chunk<3>(acc, c.sbase + OFF_KV + 32768 + row * 128, lane, 1.f - g.g0, 1.f - g.g1);
    fence_async_smem();
    __syncwarp();
    if (lane == 0) mbar_arrive(c.bars + 8 * BAR_STE);
  }
}

DEVI void first_loads(const Params& P, uint32_t sbase, int e, int j, int rb) {
  const uint32_t bars = sbase + OFF_BAR, fb = bars + 8 * (BAR_FULLB + e), fa = bars + 8 * (BAR_FULLA + 1 + e);
  mbar_expect_tx(fa, 16384);
  mbar_expect_tx(fb, (j & 1) ? 12288 : 16384);
  if (e == 0) tma_load_2d(sbase + OFF_A + SLOT, &P.tmX, 0, rb * 128, fa);
#pragma unroll
  for (int r = 0; r < 2; r++) {
    tma_load_3d(sbase + OFF_B + e * SLOT + r * 8192, &P.tmWqkv, 64 * j, e * 32 + r * 16, 0, fb);
    if (!(j & 1)) tma_load_3d(sbase + OFF_B + e * SLOT + r * 8192 + 6144, &P.tmW1a, 0, e * 32 + r * 16, 24 + (j >> 1), fb);
  }
  if (e == 1) tma_load_2d(sbase + OFF_A + 2 * SLOT, &P.tmX, 64, rb * 128, fa);
}

__global__ void __cluster_dims__(2, 1, 1) __launch_bounds__(640, 1) fused_kernel(const __grid_constant__ Params P) {
  extern __shared__ __align__(1024) uint8_t smem_raw[];
  const uint32_t sbase = smem_u32(smem_raw);
  const uint32_t bars = sbase + OFF_BAR;
  const int tid = threadIdx.x, warp = tid >> 5, lane = tid & 31;
  const uint32_t rank = blockIdx.x & 1, peer = rank ^ 1;
  const int j = (blockIdx.x >> 1) & 7, rb = ((blockIdx.x >> 4) << 1) | rank;
  const uint32_t t0 = clk32();

  const int typeB = j & 1;
  if (tid == 544) {
    for (int s = 0; s < NA2; s++) mbar_init(bars + 8 * (BAR_FULLA + s), 1);
    for (int s = 0; s < NB; s++) mbar_init(bars + 8 * (BAR_FULLB + s), 1);
    fence_async_smem();
  } else if (tid < 8) {
    asm volatile("prefetch.tensormap [%0];" ::"l"(&P.tmX + tid) : "memory");
  } else if (tid == 512) {
    for (int s = 0; s < NA2; s++) mbar_init(bars + 8 * (BAR_EMPTYA + s), 9);
    for (int s = 0; s < NB; s++) mbar_init(bars + 8 * (BAR_EMPTYB + s), 16);
  } else if (tid == 576) {
    for (int s = 0; s < 2; s++) { mbar_init(bars + 8 * (BAR_KVFULL + s), 1); mbar_init(bars + 8 * (BAR_KVEMPTY + s), 8); mbar_init(bars + 8 * (BAR_OST + s), 4); mbar_init(bars + 8 * (BAR_QRDY + s), 4); }
    mbar_init(bars + 8 * BAR_STG, 8); mbar_init(bars + 8 * BAR_STE, 8); mbar_init(bars + 8 * BAR_KVOK, 1);
    mbar_init(bars + 8 * BAR_PIN, 1); mbar_init(bars + 8 * BAR_ATTDONE, 8); mbar_init(bars + 8 * BAR_GIN, 1);
  }
  if (tid >= 512 && lane == 0) asm volatile("fence.mbarrier_init.release.cluster;" ::: "memory");
  const unsigned ep1 = ld_relaxed(&g_epoch) + 1;
  __syncwarp();
  cluster_arrive();
  if (tid == 544) { first_loads(P, sbase, 0, j, rb); first_loads(P, sbase, 1, j, rb); }
  __syncwarp();

  const int on = 12 + 4 * typeB;

  if (warp < 8) {
    asm volatile("setmaxnreg.inc.sync.aligned.u32 160;");
    cluster_wait();
    const int wg = __shfl_sync(0xffffffffu, warp >> 2, 0);
    Ctx c{sbase, bars, peer, t0, ((sbase & 0x3FFFF) + OFF_A + wg * 8192) >> 4, ((sbase & 0x3FFFF) + OFF_B) >> 4, wg, lane, 1, 0, 0u, 0u, 32 + on + 4 - NB, 0, -1, -1};
    if (tid == 0) TR(0);
    if (typeB) phase_q<192>(c, warp);
    else phase_q<256>(c, warp);
    asm volatile("setmaxnreg.dec.sync.aligned.u32 128;");
    if (tid == 0) TR(2);
    {
      Acc<192> acc;
#pragma unroll
      for (int i = 0; i < 96; i++) acc[i] = 0.f;
      bare_groups<192>(acc, c, 0, SHS);
      bare_groups<192, SH>(acc, c, SHS, 16);
      Gate at;
      get_gate(at, sbase, warp, lane, t0);
      drain(c);
      if (tid == 0) TR(1);
      const uint32_t rowoff = (warp * 16 + (lane & 7) + 8 * ((lane >> 3) & 1)) * 128;
      const float s0 = 1.f - at.g0, s1 = 1.f - at.g1;
      constexpr int e0 = 1, e1 = 2, e2 = 3;
      mbar_wait(bars + 8 * (BAR_FULLA + e0), 0, t0);
      store_h_chunk<0>(acc, sbase + OFF_A + e0 * SLOT + rowoff, lane, s0, s1);
      mbar_wait(bars + 8 * (BAR_FULLA + e1), 0, t0);
      store_h_chunk<1>(acc, sbase + OFF_A + e1 * SLOT + rowoff, lane, s0, s1);
      mbar_wait(bars + 8 * (BAR_FULLA + e2), 0, t0);
      store_h_chunk<2>(acc, sbase + OFF_A + e2 * SLOT + rowoff, lane, s0, s1);
    }
    fence_async_smem();
    wg_bar(wg);
    if (lane == 0) mbar_arrive(bars + 8 * BAR_STG);
    if (tid == 0) TR(4);
    float own[32];
    {
      Acc<128> acc;
#pragma unroll
      for (int i = 0; i < 64; i++) acc[i] = 0.f;
      bare_groups<128, SHO>(acc, c, 0, on);
      drain(c);
      if (tid == 0) TR(5);
      named_bar<3>(256);
      const uint32_t pst = sbase + OFF_B + ((30 + on) % NB) * SLOT + wg * 8192 + (tid & 127) * 16;
#pragma unroll
      for (int i = 0; i < 4; i++) {
        uint32_t r[4];
#pragma unroll
        for (int k = 0; k < 4; k++) {
          const int idx = 8 * i + 2 * k;
          const float lo = typeB ? acc[idx] : acc[32 + idx], hi = typeB ? acc[idx + 1] : acc[32 + idx + 1];
          r[k] = pack_bf16(lo, hi);
        }
        sts128(pst + i * 2048, r[0], r[1], r[2], r[3]);
      }
#pragma unroll
      for (int i = 0; i < 32; i++) own[i] = typeB ? acc[32 + i] : acc[i];
      fence_async_smem();
      __syncwarp();
      if (lane == 0) mbar_arrive(bars + 8 * BAR_STG);
    }
#pragma unroll 1
    for (int g = 0; g < 8; g++) {
      const uint32_t a16 = c.a16 + c.ai * (SLOT >> 4);
      const uint32_t b16 = c.b16 + c.bi * (SLOT >> 4) + (g & 1) * 512;
      if (g == 6) {
        mbar_wait(bars + 8 * BAR_PIN, 0, t0);
        const uint32_t pin = sbase + OFF_B + ((31 + on) % NB) * SLOT + wg * 8192 + (tid & 127) * 16;
#pragma unroll
        for (int i = 0; i < 4; i++) {
          const uint4 v = lds128(pin + i * 2048);
          const uint32_t r[4] = {v.x, v.y, v.z, v.w};
#pragma unroll
          for (int k = 0; k < 4; k++) { own[8 * i + 2 * k] += __uint_as_float(r[k] << 16); own[8 * i + 2 * k + 1] += __uint_as_float(r[k] & 0xffff0000u); }
        }
        named_bar<3>(256);
        if (tid == 0) TR(7);
      }
      gemm_wait(c);
      wgmma_fence();
#pragma unroll
      for (int s = 0; s < 4; s++) wgmma_ss_n64(own, desc_sw128<16>(a16 + s * 2), desc_sw128<2048>(b16 + s * 128));
      wgmma_commit();
      wgmma_wait<0>();
      if (lane == 2) mbar_arrive(bars + 8 * (BAR_EMPTYA + c.ai));
      c.aph ^= 1u << c.ai;
      c.ae++; c.ai = a_slot(c.ae, 0);
      if (g & 1) { if (++c.bi == NB) { c.bi = 0; c.bph ^= 1; } }
    }
    if (tid == 0) TR(6);
    {
      const uint32_t ob = sbase + OFF_B + ((31 + on) % NB) * SLOT;
      const uint32_t wb = ob + warp * 2048;
      const uint32_t orow = wb + ((lane & 7) + 8 * ((lane >> 3) & 1)) * 128;
#pragma unroll
      for (int i = 0; i < 4; i++)
        stsm_x4(orow + (((i * 2 + (lane >> 4)) ^ (lane & 7)) << 4), pack_bf16(own[8 * i], own[8 * i + 1]), pack_bf16(own[8 * i + 2], own[8 * i + 3]),
                pack_bf16(own[8 * i + 4], own[8 * i + 5]), pack_bf16(own[8 * i + 6], own[8 * i + 7]));
      __syncwarp();
      uint4* o = (uint4*)(P.out + (size_t)(rb * 128 + warp * 16 + (lane >> 3)) * DM + j * 64) + (lane & 7);
#pragma unroll
      for (int i = 0; i < 4; i++) {
        const int r = i * 4 + (lane >> 3);
        o[i * 4 * (DM / 8)] = lds128(wb + r * 128 + (((lane & 7) ^ (r & 7)) << 4));
      }
    }
    if (tid == 0) TR(8);
  } else if (warp < 16) {
    asm volatile("setmaxnreg.dec.sync.aligned.u32 56;");
    cluster_wait();
    const int aw = __shfl_sync(0xffffffffu, (warp >> 2) & 1, 0);
    {
      const int rowg = rb * 128 + j * 16 + (warp - 8) * 2;
      const uint4* gw = (const uint4*)P.gate_w;
      const uint4* xr = (const uint4*)(P.x + (size_t)rowg * DM);
      mbar_wait(bars + 8 * (BAR_FULLB + 1), 0, t0);
      const uint4 w0 = __ldg(gw + lane), w1 = __ldg(gw + 32 + lane);
      const uint4 xa0 = __ldg(xr + lane), xa1 = __ldg(xr + 32 + lane), xb0 = __ldg(xr + 64 + lane), xb1 = __ldg(xr + 96 + lane);
#pragma unroll
      for (int i = 0; i < 4; i++) sts128(sbase + OFF_KV + 32768 + i * 4096 + (tid - 256) * 16, 0u, 0u, 0u, 0u);
      const uint32_t wa[8] = {w0.x, w0.y, w0.z, w0.w, w1.x, w1.y, w1.z, w1.w};
      const uint32_t xa[8] = {xa0.x, xa0.y, xa0.z, xa0.w, xa1.x, xa1.y, xa1.z, xa1.w};
      const uint32_t xb[8] = {xb0.x, xb0.y, xb0.z, xb0.w, xb1.x, xb1.y, xb1.z, xb1.w};
      float za = 0.f, zb = 0.f;
#pragma unroll
      for (int e = 0; e < 8; e++) {
        const float wl = __uint_as_float(wa[e] << 16), wh = __uint_as_float(wa[e] & 0xffff0000u);
        za = fmaf(__uint_as_float(xa[e] << 16), wl, za); za = fmaf(__uint_as_float(xa[e] & 0xffff0000u), wh, za);
        zb = fmaf(__uint_as_float(xb[e] << 16), wl, zb); zb = fmaf(__uint_as_float(xb[e] & 0xffff0000u), wh, zb);
      }
#pragma unroll
      for (int o = 16; o > 0; o >>= 1) { za += __shfl_xor_sync(0xffffffffu, za, o); zb += __shfl_xor_sync(0xffffffffu, zb, o); }
      if (lane < 2) asm volatile("st.shared.f32 [%0], %1;" ::"r"(sbase + OFF_GST + (warp - 8) * 8 + lane * 4), "f"(1.f / (1.f + __expf(-(lane ? zb : za)))) : "memory");
      fence_async_smem();
      named_bar<6>(256);
      if (tid == 256) {
        bulk_store(&g_gate[rb * 128 + j * 16], sbase + OFF_GST, 64);
        bulk_commit(); bulk_wait_all();
        flag_add(&g_flag_g[rb * FS]);
        flag_wait(&g_flag_g[rb * FS], ep1 * 8, t0);
        fence_async_global();
        mbar_expect_tx(bars + 8 * BAR_GIN, 512);
        bulk_load(sbase + OFF_GIN, &g_gate[rb * 128], 512, bars + 8 * BAR_GIN);
        TR(10);
      }
      __syncwarp();
    }
    mbar_wait(bars + 8 * (BAR_QRDY + aw), 0, t0);
    asm volatile("setmaxnreg.inc.sync.aligned.u32 96;");
    attention(sbase, aw, warp & 3, lane, rb, t0);
    if (tid == 256) TR(3);
  } else {
    asm volatile("setmaxnreg.dec.sync.aligned.u32 32;");
    if (warp == 16) {
      __syncwarp();
      cluster_wait();
      if (lane == 0) {
        int bi = 2; uint32_t bph = 1;
        const int nb = 32 + on + 4;
        for (int eb = 2; eb < nb; eb++) {
          if (eb == 4 || eb == 6) {
            const int ea = eb >> 1;
            mbar_expect_tx(bars + 8 * (BAR_FULLA + 1 + ea), 16384);
            tma_load_2d(sbase + OFF_A + (1 + ea) * SLOT, &P.tmX, ea * 64, rb * 128, bars + 8 * (BAR_FULLA + 1 + ea));
          }
          const uint32_t fb = bars + 8 * (BAR_FULLB + bi), dst = sbase + OFF_B + bi * SLOT + rank * 8192;
          mbar_wait(bars + 8 * (BAR_EMPTYB + bi), bph, t0);
          if (eb < 16) {
            mbar_expect_tx(fb, typeB ? 12288 : 16384);
            tma_load_3d_mc(dst, &P.tmWqkv, 64 * j, eb * 32 + rank * 16, 0, fb);
            if (!typeB) tma_load_3d_mc(dst + 6144, &P.tmW1a, 0, eb * 32 + rank * 16, 24 + (j >> 1), fb);
          }
          else if (eb < 32) { mbar_expect_tx(fb, 12288); tma_load_3d_mc(dst, &P.tmW1b, 0, (eb - 16) * 32 + rank * 16, 3 * j, fb); }
          else if (eb < 32 + on) { int ow; const int ch = oh_chunk(j, eb - 32, ow); mbar_expect_tx(fb, 16384); tma_load_3d_mc(dst, &P.tmW2, 0, ch * 64 + rank * 32, (j >> 1) * 2, fb); }
          else { mbar_expect_tx(fb, 16384); tma_load_4d_mc(dst, &P.tmWo, 64 * j, 0, eb - 32 - on, rank * 4, fb); }
          if (++bi == NB) { bi = 0; bph ^= 1; }
          if (eb == PFAT) {
            const int b = blockIdx.x;
            l2_prefetch((const uint8_t*)P.w1 + b * 14336, 14336);
            l2_prefetch((const uint8_t*)P.w2 + b * 14336, 14336);
            l2_prefetch((const uint8_t*)P.wo + b * 4096, 4096);
          }
        }
      }
    } else if (warp == 17) {
      cluster_wait();
      if (lane == 0) {
        for (int ea = 1; ea < 5; ea++) mbar_arrive(bars + 8 * (BAR_EMPTYA + ea));
        uint32_t aph = 0xE1;
        const int na = 16 + on + 8;
        unsigned ready = 0;
        for (int ea = 4; ea < na; ea++) {
          const int ai = a_slot(ea, 20 + on);
          const uint32_t fb = bars + 8 * (BAR_FULLA + ai), dst = sbase + OFF_A + ai * SLOT;
          int ch = ea & 7, need = -1;
          if (ea >= 16 + on) { need = 8 + ea - 16 - on; ch = 20 + need; }
          else if (ea >= 19) ch = oh_chunk(j, ea - 16, need);
          if (need >= 0 && !((ready >> need) & 1)) {
            const unsigned* fp = need < 8 ? &g_flag_h[rb * 8 * FS] : need < 16 ? &g_flag_o[rb * 8 * FS] : &g_flag_e[rb * 8 * FS];
            const unsigned tgt = (need & 8) ? ep1 * 4 : ep1;
            do {
              unsigned v[8];
#pragma unroll
              for (int i = 0; i < 8; i++) v[i] = ld_relaxed(fp + i * FS);
#pragma unroll
              for (int i = 0; i < 8; i++) if ((int)(v[i] - tgt) >= 0) ready |= 1u << (i + (need & 24));
            } while (!((ready >> need) & 1) && clk32() - t0 < TIMEOUT);
            fence_async_global();
          }
          mbar_wait(bars + 8 * (BAR_EMPTYA + ai), (aph >> ai) & 1, t0);
          if (ea >= 16 && ea < 19) mbar_arrive(fb);
          else {
            mbar_arrive(bars + 8 * (BAR_EMPTYA + ai));
            mbar_expect_tx(fb, 16384);
            tma_load_2d(dst, ea < 16 ? &P.tmX : &P.tmHO, ch * 64, rb * 128, fb);
          }
          TR(24 + ea);
          aph ^= 1u << ai;
        }
      }
    } else {
      const int wg = warp - 18;
      cluster_wait();
      if (lane == 0 && wg == 0) {
        const uint32_t stg = bars + 8 * BAR_STG;
        mbar_wait(stg, 0, t0);
        for (int hh = 0; hh < 4; hh++) bulk_store(g_kv + ((size_t)(4 * j + hh) * SEQ + rb * 128) * 64, sbase + OFF_KV + hh * 8192, 8192);
        bulk_commit(); bulk_wait_all();
        flag_add(&g_flag_kv[(rb * 8 + j) * FS]);
        TR(21);
        if (!typeB) {
          mbar_wait(bars + 8 * BAR_STE, 0, t0);
          tma_store_2d(&P.tmHO, (24 + (j >> 1)) * 64, rb * 128, sbase + OFF_KV + 32768);
          bulk_commit(); bulk_wait_all();
          flag_add(&g_flag_e[(rb * 8 + j) * FS]);
        }
        mbar_arrive(bars + 8 * BAR_KVOK);
        mbar_wait(stg, 1, t0);
        for (int i = 0; i < 3; i++) tma_store_2d(&P.tmHO, (3 * j + i) * 64, rb * 128, sbase + OFF_A + (1 + i) * SLOT);
        bulk_commit(); bulk_wait_all();
        flag_add(&g_flag_h[(rb * 8 + j) * FS]);
        for (int i = 0; i < 3; i++) mbar_arrive(bars + 8 * (BAR_EMPTYA + 1 + i));
        TR(22);
        {
          const unsigned old = atomicAdd(&g_done, 1u);
          if (old == gridDim.x - 1) { g_done = 0; *(volatile unsigned*)&g_epoch = ep1; }
        }
        mbar_wait(stg, 0, t0);
        bulk_store(g_part + (size_t)(rb * 8 + (j ^ 1)) * 16384, sbase + OFF_B + ((30 + on) % NB) * SLOT, 16384);
        bulk_commit(); bulk_wait_all();
        flag_add(&g_flag_p[(rb * 8 + (j ^ 1)) * FS]);
        TR(23);
        flag_wait(&g_flag_p[(rb * 8 + j) * FS], ep1, t0);
        fence_async_global();
        mbar_expect_tx(bars + 8 * BAR_PIN, 16384);
        bulk_load(sbase + OFF_B + ((31 + on) % NB) * SLOT, g_part + (size_t)(rb * 8 + j) * 16384, 16384, bars + 8 * BAR_PIN);
      } else if (lane == 0) {
        const int nblk = rb >= 2 ? 3 : rb + 1;
        const uint32_t kvbytes = nblk * 8192;
        const uint8_t* kvsrc = g_kv + ((size_t)(4 * j) * SEQ + (rb + 1 - nblk) * 128) * 64;
        const uint32_t kvdst = sbase + OFF_KV + (3 - nblk) * 8192;
        {
          const unsigned* f0 = &g_flag_kv[(rb * 8 + j) * FS];
          const unsigned* f1 = rb >= 1 ? f0 - 8 * FS : f0;
          const unsigned* f2 = rb >= 2 ? f0 - 16 * FS : f0;
          unsigned v0, v1, v2;
          do { v0 = ld_relaxed(f0); v1 = ld_relaxed(f1); v2 = ld_relaxed(f2); }
          while (((int)(v0 - ep1) < 0 || (int)(v1 - ep1) < 0 || (int)(v2 - ep1) < 0) && clk32() - t0 < TIMEOUT);
        }
        TR(11);
        mbar_wait(bars + 8 * BAR_GIN, 0, t0);
        fence_async_global();
        mbar_expect_tx(bars + 8 * BAR_KVFULL, kvbytes);
        bulk_load(kvdst, kvsrc, kvbytes, bars + 8 * BAR_KVFULL);
        mbar_wait(bars + 8 * BAR_KVOK, 0, t0);
        mbar_expect_tx(bars + 8 * (BAR_KVFULL + 1), kvbytes);
        bulk_load(kvdst + KVBUF, kvsrc + (size_t)SEQ * 64, kvbytes, bars + 8 * (BAR_KVFULL + 1));
        for (int hh = 0; hh < 4; hh++) {
          for (int aw = 0; aw < 2; aw++) {
            mbar_wait(bars + 8 * (BAR_OST + aw), hh & 1, t0);
            tma_store_2d(&P.tmOs, DFF + hh * 128 + j * 16, rb * 128 + aw * 64, sbase + OFF_A + aw * 8192 + hh * 2048);
          }
          bulk_commit();
          if (hh < 2) {
            mbar_wait(bars + 8 * (BAR_KVEMPTY + hh), 0, t0);
            mbar_expect_tx(bars + 8 * (BAR_KVFULL + hh), kvbytes);
            bulk_load(kvdst + hh * KVBUF, kvsrc + (size_t)(hh + 2) * SEQ * 64, kvbytes, bars + 8 * (BAR_KVFULL + hh));
          }
          bulk_wait_all();
          flag_add(&g_flag_o[(rb * 8 + hh * 2 + (j >> 2)) * FS]);
          TR(12 + hh);
        }
      }
    }
  }
}

typedef CUresult (*EncodeFn)(CUtensorMap*, CUtensorMapDataType, cuuint32_t, void*, const cuuint64_t*, const cuuint64_t*, const cuuint32_t*,
                             const cuuint32_t*, CUtensorMapInterleave, CUtensorMapSwizzle, CUtensorMapL2promotion, CUtensorMapFloatOOBfill);

void make_map(EncodeFn enc, CUtensorMap* m, const void* ptr, int rank, const cuuint64_t* dims, const cuuint64_t* strides, const cuuint32_t* box,
              CUtensorMapSwizzle sw = CU_TENSOR_MAP_SWIZZLE_128B) {
  cuuint32_t es[4] = {1, 1, 1, 1};
  enc(m, CU_TENSOR_MAP_DATA_TYPE_BFLOAT16, rank, const_cast<void*>(ptr), dims, strides, box, es, CU_TENSOR_MAP_INTERLEAVE_NONE, sw,
      CU_TENSOR_MAP_L2_PROMOTION_L2_256B, CU_TENSOR_MAP_FLOAT_OOB_FILL_NONE);
}

}

extern "C" void kernel_launch(void* const* d_in, const int* in_sizes, int n_in, void* d_out, int out_size) {
  (void)in_sizes; (void)n_in; (void)out_size;
  static EncodeFn enc = nullptr;
  static void* ho_ptr = nullptr;
  if (!enc) {
    void* fn = nullptr; cudaDriverEntryPointQueryResult st;
    cudaGetDriverEntryPoint("cuTensorMapEncodeTiled", &fn, cudaEnableDefault, &st);
    enc = (EncodeFn)fn;
    cudaGetSymbolAddress(&ho_ptr, g_ho);
    cudaFuncSetAttribute(fused_kernel, cudaFuncAttributeMaxDynamicSharedMemorySize, SMEM_BYTES);
  }
  const __nv_bfloat16* x = (const __nv_bfloat16*)d_in[0];
  const __nv_bfloat16* wqkv = (const __nv_bfloat16*)d_in[1];
  const __nv_bfloat16* wo = (const __nv_bfloat16*)d_in[2];
  const __nv_bfloat16* w1 = (const __nv_bfloat16*)d_in[4];
  const __nv_bfloat16* w2 = (const __nv_bfloat16*)d_in[5];
  const __nv_bfloat16* gate_w = (const __nv_bfloat16*)d_in[6];
  Params P;
  { cuuint64_t d[2] = {DM, SEQ}, s[1] = {DM * 2}; cuuint32_t b[2] = {64, 128}; make_map(enc, &P.tmX, x, 2, d, s, b); }
  { cuuint64_t d[3] = {512, 512, 3}, s[2] = {1536 * 2, 512 * 2}; cuuint32_t b[3] = {64, 16, 3}; make_map(enc, &P.tmWqkv, wqkv, 3, d, s, b); }
  { cuuint64_t d[3] = {64, 512, 28}, s[2] = {DFF * 2, 128}; cuuint32_t b[3] = {64, 16, 1}; make_map(enc, &P.tmW1a, w1, 3, d, s, b);
    b[2] = 3; make_map(enc, &P.tmW1b, w1, 3, d, s, b); }
  { cuuint64_t d[3] = {64, DFF, 8}, s[2] = {DM * 2, 128}; cuuint32_t b[3] = {64, 32, 2}; make_map(enc, &P.tmW2, w2, 3, d, s, b); }
  { cuuint64_t d[4] = {DM, 16, 4, 8}, s[3] = {DM * 2, 16 * DM * 2, 64 * DM * 2}; cuuint32_t b[4] = {64, 16, 1, 4}; make_map(enc, &P.tmWo, wo, 4, d, s, b); }
  { cuuint64_t d[2] = {KHO, SEQ}, s[1] = {KHO * 2}; cuuint32_t b[2] = {64, 128}; make_map(enc, &P.tmHO, ho_ptr, 2, d, s, b);
    b[1] = 64; b[0] = 16; make_map(enc, &P.tmOs, ho_ptr, 2, d, s, b, CU_TENSOR_MAP_SWIZZLE_NONE); }
  P.x = x; P.gate_w = gate_w; P.w1 = w1; P.w2 = w2; P.wo = wo; P.wqkv = wqkv; P.out = (__nv_bfloat16*)d_out;
  fused_kernel<<<128, 640, SMEM_BYTES>>>(P);
}
```

```cpp
#include <cuda_runtime.h>
#include <cuda_bf16.h>
#include <cuda.h>
#include <stdint.h>

#define DEVI __device__ __forceinline__

namespace {

constexpr int SEQ = 2048, DM = 512, DFF = 1792, KHO = 2304;
constexpr int NA = 5, NB = 6, SLOT = 16384, KVBUF = 24576;
constexpr int NA2 = 8;
constexpr int OFF_B = 0, OFF_A = NB * SLOT, OFF_KV = OFF_A + NA * SLOT, OFF_BAR = OFF_KV + 2 * KVBUF;
constexpr int OFF_GST = OFF_BAR + 512;
constexpr int OFF_GIN = OFF_BAR + 1024;
constexpr int OFF_NM = OFF_BAR + 1536;
constexpr int SMEM_BYTES = OFF_BAR + 2560;
constexpr uint32_t TIMEOUT = 1u << 28;
#define WAIT_HINT_NS 20000u
#define PFAT 8
#define SH true
#define SHW 0
#define SHG 1
#define PF0 0
#define SHO true
#define SHS 6
constexpr int FS = 8;

constexpr int BAR_FULLA = 0, BAR_EMPTYA = BAR_FULLA + NA2, BAR_FULLB = BAR_EMPTYA + NA2, BAR_EMPTYB = BAR_FULLB + NB,
              BAR_KVFULL = BAR_EMPTYB + NB, BAR_KVEMPTY = BAR_KVFULL + 2, BAR_STG = BAR_KVEMPTY + 2, BAR_PIN = BAR_STG + 2, BAR_GATE = BAR_PIN + 1, BAR_STE = BAR_GATE + 2, BAR_PFREE = BAR_STE + 2, BAR_GIN = BAR_PFREE + 1, BAR_OST = BAR_GIN + 1, BAR_QRDY = BAR_OST + 2, BAR_KVOK = BAR_QRDY + 2;

__device__ __align__(1024) uint8_t g_kv[32 * SEQ * 64];
__device__ __align__(1024) __nv_bfloat16 g_ho[SEQ * KHO];
__device__ __align__(1024) uint8_t g_part[128 * 16384];
__device__ __align__(128) float g_gate[SEQ];
__device__ unsigned g_flag_kv[128 * FS], g_flag_h[128 * FS], g_flag_o[128 * FS], g_flag_g[16 * FS], g_flag_p[128 * FS], g_flag_e[128 * FS];
__device__ unsigned g_epoch, g_done;
#define TR(i) do {} while (0)

struct Params {
  CUtensorMap tmX, tmWqkv, tmW1a, tmW1b, tmW2, tmWo, tmHO, tmOs;
  const __nv_bfloat16* x;
  const __nv_bfloat16* gate_w;
  const __nv_bfloat16* w1;
  const __nv_bfloat16* w2;
  const __nv_bfloat16* wo;
  const __nv_bfloat16* wqkv;
  __nv_bfloat16* out;
};

DEVI uint32_t smem_u32(const void* p) { return (uint32_t)__cvta_generic_to_shared(p); }
DEVI uint32_t clk32() { uint32_t c; asm volatile("mov.u32 %0, %%clock;" : "=r"(c)); return c; }
DEVI void mbar_init(uint32_t bar, uint32_t cnt) { asm volatile("mbarrier.init.shared::cta.b64 [%0], %1;" ::"r"(bar), "r"(cnt)); }
DEVI void mbar_expect_tx(uint32_t bar, uint32_t bytes) { asm volatile("mbarrier.arrive.expect_tx.shared::cta.b64 _, [%0], %1;" ::"r"(bar), "r"(bytes) : "memory"); }
DEVI void mbar_arrive(uint32_t bar) { asm volatile("mbarrier.arrive.shared::cta.b64 _, [%0];" ::"r"(bar) : "memory"); }
DEVI void mbar_arrive_cluster(uint32_t bar, uint32_t cta) {
  asm volatile("{ .reg .b32 ra; mapa.shared::cluster.u32 ra, %0, %1; mbarrier.arrive.shared::cluster.b64 _, [ra]; }" ::"r"(bar), "r"(cta) : "memory");
}
DEVI void mbar_wait(uint32_t bar, uint32_t parity, uint32_t t0) {
  asm volatile("{ .reg .pred p; .reg .u32 c;\n"
               "mbarrier.try_wait.parity.shared::cta.b64 p, [%0], %1;\n"
               "@p bra DONE_%=;\n"
               "WAIT_%=:\n"
               "mbarrier.try_wait.parity.shared::cta.b64 p, [%0], %1, %4;\n"
               "@p bra DONE_%=;\n"
               "mov.u32 c, %%clock; sub.u32 c, c, %2; setp.lt.u32 p, c, %3;\n"
               "@p bra WAIT_%=;\n"
               "DONE_%=: }" ::"r"(bar), "r"(parity), "r"(t0), "n"(TIMEOUT), "r"(WAIT_HINT_NS) : "memory");
}
DEVI unsigned ld_relaxed(const unsigned* p) { unsigned v; asm volatile("ld.relaxed.gpu.global.u32 %0, [%1];" : "=r"(v) : "l"(p) : "memory"); return v; }
DEVI void flag_wait(const unsigned* p, unsigned target, uint32_t t0) {
  while ((int)(ld_relaxed(p) - target) < 0) { if (clk32() - t0 > TIMEOUT) break; }
}
DEVI void flag_add(unsigned* p) { asm volatile("red.relaxed.gpu.global.add.u32 [%0], 1;" ::"l"(p) : "memory"); }
DEVI void fence_async_smem() { asm volatile("fence.proxy.async.shared::cta;" ::: "memory"); }
DEVI void fence_async_global() { asm volatile("fence.proxy.async.global;" ::: "memory"); }
DEVI void tma_load_2d(uint32_t dst, const CUtensorMap* m, int c0, int c1, uint32_t bar) {
  asm volatile("cp.async.bulk.tensor.2d.shared::cluster.global.mbarrier::complete_tx::bytes [%0], [%1, {%3, %4}], [%2];" ::"r"(dst), "l"(m), "r"(bar), "r"(c0), "r"(c1) : "memory");
}
DEVI void tma_load_3d(uint32_t dst, const CUtensorMap* m, int c0, int c1, int c2, uint32_t bar) {
  asm volatile("cp.async.bulk.tensor.3d.shared::cluster.global.mbarrier::complete_tx::bytes [%0], [%1, {%3, %4, %5}], [%2];"
               ::"r"(dst), "l"(m), "r"(bar), "r"(c0), "r"(c1), "r"(c2) : "memory");
}
DEVI void tma_load_3d_mc(uint32_t dst, const CUtensorMap* m, int c0, int c1, int c2, uint32_t bar) {
  asm volatile("cp.async.bulk.tensor.3d.shared::cluster.global.mbarrier::complete_tx::bytes.multicast::cluster [%0], [%1, {%3, %4, %5}], [%2], %6;"
               ::"r"(dst), "l"(m), "r"(bar), "r"(c0), "r"(c1), "r"(c2), "h"((uint16_t)3) : "memory");
}
DEVI void tma_load_4d_mc(uint32_t dst, const CUtensorMap* m, int c0, int c1, int c2, int c3, uint32_t bar) {
  asm volatile("cp.async.bulk.tensor.4d.shared::cluster.global.mbarrier::complete_tx::bytes.multicast::cluster [%0], [%1, {%3, %4, %5, %6}], [%2], %7;"
               ::"r"(dst), "l"(m), "r"(bar), "r"(c0), "r"(c1), "r"(c2), "r"(c3), "h"((uint16_t)3) : "memory");
}
DEVI void tma_store_2d(const CUtensorMap* m, int c0, int c1, uint32_t src) {
  asm volatile("cp.async.bulk.tensor.2d.global.shared::cta.bulk_group [%0, {%1, %2}], [%3];" ::"l"(m), "r"(c0), "r"(c1), "r"(src) : "memory");
}
DEVI void bulk_store(void* dst, uint32_t src, uint32_t bytes) {
  asm volatile("cp.async.bulk.global.shared::cta.bulk_group [%0], [%1], %2;" ::"l"(dst), "r"(src), "r"(bytes) : "memory");
}
DEVI void bulk_load(uint32_t dst, const void* src, uint32_t bytes, uint32_t bar) {
  asm volatile("cp.async.bulk.shared::cluster.global.mbarrier::complete_tx::bytes [%0], [%1], %2, [%3];" ::"r"(dst), "l"(src), "r"(bytes), "r"(bar) : "memory");
}
DEVI void bulk_commit() { asm volatile("cp.async.bulk.commit_group;" ::: "memory"); }
DEVI void bulk_wait_all() { asm volatile("cp.async.bulk.wait_group 0;" ::: "memory"); }
DEVI void l2_prefetch(const void* p, uint32_t bytes) { asm volatile("cp.async.bulk.prefetch.L2.global [%0], %1;" ::"l"(p), "r"(bytes) : "memory"); }
DEVI void cluster_arrive() { asm volatile("barrier.cluster.arrive.relaxed.aligned;" ::: "memory"); }
DEVI void cluster_wait() { asm volatile("barrier.cluster.wait.aligned;" ::: "memory"); }
template <int ID> DEVI void named_bar(int n) { asm volatile("bar.sync %0, %1;" ::"n"(ID), "r"(n) : "memory"); }
DEVI void wg_bar(int wg) { if (wg == 0) named_bar<1>(128); else named_bar<2>(128); }
DEVI void wgmma_fence() { asm volatile("wgmma.fence.sync.aligned;" ::: "memory"); }
DEVI void wgmma_commit() { asm volatile("wgmma.commit_group.sync.aligned;" ::: "memory"); }
template <int N> DEVI void wgmma_wait() { asm volatile("wgmma.wait_group.sync.aligned %0;" ::"n"(N) : "memory"); }
template <uint32_t LBO> DEVI uint64_t desc_sw128(uint32_t a16) {
  return ((uint64_t)(0x40000000u | (1024 >> 4)) << 32) | (a16 + ((LBO >> 4) << 16));
}
DEVI uint64_t desc_sw64(uint32_t a16) {
  return ((uint64_t)(0x80000000u | (512 >> 4)) << 32) | (a16 + ((512 >> 4) << 16));
}
DEVI uint32_t pack_bf16(float lo, float hi) { uint32_t r; asm("cvt.rn.bf16x2.f32 %0, %1, %2;" : "=r"(r) : "f"(hi), "f"(lo)); return r; }
DEVI void stsm_x4(uint32_t addr, uint32_t r0, uint32_t r1, uint32_t r2, uint32_t r3) {
  asm volatile("stmatrix.sync.aligned.m8n8.x4.shared.b16 [%0], {%1, %2, %3, %4};" ::"r"(addr), "r"(r0), "r"(r1), "r"(r2), "r"(r3) : "memory");
}
DEVI void sts128(uint32_t addr, uint32_t r0, uint32_t r1, uint32_t r2, uint32_t r3) {
  asm volatile("st.shared.v4.b32 [%0], {%1, %2, %3, %4};" ::"r"(addr), "r"(r0), "r"(r1), "r"(r2), "r"(r3) : "memory");
}
DEVI uint4 lds128(uint32_t addr) {
  uint4 v; asm volatile("ld.shared.v4.b32 {%0, %1, %2, %3}, [%4];" : "=r"(v.x), "=r"(v.y), "=r"(v.z), "=r"(v.w) : "r"(addr) : "memory"); return v;
}
DEVI float ex2(float x) { float y; asm("ex2.approx.ftz.f32 %0, %1;" : "=f"(y) : "f"(x)); return y; }

DEVI void wgmma_ss_n64(float (&d)[32], uint64_t da, uint64_t db) {
  asm volatile("wgmma.mma_async.sync.aligned.m64n64k16.f32.bf16.bf16 {%0, %1, %2, %3, %4, %5, %6, %7, %8, %9, %10, %11, %12, %13, %14, %15, %16, %17, %18, %19, %20, %21, %22, %23, %24, %25, %26, %27, %28, %29, %30, %31}, %32, %33, 1, 1, 1, 0, 1;"
    : "+f"(d[0]), "+f"(d[1]), "+f"(d[2]), "+f"(d[3]), "+f"(d[4]), "+f"(d[5]), "+f"(d[6]), "+f"(d[7]), "+f"(d[8]), "+f"(d[9]), "+f"(d[10]), "+f"(d[11]), "+f"(d[12]), "+f"(d[13]), "+f"(d[14]), "+f"(d[15]), "+f"(d[16]), "+f"(d[17]), "+f"(d[18]), "+f"(d[19]), "+f"(d[20]), "+f"(d[21]), "+f"(d[22]), "+f"(d[23]), "+f"(d[24]), "+f"(d[25]), "+f"(d[26]), "+f"(d[27]), "+f"(d[28]), "+f"(d[29]), "+f"(d[30]), "+f"(d[31])
    : "l"(da), "l"(db));
}
DEVI void wgmma_ss_n128(float (&d)[64], uint64_t da, uint64_t db) {
  asm volatile("wgmma.mma_async.sync.aligned.m64n128k16.f32.bf16.bf16 {%0, %1, %2, %3, %4, %5, %6, %7, %8, %9, %10, %11, %12, %13, %14, %15, %16, %17, %18, %19, %20, %21, %22, %23, %24, %25, %26, %27, %28, %29, %30, %31, %32, %33, %34, %35, %36, %37, %38, %39, %40, %41, %42, %43, %44, %45, %46, %47, %48, %49, %50, %51, %52, %53, %54, %55, %56, %57, %58, %59, %60, %61, %62, %63}, %64, %65, 1, 1, 1, 0, 1;"
    : "+f"(d[0]), "+f"(d[1]), "+f"(d[2]), "+f"(d[3]), "+f"(d[4]), "+f"(d[5]), "+f"(d[6]), "+f"(d[7]), "+f"(d[8]), "+f"(d[9]), "+f"(d[10]), "+f"(d[11]), "+f"(d[12]), "+f"(d[13]), "+f"(d[14]), "+f"(d[15]), "+f"(d[16]), "+f"(d[17]), "+f"(d[18]), "+f"(d[19]), "+f"(d[20]), "+f"(d[21]), "+f"(d[22]), "+f"(d[23]), "+f"(d[24]), "+f"(d[25]), "+f"(d[26]), "+f"(d[27]), "+f"(d[28]), "+f"(d[29]), "+f"(d[30]), "+f"(d[31]), "+f"(d[32]), "+f"(d[33]), "+f"(d[34]), "+f"(d[35]), "+f"(d[36]), "+f"(d[37]), "+f"(d[38]), "+f"(d[39]), "+f"(d[40]), "+f"(d[41]), "+f"(d[42]), "+f"(d[43]), "+f"(d[44]), "+f"(d[45]), "+f"(d[46]), "+f"(d[47]), "+f"(d[48]), "+f"(d[49]), "+f"(d[50]), "+f"(d[51]), "+f"(d[52]), "+f"(d[53]), "+f"(d[54]), "+f"(d[55]), "+f"(d[56]), "+f"(d[57]), "+f"(d[58]), "+f"(d[59]), "+f"(d[60]), "+f"(d[61]), "+f"(d[62]), "+f"(d[63])
    : "l"(da), "l"(db));
}
DEVI void wgmma_qk64(float (&d)[32], uint32_t a0, uint32_t a1, uint32_t a2, uint32_t a3, uint64_t db) {
  asm volatile("wgmma.mma_async.sync.aligned.m64n64k16.f32.bf16.bf16 {%0, %1, %2, %3, %4, %5, %6, %7, %8, %9, %10, %11, %12, %13, %14, %15, %16, %17, %18, %19, %20, %21, %22, %23, %24, %25, %26, %27, %28, %29, %30, %31}, {%32, %33, %34, %35}, %36, 0, 1, 1, 0;"
    : "=f"(d[0]), "=f"(d[1]), "=f"(d[2]), "=f"(d[3]), "=f"(d[4]), "=f"(d[5]), "=f"(d[6]), "=f"(d[7]), "=f"(d[8]), "=f"(d[9]), "=f"(d[10]), "=f"(d[11]), "=f"(d[12]), "=f"(d[13]), "=f"(d[14]), "=f"(d[15]), "=f"(d[16]), "=f"(d[17]), "=f"(d[18]), "=f"(d[19]), "=f"(d[20]), "=f"(d[21]), "=f"(d[22]), "=f"(d[23]), "=f"(d[24]), "=f"(d[25]), "=f"(d[26]), "=f"(d[27]), "=f"(d[28]), "=f"(d[29]), "=f"(d[30]), "=f"(d[31])
    : "r"(a0), "r"(a1), "r"(a2), "r"(a3), "l"(db));
}
DEVI void wgmma_pv(float (&d)[8], uint32_t a0, uint32_t a1, uint32_t a2, uint32_t a3, uint64_t db) {
  asm volatile("wgmma.mma_async.sync.aligned.m64n16k16.f32.bf16.bf16 {%0, %1, %2, %3, %4, %5, %6, %7}, {%8, %9, %10, %11}, %12, 1, 1, 1, 1;"
    : "+f"(d[0]), "+f"(d[1]), "+f"(d[2]), "+f"(d[3]), "+f"(d[4]), "+f"(d[5]), "+f"(d[6]), "+f"(d[7])
    : "r"(a0), "r"(a1), "r"(a2), "r"(a3), "l"(db));
}
DEVI void wgmma_pv0(float (&d)[8], uint32_t a0, uint32_t a1, uint32_t a2, uint32_t a3, uint64_t db) {
  asm volatile("wgmma.mma_async.sync.aligned.m64n16k16.f32.bf16.bf16 {%0, %1, %2, %3, %4, %5, %6, %7}, {%8, %9, %10, %11}, %12, 0, 1, 1, 1;"
    : "=f"(d[0]), "=f"(d[1]), "=f"(d[2]), "=f"(d[3]), "=f"(d[4]), "=f"(d[5]), "=f"(d[6]), "=f"(d[7])
    : "r"(a0), "r"(a1), "r"(a2), "r"(a3), "l"(db));
}

template <int N> struct Acc { float a[64]; float b[(N - 128) / 2]; DEVI float& operator[](int i) { return i < 64 ? a[i] : b[i - 64]; } };
template <> struct Acc<128> { float a[64]; DEVI float& operator[](int i) { return a[i]; } };
template <int N> DEVI void wgmma_ss(Acc<N>& d, uint64_t da, uint64_t db) {
  wgmma_ss_n128(d.a, da, db);
  if constexpr (N == 192) wgmma_ss_n64(d.b, da, db + 256);
  if constexpr (N == 256) wgmma_ss_n128(d.b, da, db + 256);
}

DEVI int oh_chunk(int j, int i, int& need) {
  if (i >= 3 && i < 5) { const int e = (j & 1) * 2 + i - 3; need = 16 + 2 * e; return 24 + e; }
  if (i >= 5) i -= 2;
  int o, r;
  if (i >= 12) { o = (j + 5) & 7; r = i - 11; }
  else { const int g = i / 3; o = (j + 2 * g) & 7; r = i - 3 * g; }
  need = o;
  return 3 * o + r;
}

DEVI int a_slot(int e, int) { return 1 + (e & 3); }

struct Ctx {
  uint32_t sbase, bars, peer, t0, a16, b16;
  int wg, lane;
  int ai, bi; uint32_t aph, bph;
  int brem, ae;
  int pa, pb;
};

DEVI void release_prev(Ctx& c) {
  if (c.pb >= 0) {
    if (c.lane == 0) mbar_arrive(c.bars + 8 * (BAR_EMPTYB + c.pb));
    if (c.lane == 1) mbar_arrive_cluster(c.bars + 8 * (BAR_EMPTYB + c.pb), c.peer);
  }
  if (c.pa >= 0 && c.lane == 2) mbar_arrive(c.bars + 8 * (BAR_EMPTYA + c.pa));
}

DEVI void gemm_wait(Ctx& c) {
  asm volatile("{ .reg .pred p, q; .reg .u32 c;\n"
               "mbarrier.try_wait.parity.shared::cta.b64 p, [%0], %1;\n"
               "mbarrier.try_wait.parity.shared::cta.b64 q, [%2], %3;\n"
               "and.pred p, p, q;\n"
               "@p bra DONE_%=;\n"
               "WAIT_%=:\n"
               "mbarrier.try_wait.parity.shared::cta.b64 p, [%0], %1, %6;\n"
               "mbarrier.try_wait.parity.shared::cta.b64 q, [%2], %3, %6;\n"
               "and.pred p, p, q;\n"
               "@p bra DONE_%=;\n"
               "mov.u32 c, %%clock; sub.u32 c, c, %4; setp.lt.u32 p, c, %5;\n"
               "@p bra WAIT_%=;\n"
               "DONE_%=: }" ::"r"(c.bars + 8 * (BAR_FULLA + c.ai)), "r"((c.aph >> c.ai) & 1), "r"(c.bars + 8 * (BAR_FULLB + c.bi)), "r"(c.bph), "r"(c.t0),
               "n"(TIMEOUT), "r"(WAIT_HINT_NS) : "memory");
}
template <int N, bool SHALLOW>
DEVI void gemm_group(Acc<N>& acc, Ctx& c, int g, int& npa, int& npb) {
  const uint32_t a16 = c.a16 + c.ai * (SLOT >> 4);
  const uint32_t b16 = c.b16 + c.bi * (SLOT >> 4);
  bool adv;
  if constexpr (N >= 192) {
    const uint32_t a2 = a16 + (g & 1) * 4;
    wgmma_ss<N>(acc, desc_sw128<16>(a2), desc_sw128<2048>(b16));
    if (SHALLOW) { wgmma_commit(); wgmma_wait<SHW>(); }
    wgmma_ss<N>(acc, desc_sw128<16>(a2 + 2), desc_sw128<2048>(b16 + 512));
    adv = g & 1;
  } else {
#pragma unroll
    for (int s = 0; s < 4; s++) {
      wgmma_ss<N>(acc, desc_sw128<16>(a16 + s * 2), desc_sw128<4096>(b16 + (s >> 1) * 512 + (s & 1) * 128));
      if (SHALLOW && s < 3 && (SHG == 1 || s == 1)) { wgmma_commit(); wgmma_wait<SHW>(); }
    }
    adv = true;
  }
  wgmma_commit();
  npb = c.brem > 0 ? c.bi : -1;
  c.brem--;
  if (++c.bi == NB) { c.bi = 0; c.bph ^= 1; }
  npa = -1;
  if (adv) { npa = c.ai; c.aph ^= 1u << c.ai; c.ae++; c.ai = 1 + (c.ae & 3); }
}

template <int N, bool SHALLOW = false>
DEVI void bare_groups(Acc<N>& acc, Ctx& c, int g0, int g1) {
  for (int g = g0; g < g1; g++) {
    int npa, npb;
    gemm_wait(c);
    wgmma_fence();
    gemm_group<N, SHALLOW>(acc, c, g, npa, npb);
    wgmma_wait<SHALLOW ? SHW : 1>();
    release_prev(c);
    c.pa = npa; c.pb = npb;
  }
}
DEVI void drain(Ctx& c) {
  wgmma_wait<0>();
  release_prev(c);
  c.pa = c.pb = -1;
}

constexpr float SC = 0.25f * 1.4426950408889634f;

#define ONCE _Pragma("unroll 1") for (unsigned once_ = 0; once_ < gridDim.y; once_++)

struct Gate { float g0, g1; };

DEVI void kill32(float (&S)[32]) {
#pragma unroll
  for (int i = 0; i < 32; i++) S[i] = __int_as_float(0xff800000);
}
DEVI void row_max(const float (&S)[32], float& x0, float& x1) {
  float y0 = S[1], y1 = S[3];
  x0 = fmaxf(x0, S[0]); x1 = fmaxf(x1, S[2]);
#pragma unroll
  for (int n = 1; n < 8; n++) {
    x0 = fmaxf(x0, S[4 * n]); y0 = fmaxf(y0, S[4 * n + 1]); x1 = fmaxf(x1, S[4 * n + 2]); y1 = fmaxf(y1, S[4 * n + 3]);
  }
  x0 = fmaxf(x0, y0); x1 = fmaxf(x1, y1);
}
DEVI void quad_max(float& x0, float& x1) {
  x0 = fmaxf(x0, __shfl_xor_sync(0xffffffffu, x0, 1)); x1 = fmaxf(x1, __shfl_xor_sync(0xffffffffu, x1, 1));
  x0 = fmaxf(x0, __shfl_xor_sync(0xffffffffu, x0, 2)); x1 = fmaxf(x1, __shfl_xor_sync(0xffffffffu, x1, 2));
}
DEVI void exp32(const float (&S)[32], float (&E)[32], float n0, float n1, float (&l)[4]) {
#pragma unroll
  for (int i = 0; i < 32; i++) { E[i] = ex2(fmaf(S[i], SC, (i & 2) ? n1 : n0)); l[i & 3] += E[i]; }
}
DEVI void pack32(const float (&E)[32], uint32_t (&P)[16]) {
#pragma unroll
  for (int i = 0; i < 16; i++) P[i] = pack_bf16(E[2 * i], E[2 * i + 1]);
}
template <bool FIRST> DEVI void pv4(float (&O)[8], const uint32_t (&P)[16], uint32_t v16) {
  if (FIRST) wgmma_pv0(O, P[0], P[1], P[2], P[3], desc_sw64(v16)); else wgmma_pv(O, P[0], P[1], P[2], P[3], desc_sw64(v16));
#pragma unroll
  for (int k = 1; k < 4; k++) wgmma_pv(O, P[4 * k], P[4 * k + 1], P[4 * k + 2], P[4 * k + 3], desc_sw64(v16 + k * 64));
}
DEVI bool wg_any(int wg, bool v) {
  uint32_t r;
  if (wg == 0) asm volatile("{ .reg .pred p, q; setp.ne.u32 p, %1, 0; bar.red.or.pred q, 4, 128, p; selp.u32 %0, 1, 0, q; }" : "=r"(r) : "r"((uint32_t)v) : "memory");
  else asm volatile("{ .reg .pred p, q; setp.ne.u32 p, %1, 0; bar.red.or.pred q, 5, 128, p; selp.u32 %0, 1, 0, q; }" : "=r"(r) : "r"((uint32_t)v) : "memory");
  return r != 0;
}
DEVI void get_gate(Gate& g, uint32_t sbase, int row16, int lane, uint32_t t0) {
  mbar_wait(sbase + OFF_BAR + 8 * BAR_GIN, 0, t0);
  const uint32_t a = sbase + OFF_GIN + (row16 * 16 + (lane >> 2)) * 4;
  asm volatile("ld.shared.f32 %0, [%1];" : "=f"(g.g0) : "r"(a) : "memory");
  asm volatile("ld.shared.f32 %0, [%1];" : "=f"(g.g1) : "r"(a + 32) : "memory");
}

DEVI void attention(uint32_t sbase, int aw, int wi, int lane, int rb, uint32_t t0) {
  const uint32_t bars = sbase + OFF_BAR;
  const uint32_t kvb = ((sbase & 0x3FFFF) + OFF_KV + aw * 4096) >> 4;
  const int cmin = 4 - 2 * rb - aw;
  const int rowc = wi * 16 + (lane >> 2) - (lane & 3) * 2;
  const uint32_t qst = sbase + OFF_A + aw * 8192;
  const float NINF = __int_as_float(0xff800000);
  const int tlo = max(cmin, 1);
#pragma unroll 1
  for (int h = 0; h < 4; h++) {
    const uint32_t kb = kvb + (h & 1) * (KVBUF >> 4);
    const uint4 q = lds128(qst + h * 2048 + (wi * 32 + lane) * 16);
    float O[8], l0, l1;
    uint32_t nm;
    asm volatile("ld.shared.u32 %0, [%1];" : "=r"(nm) : "r"(sbase + OFF_NM + ((aw * 4 + wi) * 32 + (lane & 28) + h) * 4) : "memory");
    float n0 = __uint_as_float(nm << 16), n1 = __uint_as_float(nm & 0xffff0000u);
    mbar_wait(bars + 8 * (BAR_KVFULL + (h & 1)), h >> 1, t0);
#pragma unroll 1
    for (int attempt = 0; attempt < 2; attempt++) {
      float l[4] = {0.f, 0.f, 0.f, 0.f};
      uint32_t P[16];
      {
        float S[32], F[32];
        wgmma_fence();
        wgmma_qk64(S, q.x, q.y, q.z, q.w, desc_sw64(kb + 4 * 256));
        wgmma_qk64(F, q.x, q.y, q.z, q.w, desc_sw64(kb));
        wgmma_commit();
        wgmma_wait<0>();
        for (int r = 0; r < (cmin > 0 ? 1 : 0); r++) kill32(F);
        float M[32];
#pragma unroll
        for (int i = 0; i < 32; i++) M[i] = ((i >> 2) * 8 + (i & 1) > rowc + (i & 2) * 4) ? F[i] : S[i];
        for (int r = 0; r < attempt; r++) {
          row_max(M, n0, n1);
          quad_max(n0, n1);
          n0 *= -SC; n1 *= -SC;
        }
        exp32(M, M, n0, n1, l);
        pack32(M, P);
        uint32_t PF[16];
#pragma unroll
        for (int i = 0; i < 16; i++) {
          const int col = (i >> 1) * 8, r = rowc + (i & 1) * 8;
          const uint32_t m = (col > r ? 0xFFFFu : 0u) | (col + 1 > r ? 0xFFFF0000u : 0u);
          PF[i] = P[i] & m; P[i] &= ~m;
        }
        wgmma_fence();
        pv4<true>(O, PF, kb + 2);
        wgmma_commit();
        wgmma_wait<0>();
      }
      int t = 3;
#pragma unroll 1
      for (; t >= tlo; t--) {
        float S[32];
        wgmma_fence();
        wgmma_qk64(S, q.x, q.y, q.z, q.w, desc_sw64(kb + t * 256));
        wgmma_commit();
        pv4<false>(O, P, kb + (t + 1) * 256 + 2);
        wgmma_commit();
        wgmma_wait<1>();
        ONCE { exp32(S, S, n0, n1, l); }
        wgmma_wait<0>();
        pack32(S, P);
      }
      wgmma_fence();
      pv4<false>(O, P, kb + (t + 1) * 256 + 2);
      wgmma_commit();
      l0 = l[0] + l[1]; l1 = l[2] + l[3];
      l0 += __shfl_xor_sync(0xffffffffu, l0, 1); l1 += __shfl_xor_sync(0xffffffffu, l1, 1);
      l0 += __shfl_xor_sync(0xffffffffu, l0, 2); l1 += __shfl_xor_sync(0xffffffffu, l1, 2);
      const bool redo = wg_any(aw, attempt == 0 && !(l0 > 1e-6f && l0 < 1e18f && l1 > 1e-6f && l1 < 1e18f));
      wgmma_wait<0>();
      if (!redo) break;
      n0 = NINF; n1 = NINF;
#pragma unroll 1
      for (int u = 3; u >= tlo; u--) {
        float S[32];
        wgmma_fence();
        wgmma_qk64(S, q.x, q.y, q.z, q.w, desc_sw64(kb + u * 256));
        wgmma_commit();
        wgmma_wait<0>();
        row_max(S, n0, n1);
      }
    }
    if (lane == 0) mbar_arrive(bars + 8 * (BAR_KVEMPTY + (h & 1)));
    Gate g;
    get_gate(g, sbase, aw * 4 + wi, lane, t0);
    const float c0 = __fdividef(g.g0, l0), c1 = __fdividef(g.g1, l1);
    const int mi = lane >> 3;
    const int srow = wi * 16 + (lane & 7) + 8 * (mi & 1);
    stsm_x4(qst + h * 2048 + srow * 32 + (mi >> 1) * 16, pack_bf16(O[0] * c0, O[1] * c0), pack_bf16(O[2] * c1, O[3] * c1),
            pack_bf16(O[4] * c0, O[5] * c0), pack_bf16(O[6] * c1, O[7] * c1));
    fence_async_smem();
    __syncwarp();
    if (lane == 0) mbar_arrive(bars + 8 * (BAR_OST + aw));
  }
}

template <int CH, int N>
DEVI void store_h_chunk(Acc<N>& acc, uint32_t base  , int lane, float s0, float s1) {
  const int mi = lane >> 3;
#pragma unroll
  for (int tp = 0; tp < 4; tp++) {
    const int t = CH * 8 + tp * 2;
    const uint32_t r0 = pack_bf16(fmaxf(acc[4 * t + 0], 0.f) * s0, fmaxf(acc[4 * t + 1], 0.f) * s0);
    const uint32_t r1 = pack_bf16(fmaxf(acc[4 * t + 2], 0.f) * s1, fmaxf(acc[4 * t + 3], 0.f) * s1);
    const uint32_t r2 = pack_bf16(fmaxf(acc[4 * t + 4], 0.f) * s0, fmaxf(acc[4 * t + 5], 0.f) * s0);
    const uint32_t r3 = pack_bf16(fmaxf(acc[4 * t + 6], 0.f) * s1, fmaxf(acc[4 * t + 7], 0.f) * s1);
    stsm_x4(base + (((tp * 2 + (mi >> 1)) ^ (lane & 7)) << 4), r0, r1, r2, r3);
  }
}

template <int N>
DEVI void phase_q(Ctx& c, int warp) {
  Acc<N> acc;
#pragma unroll
  for (int i = 0; i < N / 2; i++) acc[i] = 0.f;
  bare_groups<N>(acc, c, 0, 16);
  drain(c);
  const int lane = c.lane, mi = lane >> 3;
  const int row = warp * 16 + (lane & 7) + 8 * (mi & 1);
  const int sw = (row >> 1) & 3;
#pragma unroll
  for (int hh = 0; hh < 4; hh++) {
    const uint32_t base = c.sbase + OFF_KV + hh * 8192 + row * 64;
#pragma unroll
    for (int kv = 0; kv < 2; kv++) {
      const int t = 8 + kv * 8 + 2 * hh;
      stsm_x4(base + (((kv * 2 + (mi >> 1)) ^ sw) << 4),
              pack_bf16(acc[4 * t + 0], acc[4 * t + 1]), pack_bf16(acc[4 * t + 2], acc[4 * t + 3]),
              pack_bf16(acc[4 * t + 4], acc[4 * t + 5]), pack_bf16(acc[4 * t + 6], acc[4 * t + 7]));
    }
  }
  fence_async_smem();
  __syncwarp();
  if (lane == 0) mbar_arrive(c.bars + 8 * BAR_STG);
#pragma unroll
  for (int hh = 0; hh < 4; hh++)
    sts128(c.sbase + OFF_A + c.wg * 8192 + hh * 2048 + ((warp & 3) * 32 + lane) * 16,
           pack_bf16(acc[8 * hh], acc[8 * hh + 1]), pack_bf16(acc[8 * hh + 2], acc[8 * hh + 3]),
           pack_bf16(acc[8 * hh + 4], acc[8 * hh + 5]), pack_bf16(acc[8 * hh + 6], acc[8 * hh + 7]));
#pragma unroll
  for (int hh = 0; hh < 4; hh++) {
    const int q = 8 * hh, k = 32 + 8 * hh;
    float d0 = acc[q] * acc[k] + acc[q + 1] * acc[k + 1] + acc[q + 4] * acc[k + 4] + acc[q + 5] * acc[k + 5];
    float d1 = acc[q + 2] * acc[k + 2] + acc[q + 3] * acc[k + 3] + acc[q + 6] * acc[k + 6] + acc[q + 7] * acc[k + 7];
    d0 += __shfl_xor_sync(0xffffffffu, d0, 1); d1 += __shfl_xor_sync(0xffffffffu, d1, 1);
    d0 += __shfl_xor_sync(0xffffffffu, d0, 2); d1 += __shfl_xor_sync(0xffffffffu, d1, 2);
    if ((lane & 3) == hh)
      asm volatile("st.shared.u32 [%0], %1;" ::"r"(c.sbase + OFF_NM + (warp * 32 + lane) * 4), "r"(pack_bf16(-d0 * SC, -d1 * SC)) : "memory");
  }
  __syncwarp();
  if (lane == 0) mbar_arrive(c.bars + 8 * (BAR_QRDY + c.wg));
  if constexpr (N == 256) {
    Gate g;
    get_gate(g, c.sbase, warp, lane, c.t0);
    store_h_chunk<3>(acc, c.sbase + OFF_KV + 32768 + row * 128, lane, 1.f - g.g0, 1.f - g.g1);
    fence_async_smem();
    __syncwarp();
    if (lane == 0) mbar_arrive(c.bars + 8 * BAR_STE);
  }
}

DEVI void first_loads(const Params& P, uint32_t sbase, int e, int j, int rb) {
  const uint32_t bars = sbase + OFF_BAR, fb = bars + 8 * (BAR_FULLB + e), fa = bars + 8 * (BAR_FULLA + 1 + e);
  mbar_expect_tx(fa, 16384);
  mbar_expect_tx(fb, (j & 1) ? 12288 : 16384);
  if (e == 0) tma_load_2d(sbase + OFF_A + SLOT, &P.tmX, 0, rb * 128, fa);
#pragma unroll
  for (int r = 0; r < 2; r++) {
    tma_load_3d(sbase + OFF_B + e * SLOT + r * 8192, &P.tmWqkv, 64 * j, e * 32 + r * 16, 0, fb);
    if (!(j & 1)) tma_load_3d(sbase + OFF_B + e * SLOT + r * 8192 + 6144, &P.tmW1a, 0, e * 32 + r * 16, 24 + (j >> 1), fb);
  }
  if (e == 1) tma_load_2d(sbase + OFF_A + 2 * SLOT, &P.tmX, 64, rb * 128, fa);
}

__global__ void __cluster_dims__(2, 1, 1) __launch_bounds__(640, 1) fused_kernel(const __grid_constant__ Params P) {
  extern __shared__ __align__(1024) uint8_t smem_raw[];
  const uint32_t sbase = smem_u32(smem_raw);
  const uint32_t bars = sbase + OFF_BAR;
  const int tid = threadIdx.x, warp = tid >> 5, lane = tid & 31;
  const uint32_t rank = blockIdx.x & 1, peer = rank ^ 1;
  const int j = (blockIdx.x >> 1) & 7, rb = ((blockIdx.x >> 4) << 1) | rank;
  const uint32_t t0 = clk32();

  const int typeB = j & 1;
  if (tid == 544) {
    for (int s = 0; s < NA2; s++) mbar_init(bars + 8 * (BAR_FULLA + s), 1);
    for (int s = 0; s < NB; s++) mbar_init(bars + 8 * (BAR_FULLB + s), 1);
    fence_async_smem();
  } else if (tid < 8) {
    asm volatile("prefetch.tensormap [%0];" ::"l"(&P.tmX + tid) : "memory");
  } else if (tid == 512) {
    for (int s = 0; s < NA2; s++) mbar_init(bars + 8 * (BAR_EMPTYA + s), 9);
    for (int s = 0; s < NB; s++) mbar_init(bars + 8 * (BAR_EMPTYB + s), 16);
  } else if (tid == 576) {
    for (int s = 0; s < 2; s++) { mbar_init(bars + 8 * (BAR_KVFULL + s), 1); mbar_init(bars + 8 * (BAR_KVEMPTY + s), 8); mbar_init(bars + 8 * (BAR_OST + s), 4); mbar_init(bars + 8 * (BAR_QRDY + s), 4); }
    mbar_init(bars + 8 * BAR_STG, 8); mbar_init(bars + 8 * BAR_STE, 8); mbar_init(bars + 8 * BAR_KVOK, 1);
    mbar_init(bars + 8 * BAR_PIN, 1); mbar_init(bars + 8 * BAR_PFREE, 8); mbar_init(bars + 8 * BAR_GIN, 1);
  }
  if (tid >= 512 && lane == 0) asm volatile("fence.mbarrier_init.release.cluster;" ::: "memory");
  const unsigned ep1 = ld_relaxed(&g_epoch) + 1;
  __syncwarp();
  cluster_arrive();
  if (tid == 544) { first_loads(P, sbase, 0, j, rb); first_loads(P, sbase, 1, j, rb); }
  __syncwarp();

  const int on = 12 + 4 * typeB;

  if (warp < 8) {
    asm volatile("setmaxnreg.inc.sync.aligned.u32 160;");
    cluster_wait();
    const int wg = __shfl_sync(0xffffffffu, warp >> 2, 0);
    Ctx c{sbase, bars, peer, t0, ((sbase & 0x3FFFF) + OFF_A + wg * 8192) >> 4, ((sbase & 0x3FFFF) + OFF_B) >> 4, wg, lane, 1, 0, 0u, 0u, 32 + on + 4 - NB, 0, -1, -1};
    if (tid == 0) TR(0);
    if (typeB) phase_q<192>(c, warp);
    else phase_q<256>(c, warp);
    asm volatile("setmaxnreg.dec.sync.aligned.u32 128;");
    if (tid == 0) TR(2);
    {
      Acc<192> acc;
#pragma unroll
      for (int i = 0; i < 96; i++) acc[i] = 0.f;
      bare_groups<192>(acc, c, 0, SHS);
      bare_groups<192, SH>(acc, c, SHS, 16);
      Gate at;
      get_gate(at, sbase, warp, lane, t0);
      drain(c);
      if (tid == 0) TR(1);
      const uint32_t rowoff = (warp * 16 + (lane & 7) + 8 * ((lane >> 3) & 1)) * 128;
      const float s0 = 1.f - at.g0, s1 = 1.f - at.g1;
      constexpr int e0 = 1, e1 = 2, e2 = 3;
      mbar_wait(bars + 8 * (BAR_FULLA + e0), 0, t0);
      store_h_chunk<0>(acc, sbase + OFF_A + e0 * SLOT + rowoff, lane, s0, s1);
      mbar_wait(bars + 8 * (BAR_FULLA + e1), 0, t0);
      store_h_chunk<1>(acc, sbase + OFF_A + e1 * SLOT + rowoff, lane, s0, s1);
      mbar_wait(bars + 8 * (BAR_FULLA + e2), 0, t0);
      store_h_chunk<2>(acc, sbase + OFF_A + e2 * SLOT + rowoff, lane, s0, s1);
    }
    fence_async_smem();
    wg_bar(wg);
    if (lane == 0) mbar_arrive(bars + 8 * BAR_STG);
    if (tid == 0) TR(4);
    float own[32];
    {
      Acc<128> acc;
#pragma unroll
      for (int i = 0; i < 64; i++) acc[i] = 0.f;
      bare_groups<128, SHO>(acc, c, 0, on);
      drain(c);
      if (tid == 0) TR(5);
      if (lane == 0) mbar_arrive(bars + 8 * BAR_PFREE);
      named_bar<3>(256);
      const uint32_t pst = sbase + OFF_B + ((30 + on) % NB) * SLOT + wg * 8192 + (tid & 127) * 16;
#pragma unroll
      for (int i = 0; i < 4; i++) {
        uint32_t r[4];
#pragma unroll
        for (int k = 0; k < 4; k++) {
          const int idx = 8 * i + 2 * k;
          const float lo = typeB ? acc[idx] : acc[32 + idx], hi = typeB ? acc[idx + 1] : acc[32 + idx + 1];
          r[k] = pack_bf16(lo, hi);
        }
        sts128(pst + i * 2048, r[0], r[1], r[2], r[3]);
      }
#pragma unroll
      for (int i = 0; i < 32; i++) own[i] = typeB ? acc[32 + i] : acc[i];
      fence_async_smem();
      __syncwarp();
      if (lane == 0) mbar_arrive(bars + 8 * BAR_STG);
    }
#pragma unroll 1
    for (int g = 0; g < 8; g++) {
      const uint32_t a16 = c.a16 + c.ai * (SLOT >> 4);
      const uint32_t b16 = c.b16 + c.bi * (SLOT >> 4) + (g & 1) * 512;
      if (g == 6) {
        mbar_wait(bars + 8 * BAR_PIN, 0, t0);
        const uint32_t pin = sbase + OFF_B + ((31 + on) % NB) * SLOT + wg * 8192 + (tid & 127) * 16;
#pragma unroll
        for (int i = 0; i < 4; i++) {
          const uint4 v = lds128(pin + i * 2048);
          const uint32_t r[4] = {v.x, v.y, v.z, v.w};
#pragma unroll
          for (int k = 0; k < 4; k++) { own[8 * i + 2 * k] += __uint_as_float(r[k] << 16); own[8 * i + 2 * k + 1] += __uint_as_float(r[k] & 0xffff0000u); }
        }
        named_bar<3>(256);
        if (tid == 0) TR(7);
      }
      gemm_wait(c);
      wgmma_fence();
#pragma unroll
      for (int s = 0; s < 4; s++) wgmma_ss_n64(own, desc_sw128<16>(a16 + s * 2), desc_sw128<2048>(b16 + s * 128));
      wgmma_commit();
      wgmma_wait<0>();
      if (lane == 2) mbar_arrive(bars + 8 * (BAR_EMPTYA + c.ai));
      c.aph ^= 1u << c.ai;
      c.ae++; c.ai = a_slot(c.ae, 0);
      if (g & 1) { if (++c.bi == NB) { c.bi = 0; c.bph ^= 1; } }
    }
    if (tid == 0) TR(6);
    {
      const uint32_t ob = sbase + OFF_B + ((31 + on) % NB) * SLOT;
      const uint32_t wb = ob + warp * 2048;
      const uint32_t orow = wb + ((lane & 7) + 8 * ((lane >> 3) & 1)) * 128;
#pragma unroll
      for (int i = 0; i < 4; i++)
        stsm_x4(orow + (((i * 2 + (lane >> 4)) ^ (lane & 7)) << 4), pack_bf16(own[8 * i], own[8 * i + 1]), pack_bf16(own[8 * i + 2], own[8 * i + 3]),
                pack_bf16(own[8 * i + 4], own[8 * i + 5]), pack_bf16(own[8 * i + 6], own[8 * i + 7]));
      __syncwarp();
      uint4* o = (uint4*)(P.out + (size_t)(rb * 128 + warp * 16 + (lane >> 3)) * DM + j * 64) + (lane & 7);
#pragma unroll
      for (int i = 0; i < 4; i++) {
        const int r = i * 4 + (lane >> 3);
        o[i * 4 * (DM / 8)] = lds128(wb + r * 128 + (((lane & 7) ^ (r & 7)) << 4));
      }
    }
    if (tid == 0) TR(8);
  } else if (warp < 16) {
    asm volatile("setmaxnreg.dec.sync.aligned.u32 56;");
    cluster_wait();
    const int aw = __shfl_sync(0xffffffffu, (warp >> 2) & 1, 0);
    {
      const int rowg = rb * 128 + j * 16 + (warp - 8) * 2;
      const uint4* gw = (const uint4*)P.gate_w;
      const uint4* xr = (const uint4*)(P.x + (size_t)rowg * DM);
      mbar_wait(bars + 8 * (BAR_FULLB + 1), 0, t0);
      const uint4 w0 = __ldg(gw + lane), w1 = __ldg(gw + 32 + lane);
      const uint4 xa0 = __ldg(xr + lane), xa1 = __ldg(xr + 32 + lane), xb0 = __ldg(xr + 64 + lane), xb1 = __ldg(xr + 96 + lane);
#pragma unroll
      for (int i = 0; i < 4; i++) sts128(sbase + OFF_KV + 32768 + i * 4096 + (tid - 256) * 16, 0u, 0u, 0u, 0u);
      const uint32_t wa[8] = {w0.x, w0.y, w0.z, w0.w, w1.x, w1.y, w1.z, w1.w};
      const uint32_t xa[8] = {xa0.x, xa0.y, xa0.z, xa0.w, xa1.x, xa1.y, xa1.z, xa1.w};
      const uint32_t xb[8] = {xb0.x, xb0.y, xb0.z, xb0.w, xb1.x, xb1.y, xb1.z, xb1.w};
      float za = 0.f, zb = 0.f;
#pragma unroll
      for (int e = 0; e < 8; e++) {
        const float wl = __uint_as_float(wa[e] << 16), wh = __uint_as_float(wa[e] & 0xffff0000u);
        za = fmaf(__uint_as_float(xa[e] << 16), wl, za); za = fmaf(__uint_as_float(xa[e] & 0xffff0000u), wh, za);
        zb = fmaf(__uint_as_float(xb[e] << 16), wl, zb); zb = fmaf(__uint_as_float(xb[e] & 0xffff0000u), wh, zb);
      }
#pragma unroll
      for (int o = 16; o > 0; o >>= 1) { za += __shfl_xor_sync(0xffffffffu, za, o); zb += __shfl_xor_sync(0xffffffffu, zb, o); }
      if (lane < 2) asm volatile("st.shared.f32 [%0], %1;" ::"r"(sbase + OFF_GST + (warp - 8) * 8 + lane * 4), "f"(1.f / (1.f + __expf(-(lane ? zb : za)))) : "memory");
      fence_async_smem();
      named_bar<6>(256);
      if (tid == 256) {
        bulk_store(&g_gate[rb * 128 + j * 16], sbase + OFF_GST, 64);
        bulk_commit(); bulk_wait_all();
        flag_add(&g_flag_g[rb * FS]);
        flag_wait(&g_flag_g[rb * FS], ep1 * 8, t0);
        fence_async_global();
        mbar_expect_tx(bars + 8 * BAR_GIN, 512);
        bulk_load(sbase + OFF_GIN, &g_gate[rb * 128], 512, bars + 8 * BAR_GIN);
        TR(10);
      }
      __syncwarp();
    }
    mbar_wait(bars + 8 * (BAR_QRDY + aw), 0, t0);
    asm volatile("setmaxnreg.inc.sync.aligned.u32 96;");
    attention(sbase, aw, warp & 3, lane, rb, t0);
    if (tid == 256) TR(3);
  } else {
    asm volatile("setmaxnreg.dec.sync.aligned.u32 32;");
    if (warp == 16) {
      __syncwarp();
      cluster_wait();
      if (lane == 0) {
        int bi = 2; uint32_t bph = 1;
        const int nb = 32 + on + 4;
        for (int eb = 2; eb < nb; eb++) {
          if (eb == 4 || eb == 6) {
            const int ea = eb >> 1;
            mbar_expect_tx(bars + 8 * (BAR_FULLA + 1 + ea), 16384);
            tma_load_2d(sbase + OFF_A + (1 + ea) * SLOT, &P.tmX, ea * 64, rb * 128, bars + 8 * (BAR_FULLA + 1 + ea));
          }
          const uint32_t fb = bars + 8 * (BAR_FULLB + bi), dst = sbase + OFF_B + bi * SLOT + rank * 8192;
          mbar_wait(bars + 8 * (BAR_EMPTYB + bi), bph, t0);
          if (eb < 16) {
            mbar_expect_tx(fb, typeB ? 12288 : 16384);
            tma_load_3d_mc(dst, &P.tmWqkv, 64 * j, eb * 32 + rank * 16, 0, fb);
            if (!typeB) tma_load_3d_mc(dst + 6144, &P.tmW1a, 0, eb * 32 + rank * 16, 24 + (j >> 1), fb);
          }
          else if (eb < 32) { mbar_expect_tx(fb, 12288); tma_load_3d_mc(dst, &P.tmW1b, 0, (eb - 16) * 32 + rank * 16, 3 * j, fb); }
          else if (eb < 32 + on) { int ow; const int ch = oh_chunk(j, eb - 32, ow); mbar_expect_tx(fb, 16384); tma_load_3d_mc(dst, &P.tmW2, 0, ch * 64 + rank * 32, (j >> 1) * 2, fb); }
          else { mbar_expect_tx(fb, 16384); tma_load_4d_mc(dst, &P.tmWo, 64 * j, 0, eb - 32 - on, rank * 4, fb); }
          if (++bi == NB) { bi = 0; bph ^= 1; }
          if (eb == PFAT) {
            const int b = blockIdx.x;
            l2_prefetch((const uint8_t*)P.w1 + b * 14336, 14336);
            l2_prefetch((const uint8_t*)P.w2 + b * 14336, 14336);
            l2_prefetch((const uint8_t*)P.wo + b * 4096, 4096);
          }
        }
        mbar_wait(bars + 8 * BAR_PFREE, 0, t0);
        flag_wait(&g_flag_p[(rb * 8 + j) * FS], ep1, t0);
        fence_async_global();
        mbar_expect_tx(bars + 8 * BAR_PIN, 16384);
        bulk_load(sbase + OFF_B + ((31 + on) % NB) * SLOT, g_part + (size_t)(rb * 8 + j) * 16384, 16384, bars + 8 * BAR_PIN);
      }
    } else if (warp == 17) {
      cluster_wait();
      if (lane == 0) {
        for (int ea = 1; ea < 5; ea++) mbar_arrive(bars + 8 * (BAR_EMPTYA + ea));
        uint32_t aph = 0xE1;
        const int na = 16 + on + 8;
        unsigned ready = 0;
        for (int ea = 4; ea < na; ea++) {
          const int ai = a_slot(ea, 20 + on);
          const uint32_t fb = bars + 8 * (BAR_FULLA + ai), dst = sbase + OFF_A + ai * SLOT;
          int ch = ea & 7, need = -1;
          if (ea >= 16 + on) { need = 8 + ea - 16 - on; ch = 20 + need; }
          else if (ea >= 19) ch = oh_chunk(j, ea - 16, need);
          if (need >= 0 && !((ready >> need) & 1)) {
            const unsigned* fp = need < 8 ? &g_flag_h[rb * 8 * FS] : need < 16 ? &g_flag_o[rb * 8 * FS] : &g_flag_e[rb * 8 * FS];
            const unsigned tgt = (need & 8) ? ep1 * 4 : ep1;
            do {
              unsigned v[8];
#pragma unroll
              for (int i = 0; i < 8; i++) v[i] = ld_relaxed(fp + i * FS);
#pragma unroll
              for (int i = 0; i < 8; i++) if ((int)(v[i] - tgt) >= 0) ready |= 1u << (i + (need & 24));
            } while (!((ready >> need) & 1) && clk32() - t0 < TIMEOUT);
            fence_async_global();
          }
          mbar_wait(bars + 8 * (BAR_EMPTYA + ai), (aph >> ai) & 1, t0);
          if (ea >= 16 && ea < 19) mbar_arrive(fb);
          else {
            mbar_arrive(bars + 8 * (BAR_EMPTYA + ai));
            mbar_expect_tx(fb, 16384);
            tma_load_2d(dst, ea < 16 ? &P.tmX : &P.tmHO, ch * 64, rb * 128, fb);
          }
          TR(24 + ea);
          aph ^= 1u << ai;
        }
      }
    } else {
      const int wg = warp - 18;
      cluster_wait();
      if (lane == 0 && wg == 0) {
        const uint32_t stg = bars + 8 * BAR_STG;
        mbar_wait(stg, 0, t0);
        for (int hh = 0; hh < 4; hh++) bulk_store(g_kv + ((size_t)(4 * j + hh) * SEQ + rb * 128) * 64, sbase + OFF_KV + hh * 8192, 8192);
        bulk_commit(); bulk_wait_all();
        flag_add(&g_flag_kv[(rb * 8 + j) * FS]);
        TR(21);
        if (!typeB) {
          mbar_wait(bars + 8 * BAR_STE, 0, t0);
          tma_store_2d(&P.tmHO, (24 + (j >> 1)) * 64, rb * 128, sbase + OFF_KV + 32768);
          bulk_commit(); bulk_wait_all();
          flag_add(&g_flag_e[(rb * 8 + j) * FS]);
        }
        mbar_arrive(bars + 8 * BAR_KVOK);
        mbar_wait(stg, 1, t0);
        for (int i = 0; i < 3; i++) tma_store_2d(&P.tmHO, (3 * j + i) * 64, rb * 128, sbase + OFF_A + (1 + i) * SLOT);
        bulk_commit();
        asm volatile("cp.async.bulk.wait_group.read 0;" ::: "memory");
        for (int i = 0; i < 3; i++) mbar_arrive(bars + 8 * (BAR_EMPTYA + 1 + i));
        TR(19);
        bulk_wait_all();
        flag_add(&g_flag_h[(rb * 8 + j) * FS]);
        TR(22);
        {
          const unsigned old = atomicAdd(&g_done, 1u);
          if (old == gridDim.x - 1) { g_done = 0; *(volatile unsigned*)&g_epoch = ep1; }
        }
        mbar_wait(stg, 0, t0);
        bulk_store(g_part + (size_t)(rb * 8 + (j ^ 1)) * 16384, sbase + OFF_B + ((30 + on) % NB) * SLOT, 16384);
        bulk_commit(); bulk_wait_all();
        flag_add(&g_flag_p[(rb * 8 + (j ^ 1)) * FS]);
        TR(23);
      } else if (lane == 0) {
        const int nblk = rb >= 2 ? 3 : rb + 1;
        const uint32_t kvbytes = nblk * 8192;
        const uint8_t* kvsrc = g_kv + ((size_t)(4 * j) * SEQ + (rb + 1 - nblk) * 128) * 64;
        const uint32_t kvdst = sbase + OFF_KV + (3 - nblk) * 8192;
        {
          const unsigned* f0 = &g_flag_kv[(rb * 8 + j) * FS];
          const unsigned* f1 = rb >= 1 ? f0 - 8 * FS : f0;
          const unsigned* f2 = rb >= 2 ? f0 - 16 * FS : f0;
          unsigned v0, v1, v2;
          do { v0 = ld_relaxed(f0); v1 = ld_relaxed(f1); v2 = ld_relaxed(f2); }
          while (((int)(v0 - ep1) < 0 || (int)(v1 - ep1) < 0 || (int)(v2 - ep1) < 0) && clk32() - t0 < TIMEOUT);
        }
        TR(11);
        mbar_wait(bars + 8 * BAR_GIN, 0, t0);
        fence_async_global();
        mbar_expect_tx(bars + 8 * BAR_KVFULL, kvbytes);
        bulk_load(kvdst, kvsrc, kvbytes, bars + 8 * BAR_KVFULL);
        mbar_wait(bars + 8 * BAR_KVOK, 0, t0);
        mbar_expect_tx(bars + 8 * (BAR_KVFULL + 1), kvbytes);
        bulk_load(kvdst + KVBUF, kvsrc + (size_t)SEQ * 64, kvbytes, bars + 8 * (BAR_KVFULL + 1));
        for (int hh = 0; hh < 4; hh++) {
          for (int aw = 0; aw < 2; aw++) {
            mbar_wait(bars + 8 * (BAR_OST + aw), hh & 1, t0);
            tma_store_2d(&P.tmOs, DFF + hh * 128 + j * 16, rb * 128 + aw * 64, sbase + OFF_A + aw * 8192 + hh * 2048);
          }
          bulk_commit();
          if (hh < 2) {
            mbar_wait(bars + 8 * (BAR_KVEMPTY + hh), 0, t0);
            mbar_expect_tx(bars + 8 * (BAR_KVFULL + hh), kvbytes);
            bulk_load(kvdst + hh * KVBUF, kvsrc + (size_t)(hh + 2) * SEQ * 64, kvbytes, bars + 8 * (BAR_KVFULL + hh));
          }
          bulk_wait_all();
          flag_add(&g_flag_o[(rb * 8 + hh * 2 + (j >> 2)) * FS]);
          TR(12 + hh);
        }
      }
    }
  }
}

typedef CUresult (*EncodeFn)(CUtensorMap*, CUtensorMapDataType, cuuint32_t, void*, const cuuint64_t*, const cuuint64_t*, const cuuint32_t*,
                             const cuuint32_t*, CUtensorMapInterleave, CUtensorMapSwizzle, CUtensorMapL2promotion, CUtensorMapFloatOOBfill);

void make_map(EncodeFn enc, CUtensorMap* m, const void* ptr, int rank, const cuuint64_t* dims, const cuuint64_t* strides, const cuuint32_t* box,
              CUtensorMapSwizzle sw = CU_TENSOR_MAP_SWIZZLE_128B) {
  cuuint32_t es[4] = {1, 1, 1, 1};
  enc(m, CU_TENSOR_MAP_DATA_TYPE_BFLOAT16, rank, const_cast<void*>(ptr), dims, strides, box, es, CU_TENSOR_MAP_INTERLEAVE_NONE, sw,
      CU_TENSOR_MAP_L2_PROMOTION_L2_256B, CU_TENSOR_MAP_FLOAT_OOB_FILL_NONE);
}

}

extern "C" void kernel_launch(void* const* d_in, const int* in_sizes, int n_in, void* d_out, int out_size) {
  (void)in_sizes; (void)n_in; (void)out_size;
  static EncodeFn enc = nullptr;
  static void* ho_ptr = nullptr;
  if (!enc) {
    void* fn = nullptr; cudaDriverEntryPointQueryResult st;
    cudaGetDriverEntryPoint("cuTensorMapEncodeTiled", &fn, cudaEnableDefault, &st);
    enc = (EncodeFn)fn;
    cudaGetSymbolAddress(&ho_ptr, g_ho);
    cudaFuncSetAttribute(fused_kernel, cudaFuncAttributeMaxDynamicSharedMemorySize, SMEM_BYTES);
  }
  const __nv_bfloat16* x = (const __nv_bfloat16*)d_in[0];
  const __nv_bfloat16* wqkv = (const __nv_bfloat16*)d_in[1];
  const __nv_bfloat16* wo = (const __nv_bfloat16*)d_in[2];
  const __nv_bfloat16* w1 = (const __nv_bfloat16*)d_in[4];
  const __nv_bfloat16* w2 = (const __nv_bfloat16*)d_in[5];
  const __nv_bfloat16* gate_w = (const __nv_bfloat16*)d_in[6];
  Params P;
  { cuuint64_t d[2] = {DM, SEQ}, s[1] = {DM * 2}; cuuint32_t b[2] = {64, 128}; make_map(enc, &P.tmX, x, 2, d, s, b); }
  { cuuint64_t d[3] = {512, 512, 3}, s[2] = {1536 * 2, 512 * 2}; cuuint32_t b[3] = {64, 16, 3}; make_map(enc, &P.tmWqkv, wqkv, 3, d, s, b); }
  { cuuint64_t d[3] = {64, 512, 28}, s[2] = {DFF * 2, 128}; cuuint32_t b[3] = {64, 16, 1}; make_map(enc, &P.tmW1a, w1, 3, d, s, b);
    b[2] = 3; make_map(enc, &P.tmW1b, w1, 3, d, s, b); }
  { cuuint64_t d[3] = {64, DFF, 8}, s[2] = {DM * 2, 128}; cuuint32_t b[3] = {64, 32, 2}; make_map(enc, &P.tmW2, w2, 3, d, s, b); }
  { cuuint64_t d[4] = {DM, 16, 4, 8}, s[3] = {DM * 2, 16 * DM * 2, 64 * DM * 2}; cuuint32_t b[4] = {64, 16, 1, 4}; make_map(enc, &P.tmWo, wo, 4, d, s, b); }
  { cuuint64_t d[2] = {KHO, SEQ}, s[1] = {KHO * 2}; cuuint32_t b[2] = {64, 128}; make_map(enc, &P.tmHO, ho_ptr, 2, d, s, b);
    b[1] = 64; b[0] = 16; make_map(enc, &P.tmOs, ho_ptr, 2, d, s, b, CU_TENSOR_MAP_SWIZZLE_NONE); }
  P.x = x; P.gate_w = gate_w; P.w1 = w1; P.w2 = w2; P.wo = wo; P.wqkv = wqkv; P.out = (__nv_bfloat16*)d_out;
  fused_kernel<<<128, 640, SMEM_BYTES>>>(P);
}
```

```cpp
#include <cuda_runtime.h>
#include <cuda_bf16.h>
#include <cuda.h>
#include <stdint.h>

#define DEVI __device__ __forceinline__

namespace {

constexpr int SEQ = 2048, DM = 512, DFF = 1792, KHO = 2304;
constexpr int NA = 5, NB = 6, SLOT = 16384, KVBUF = 24576;
constexpr int NA2 = 8;
constexpr int OFF_B = 0, OFF_A = NB * SLOT, OFF_KV = OFF_A + NA * SLOT, OFF_BAR = OFF_KV + 2 * KVBUF;
constexpr int OFF_GST = OFF_BAR + 512;
constexpr int OFF_GIN = OFF_BAR + 1024;
constexpr int OFF_NM = OFF_BAR + 1536;
constexpr int SMEM_BYTES = OFF_BAR + 2560;
constexpr uint32_t TIMEOUT = 1u << 28;
#ifndef WAIT_HINT_NS
#define WAIT_HINT_NS 20000u
#endif
#ifndef PFAT
#define PFAT 8
#endif
#ifndef SH
#define SH true
#endif
#ifndef SHW
#define SHW 0
#endif
#ifndef SHG
#define SHG 1
#endif
#ifndef PF0
#define PF0 0
#endif
#ifndef SHO
#define SHO true
#endif
#ifndef SHS
#define SHS 6
#endif
constexpr int FS = 8;

constexpr int BAR_FULLA = 0, BAR_EMPTYA = BAR_FULLA + NA2, BAR_FULLB = BAR_EMPTYA + NA2, BAR_EMPTYB = BAR_FULLB + NB,
              BAR_KVFULL = BAR_EMPTYB + NB, BAR_KVEMPTY = BAR_KVFULL + 2, BAR_STG = BAR_KVEMPTY + 2, BAR_PIN = BAR_STG + 2, BAR_GATE = BAR_PIN + 1, BAR_STE = BAR_GATE + 2, BAR_PFREE = BAR_STE + 2, BAR_GIN = BAR_PFREE + 1, BAR_OST = BAR_GIN + 1, BAR_QRDY = BAR_OST + 2, BAR_KVOK = BAR_QRDY + 2;

__device__ __align__(1024) uint8_t g_kv[32 * SEQ * 64];
__device__ __align__(1024) __nv_bfloat16 g_ho[SEQ * KHO];
__device__ __align__(1024) uint8_t g_part[128 * 16384];
__device__ __align__(128) float g_gate[SEQ];
__device__ unsigned g_flag_kv[128 * FS], g_flag_h[128 * FS], g_flag_o[128 * FS], g_flag_g[16 * FS], g_flag_p[128 * FS], g_flag_e[128 * FS];
__device__ unsigned g_epoch, g_done;
#ifdef TRACE
__device__ unsigned g_trace[128 * 64];
#define TR(i) do { asm volatile("st.shared.u32 [%0], %1;" ::"r"(sbase + OFF_BAR + 640 + 4 * (i)), "r"(clk32() - t0)); } while (0)
#else
#define TR(i) do {} while (0)
#endif

struct Params {
  CUtensorMap tmX, tmWqkv, tmW1a, tmW1b, tmW2, tmWo, tmHO, tmOs;
  const __nv_bfloat16* x;
  const __nv_bfloat16* gate_w;
  const __nv_bfloat16* w1;
  const __nv_bfloat16* w2;
  const __nv_bfloat16* wo;
  const __nv_bfloat16* wqkv;
  __nv_bfloat16* out;
};

DEVI uint32_t smem_u32(const void* p) { return (uint32_t)__cvta_generic_to_shared(p); }
DEVI uint32_t clk32() { uint32_t c; asm volatile("mov.u32 %0, %%clock;" : "=r"(c)); return c; }
DEVI void mbar_init(uint32_t bar, uint32_t cnt) { asm volatile("mbarrier.init.shared::cta.b64 [%0], %1;" ::"r"(bar), "r"(cnt)); }
DEVI void mbar_expect_tx(uint32_t bar, uint32_t bytes) { asm volatile("mbarrier.arrive.expect_tx.shared::cta.b64 _, [%0], %1;" ::"r"(bar), "r"(bytes) : "memory"); }
DEVI void mbar_arrive(uint32_t bar) { asm volatile("mbarrier.arrive.shared::cta.b64 _, [%0];" ::"r"(bar) : "memory"); }
DEVI void mbar_arrive_cluster(uint32_t bar, uint32_t cta) {
  asm volatile("{ .reg .b32 ra; mapa.shared::cluster.u32 ra, %0, %1; mbarrier.arrive.shared::cluster.b64 _, [ra]; }" ::"r"(bar), "r"(cta) : "memory");
}
DEVI void mbar_wait(uint32_t bar, uint32_t parity, uint32_t t0) {
  asm volatile("{ .reg .pred p; .reg .u32 c;\n"
               "mbarrier.try_wait.parity.shared::cta.b64 p, [%0], %1;\n"
               "@p bra DONE_%=;\n"
               "WAIT_%=:\n"
               "mbarrier.try_wait.parity.shared::cta.b64 p, [%0], %1, %4;\n"
               "@p bra DONE_%=;\n"
               "mov.u32 c, %%clock; sub.u32 c, c, %2; setp.lt.u32 p, c, %3;\n"
               "@p bra WAIT_%=;\n"
               "DONE_%=: }" ::"r"(bar), "r"(parity), "r"(t0), "n"(TIMEOUT), "r"(WAIT_HINT_NS) : "memory");
}
DEVI unsigned ld_relaxed(const unsigned* p) { unsigned v; asm volatile("ld.relaxed.gpu.global.u32 %0, [%1];" : "=r"(v) : "l"(p) : "memory"); return v; }
DEVI void flag_wait(const unsigned* p, unsigned target, uint32_t t0) {
  while ((int)(ld_relaxed(p) - target) < 0) { if (clk32() - t0 > TIMEOUT) break; }
}
DEVI void flag_add(unsigned* p) { asm volatile("red.relaxed.gpu.global.add.u32 [%0], 1;" ::"l"(p) : "memory"); }
DEVI void fence_async_smem() { asm volatile("fence.proxy.async.shared::cta;" ::: "memory"); }
DEVI void fence_async_global() { asm volatile("fence.proxy.async.global;" ::: "memory"); }
DEVI void tma_load_2d(uint32_t dst, const CUtensorMap* m, int c0, int c1, uint32_t bar) {
  asm volatile("cp.async.bulk.tensor.2d.shared::cluster.global.mbarrier::complete_tx::bytes [%0], [%1, {%3, %4}], [%2];" ::"r"(dst), "l"(m), "r"(bar), "r"(c0), "r"(c1) : "memory");
}
DEVI void tma_load_3d(uint32_t dst, const CUtensorMap* m, int c0, int c1, int c2, uint32_t bar) {
  asm volatile("cp.async.bulk.tensor.3d.shared::cluster.global.mbarrier::complete_tx::bytes [%0], [%1, {%3, %4, %5}], [%2];"
               ::"r"(dst), "l"(m), "r"(bar), "r"(c0), "r"(c1), "r"(c2) : "memory");
}
DEVI void tma_load_3d_mc(uint32_t dst, const CUtensorMap* m, int c0, int c1, int c2, uint32_t bar) {
  asm volatile("cp.async.bulk.tensor.3d.shared::cluster.global.mbarrier::complete_tx::bytes.multicast::cluster [%0], [%1, {%3, %4, %5}], [%2], %6;"
               ::"r"(dst), "l"(m), "r"(bar), "r"(c0), "r"(c1), "r"(c2), "h"((uint16_t)3) : "memory");
}
DEVI void tma_load_4d_mc(uint32_t dst, const CUtensorMap* m, int c0, int c1, int c2, int c3, uint32_t bar) {
  asm volatile("cp.async.bulk.tensor.4d.shared::cluster.global.mbarrier::complete_tx::bytes.multicast::cluster [%0], [%1, {%3, %4, %5, %6}], [%2], %7;"
               ::"r"(dst), "l"(m), "r"(bar), "r"(c0), "r"(c1), "r"(c2), "r"(c3), "h"((uint16_t)3) : "memory");
}
DEVI void tma_store_2d(const CUtensorMap* m, int c0, int c1, uint32_t src) {
  asm volatile("cp.async.bulk.tensor.2d.global.shared::cta.bulk_group [%0, {%1, %2}], [%3];" ::"l"(m), "r"(c0), "r"(c1), "r"(src) : "memory");
}
DEVI void bulk_store(void* dst, uint32_t src, uint32_t bytes) {
  asm volatile("cp.async.bulk.global.shared::cta.bulk_group [%0], [%1], %2;" ::"l"(dst), "r"(src), "r"(bytes) : "memory");
}
DEVI void bulk_load(uint32_t dst, const void* src, uint32_t bytes, uint32_t bar) {
  asm volatile("cp.async.bulk.shared::cluster.global.mbarrier::complete_tx::bytes [%0], [%1], %2, [%3];" ::"r"(dst), "l"(src), "r"(bytes), "r"(bar) : "memory");
}
DEVI void bulk_commit() { asm volatile("cp.async.bulk.commit_group;" ::: "memory"); }
DEVI void bulk_wait_all() { asm volatile("cp.async.bulk.wait_group 0;" ::: "memory"); }
DEVI void l2_prefetch(const void* p, uint32_t bytes) { asm volatile("cp.async.bulk.prefetch.L2.global [%0], %1;" ::"l"(p), "r"(bytes) : "memory"); }
DEVI void cluster_arrive() { asm volatile("barrier.cluster.arrive.relaxed.aligned;" ::: "memory"); }
DEVI void cluster_wait() { asm volatile("barrier.cluster.wait.aligned;" ::: "memory"); }
template <int ID> DEVI void named_bar(int n) { asm volatile("bar.sync %0, %1;" ::"n"(ID), "r"(n) : "memory"); }
DEVI void wg_bar(int wg) { if (wg == 0) named_bar<1>(128); else named_bar<2>(128); }
DEVI void wgmma_fence() { asm volatile("wgmma.fence.sync.aligned;" ::: "memory"); }
DEVI void wgmma_commit() { asm volatile("wgmma.commit_group.sync.aligned;" ::: "memory"); }
template <int N> DEVI void wgmma_wait() { asm volatile("wgmma.wait_group.sync.aligned %0;" ::"n"(N) : "memory"); }
template <uint32_t LBO> DEVI uint64_t desc_sw128(uint32_t a16) {
  return ((uint64_t)(0x40000000u | (1024 >> 4)) << 32) | (a16 + ((LBO >> 4) << 16));
}
DEVI uint64_t desc_sw64(uint32_t a16) {
  return ((uint64_t)(0x80000000u | (512 >> 4)) << 32) | (a16 + ((512 >> 4) << 16));
}
DEVI uint32_t pack_bf16(float lo, float hi) { uint32_t r; asm("cvt.rn.bf16x2.f32 %0, %1, %2;" : "=r"(r) : "f"(hi), "f"(lo)); return r; }
DEVI void stsm_x4(uint32_t addr, uint32_t r0, uint32_t r1, uint32_t r2, uint32_t r3) {
  asm volatile("stmatrix.sync.aligned.m8n8.x4.shared.b16 [%0], {%1, %2, %3, %4};" ::"r"(addr), "r"(r0), "r"(r1), "r"(r2), "r"(r3) : "memory");
}
DEVI void sts128(uint32_t addr, uint32_t r0, uint32_t r1, uint32_t r2, uint32_t r3) {
  asm volatile("st.shared.v4.b32 [%0], {%1, %2, %3, %4};" ::"r"(addr), "r"(r0), "r"(r1), "r"(r2), "r"(r3) : "memory");
}
DEVI uint4 lds128(uint32_t addr) {
  uint4 v; asm volatile("ld.shared.v4.b32 {%0, %1, %2, %3}, [%4];" : "=r"(v.x), "=r"(v.y), "=r"(v.z), "=r"(v.w) : "r"(addr) : "memory"); return v;
}
DEVI float ex2(float x) { float y; asm("ex2.approx.ftz.f32 %0, %1;" : "=f"(y) : "f"(x)); return y; }

DEVI void wgmma_ss_n64(float (&d)[32], uint64_t da, uint64_t db) {
  asm volatile("wgmma.mma_async.sync.aligned.m64n64k16.f32.bf16.bf16 {%0, %1, %2, %3, %4, %5, %6, %7, %8, %9, %10, %11, %12, %13, %14, %15, %16, %17, %18, %19, %20, %21, %22, %23, %24, %25, %26, %27, %28, %29, %30, %31}, %32, %33, 1, 1, 1, 0, 1;"
    : "+f"(d[0]), "+f"(d[1]), "+f"(d[2]), "+f"(d[3]), "+f"(d[4]), "+f"(d[5]), "+f"(d[6]), "+f"(d[7]), "+f"(d[8]), "+f"(d[9]), "+f"(d[10]), "+f"(d[11]), "+f"(d[12]), "+f"(d[13]), "+f"(d[14]), "+f"(d[15]), "+f"(d[16]), "+f"(d[17]), "+f"(d[18]), "+f"(d[19]), "+f"(d[20]), "+f"(d[21]), "+f"(d[22]), "+f"(d[23]), "+f"(d[24]), "+f"(d[25]), "+f"(d[26]), "+f"(d[27]), "+f"(d[28]), "+f"(d[29]), "+f"(d[30]), "+f"(d[31])
    : "l"(da), "l"(db));
}
DEVI void wgmma_ss_n128(float (&d)[64], uint64_t da, uint64_t db) {
  asm volatile("wgmma.mma_async.sync.aligned.m64n128k16.f32.bf16.bf16 {%0, %1, %2, %3, %4, %5, %6, %7, %8, %9, %10, %11, %12, %13, %14, %15, %16, %17, %18, %19, %20, %21, %22, %23, %24, %25, %26, %27, %28, %29, %30, %31, %32, %33, %34, %35, %36, %37, %38, %39, %40, %41, %42, %43, %44, %45, %46, %47, %48, %49, %50, %51, %52, %53, %54, %55, %56, %57, %58, %59, %60, %61, %62, %63}, %64, %65, 1, 1, 1, 0, 1;"
    : "+f"(d[0]), "+f"(d[1]), "+f"(d[2]), "+f"(d[3]), "+f"(d[4]), "+f"(d[5]), "+f"(d[6]), "+f"(d[7]), "+f"(d[8]), "+f"(d[9]), "+f"(d[10]), "+f"(d[11]), "+f"(d[12]), "+f"(d[13]), "+f"(d[14]), "+f"(d[15]), "+f"(d[16]), "+f"(d[17]), "+f"(d[18]), "+f"(d[19]), "+f"(d[20]), "+f"(d[21]), "+f"(d[22]), "+f"(d[23]), "+f"(d[24]), "+f"(d[25]), "+f"(d[26]), "+f"(d[27]), "+f"(d[28]), "+f"(d[29]), "+f"(d[30]), "+f"(d[31]), "+f"(d[32]), "+f"(d[33]), "+f"(d[34]), "+f"(d[35]), "+f"(d[36]), "+f"(d[37]), "+f"(d[38]), "+f"(d[39]), "+f"(d[40]), "+f"(d[41]), "+f"(d[42]), "+f"(d[43]), "+f"(d[44]), "+f"(d[45]), "+f"(d[46]), "+f"(d[47]), "+f"(d[48]), "+f"(d[49]), "+f"(d[50]), "+f"(d[51]), "+f"(d[52]), "+f"(d[53]), "+f"(d[54]), "+f"(d[55]), "+f"(d[56]), "+f"(d[57]), "+f"(d[58]), "+f"(d[59]), "+f"(d[60]), "+f"(d[61]), "+f"(d[62]), "+f"(d[63])
    : "l"(da), "l"(db));
}
DEVI void wgmma_qk64(float (&d)[32], uint32_t a0, uint32_t a1, uint32_t a2, uint32_t a3, uint64_t db) {
  asm volatile("wgmma.mma_async.sync.aligned.m64n64k16.f32.bf16.bf16 {%0, %1, %2, %3, %4, %5, %6, %7, %8, %9, %10, %11, %12, %13, %14, %15, %16, %17, %18, %19, %20, %21, %22, %23, %24, %25, %26, %27, %28, %29, %30, %31}, {%32, %33, %34, %35}, %36, 0, 1, 1, 0;"
    : "=f"(d[0]), "=f"(d[1]), "=f"(d[2]), "=f"(d[3]), "=f"(d[4]), "=f"(d[5]), "=f"(d[6]), "=f"(d[7]), "=f"(d[8]), "=f"(d[9]), "=f"(d[10]), "=f"(d[11]), "=f"(d[12]), "=f"(d[13]), "=f"(d[14]), "=f"(d[15]), "=f"(d[16]), "=f"(d[17]), "=f"(d[18]), "=f"(d[19]), "=f"(d[20]), "=f"(d[21]), "=f"(d[22]), "=f"(d[23]), "=f"(d[24]), "=f"(d[25]), "=f"(d[26]), "=f"(d[27]), "=f"(d[28]), "=f"(d[29]), "=f"(d[30]), "=f"(d[31])
    : "r"(a0), "r"(a1), "r"(a2), "r"(a3), "l"(db));
}
DEVI void wgmma_pv(float (&d)[8], uint32_t a0, uint32_t a1, uint32_t a2, uint32_t a3, uint64_t db) {
  asm volatile("wgmma.mma_async.sync.aligned.m64n16k16.f32.bf16.bf16 {%0, %1, %2, %3, %4, %5, %6, %7}, {%8, %9, %10, %11}, %12, 1, 1, 1, 1;"
    : "+f"(d[0]), "+f"(d[1]), "+f"(d[2]), "+f"(d[3]), "+f"(d[4]), "+f"(d[5]), "+f"(d[6]), "+f"(d[7])
    : "r"(a0), "r"(a1), "r"(a2), "r"(a3), "l"(db));
}
DEVI void wgmma_pv0(float (&d)[8], uint32_t a0, uint32_t a1, uint32_t a2, uint32_t a3, uint64_t db) {
  asm volatile("wgmma.mma_async.sync.aligned.m64n16k16.f32.bf16.bf16 {%0, %1, %2, %3, %4, %5, %6, %7}, {%8, %9, %10, %11}, %12, 0, 1, 1, 1;"
    : "=f"(d[0]), "=f"(d[1]), "=f"(d[2]), "=f"(d[3]), "=f"(d[4]), "=f"(d[5]), "=f"(d[6]), "=f"(d[7])
    : "r"(a0), "r"(a1), "r"(a2), "r"(a3), "l"(db));
}


template <int N> struct Acc { float a[64]; float b[(N - 128) / 2]; DEVI float& operator[](int i) { return i < 64 ? a[i] : b[i - 64]; } };
template <> struct Acc<128> { float a[64]; DEVI float& operator[](int i) { return a[i]; } };
template <int N> DEVI void wgmma_ss(Acc<N>& d, uint64_t da, uint64_t db) {
  wgmma_ss_n128(d.a, da, db);
  if constexpr (N == 192) wgmma_ss_n64(d.b, da, db + 256);
  if constexpr (N == 256) wgmma_ss_n128(d.b, da, db + 256);
}

DEVI int oh_chunk(inDEVI int oh_chunk(int j, int i, int& need) {
  if (i >= 3 && i < 5) { const int e = (j & 1) * 2 + i - 3; need = 16 + 2 * e; return 24 + e; }
  if (i >= 5) i -= 2;
  int o, r;
  if (i >= 12) { o = (j + 5) & 7; r = i - 11; }
  else { const int g = i / 3; o = (j + 2 * g) & 7; r = i - 3 * g; }
  need = o;
  return 3 * o + r;
}

 int k = i - 5;
    r = k < 3 ? 0 : k < 5 ? 1 : 2; g = k < 3 ? 1 + k : 1 + ((k - 3) & 1);
  }
  return 3 * ((j + 2 * g) & 7) + r;
}

DEVI int a_slot(int e, int) { return 1 + (e & 3); }

struct Ctx {
  uint32_t sbase, bars, peer, t0, a16, b16;
  int wg, lane;
  int ai, bi; uint32_t aph, bph;
  int brem, ae;
  int pa, pb;
};

DEVI void release_prev(Ctx& c) {
  if (c.pb >= 0) {
    if (c.lane == 0) mbar_arrive(c.bars + 8 * (BAR_EMPTYB + c.pb));
    if (c.lane == 1) mbar_arrive_cluster(c.bars + 8 * (BAR_EMPTYB + c.pb), c.peer);
  }
  if (c.pa >= 0 && c.lane == 2) mbar_arrive(c.bars + 8 * (BAR_EMPTYA + c.pa));
}

DEVI void gemm_wait(Ctx& c) {
  asm volatile("{ .reg .pred p, q; .reg .u32 c;\n"
               "mbarrier.try_wait.parity.shared::cta.b64 p, [%0], %1;\n"
               "mbarrier.try_wait.parity.shared::cta.b64 q, [%2], %3;\n"
               "and.pred p, p, q;\n"
               "@p bra DONE_%=;\n"
               "WAIT_%=:\n"
               "mbarrier.try_wait.parity.shared::cta.b64 p, [%0], %1, %6;\n"
               "mbarrier.try_wait.parity.shared::cta.b64 q, [%2], %3, %6;\n"
               "and.pred p, p, q;\n"
               "@p bra DONE_%=;\n"
               "mov.u32 c, %%clock; sub.u32 c, c, %4; setp.lt.u32 p, c, %5;\n"
               "@p bra WAIT_%=;\n"
               "DONE_%=: }" ::"r"(c.bars + 8 * (BAR_FULLA + c.ai)), "r"((c.aph >> c.ai) & 1), "r"(c.bars + 8 * (BAR_FULLB + c.bi)), "r"(c.bph), "r"(c.t0),
               "n"(TIMEOUT), "r"(WAIT_HINT_NS) : "memory");
}
template <int N, bool SHALLOW>
DEVI void gemm_group(Acc<N>& acc, Ctx& c, int g, int& npa, int& npb) {
  const uint32_t a16 = c.a16 + c.ai * (SLOT >> 4);
  const uint32_t b16 = c.b16 + c.bi * (SLOT >> 4);
  bool adv;
  if constexpr (N >= 192) {
    const uint32_t a2 = a16 + (g & 1) * 4;
    wgmma_ss<N>(acc, desc_sw128<16>(a2), desc_sw128<2048>(b16));
    if (SHALLOW) { wgmma_commit(); wgmma_wait<SHW>(); }
    wgmma_ss<N>(acc, desc_sw128<16>(a2 + 2), desc_sw128<2048>(b16 + 512));
    adv = g & 1;
  } else {
#pragma unroll
    for (int s = 0; s < 4; s++) {
      wgmma_ss<N>(acc, desc_sw128<16>(a16 + s * 2), desc_sw128<4096>(b16 + (s >> 1) * 512 + (s & 1) * 128));
      if (SHALLOW && s < 3 && (SHG == 1 || s == 1)) { wgmma_commit(); wgmma_wait<SHW>(); }
    }
    adv = true;
  }
  wgmma_commit();
  npb = c.brem > 0 ? c.bi : -1;
  c.brem--;
  if (++c.bi == NB) { c.bi = 0; c.bph ^= 1; }
  npa = -1;
  if (adv) { npa = c.ai; c.aph ^= 1u << c.ai; c.ae++; c.ai = 1 + (c.ae & 3); }
}

template <int N, bool SHALLOW = false>
DEVI void bare_groups(Acc<N>& acc, Ctx& c, int g0, int g1) {
  for (int g = g0; g < g1; g++) {
    int npa, npb;
#ifdef TRACE3
    { const uint32_t sbase = c.sbase, t0 = c.t0;
      if (c.brem > 30 && threadIdx.x == 0 && g < 6) { mbar_wait(c.bars + 8 * (BAR_FULLA + c.ai), (c.aph >> c.ai) & 1, c.t0); TR(40 + g); } }
#endif
    gemm_wait(c);
#ifdef TRACE3
    { const uint32_t sbase = c.sbase, t0 = c.t0; if (c.brem > 30 && threadIdx.x == 0 && g < 8) TR(24 + g); }
#endif
    wgmma_fence();
    gemm_group<N, SHALLOW>(acc, c, g, npa, npb);
    wgmma_wait<SHALLOW ? SHW : 1>();
    release_prev(c);
    c.pa = npa; c.pb = npb;
  }
}
DEVI void drain(Ctx& c) {
  wgmma_wait<0>();
  release_prev(c);
  c.pa = c.pb = -1;
}

constexpr float SC = 0.25f * 1.4426950408889634f;

#define ONCE _Pragma("unroll 1") for (unsigned once_ = 0; once_ < gridDim.y; once_++)

struct Gate { float g0, g1; };

DEVI void kill32(float (&S)[32]) {
#pragma unroll
  for (int i = 0; i < 32; i++) S[i] = __int_as_float(0xff800000);
}
DEVI void row_max(const float (&S)[32], float& x0, float& x1) {
  float y0 = S[1], y1 = S[3];
  x0 = fmaxf(x0, S[0]); x1 = fmaxf(x1, S[2]);
#pragma unroll
  for (int n = 1; n < 8; n++) {
    x0 = fmaxf(x0, S[4 * n]); y0 = fmaxf(y0, S[4 * n + 1]); x1 = fmaxf(x1, S[4 * n + 2]); y1 = fmaxf(y1, S[4 * n + 3]);
  }
  x0 = fmaxf(x0, y0); x1 = fmaxf(x1, y1);
}
DEVI void quad_max(float& x0, float& x1) {
  x0 = fmaxf(x0, __shfl_xor_sync(0xffffffffu, x0, 1)); x1 = fmaxf(x1, __shfl_xor_sync(0xffffffffu, x1, 1));
  x0 = fmaxf(x0, __shfl_xor_sync(0xffffffffu, x0, 2)); x1 = fmaxf(x1, __shfl_xor_sync(0xffffffffu, x1, 2));
}
DEVI void exp32(const float (&S)[32], float (&E)[32], float n0, float n1, float (&l)[4]) {
#pragma unroll
  for (int i = 0; i < 32; i++) { E[i] = ex2(fmaf(S[i], SC, (i & 2) ? n1 : n0)); l[i & 3] += E[i]; }
}
DEVI void pack32(const float (&E)[32], uint32_t (&P)[16]) {
#pragma unroll
  for (int i = 0; i < 16; i++) P[i] = pack_bf16(E[2 * i], E[2 * i + 1]);
}
template <bool FIRST> DEVI void pv4(float (&O)[8], const uint32_t (&P)[16], uint32_t v16) {
  if (FIRST) wgmma_pv0(O, P[0], P[1], P[2], P[3], desc_sw64(v16)); else wgmma_pv(O, P[0], P[1], P[2], P[3], desc_sw64(v16));
#pragma unroll
  for (int k = 1; k < 4; k++) wgmma_pv(O, P[4 * k], P[4 * k + 1], P[4 * k + 2], P[4 * k + 3], desc_sw64(v16 + k * 64));
}
DEVI bool wg_any(int wg, bool v) {
  uint32_t r;
  if (wg == 0) asm volatile("{ .reg .pred p, q; setp.ne.u32 p, %1, 0; bar.red.or.pred q, 4, 128, p; selp.u32 %0, 1, 0, q; }" : "=r"(r) : "r"((uint32_t)v) : "memory");
  else asm volatile("{ .reg .pred p, q; setp.ne.u32 p, %1, 0; bar.red.or.pred q, 5, 128, p; selp.u32 %0, 1, 0, q; }" : "=r"(r) : "r"((uint32_t)v) : "memory");
  return r != 0;
}
DEVI void get_gate(Gate& g, uint32_t sbase, int row16, int lane, uint32_t t0) {
  mbar_wait(sbase + OFF_BAR + 8 * BAR_GIN, 0, t0);
  const uint32_t a = sbase + OFF_GIN + (row16 * 16 + (lane >> 2)) * 4;
  asm volatile("ld.shared.f32 %0, [%1];" : "=f"(g.g0) : "r"(a) : "memory");
  asm volatile("ld.shared.f32 %0, [%1];" : "=f"(g.g1) : "r"(a + 32) : "memory");
}

DEVI void attention(uint32_t sbase, int aw, int wi, int lane, int rb, uint32_t t0) {
  const uint32_t bars = sbase + OFF_BAR;
  const uint32_t kvb = ((sbase & 0x3FFFF) + OFF_KV + aw * 4096) >> 4;
  const int cmin = 4 - 2 * rb - aw;
  const int rowc = wi * 16 + (lane >> 2) - (lane & 3) * 2;
  const uint32_t qst = sbase + OFF_A + aw * 8192;
  const float NINF = __int_as_float(0xff800000);
  const int tlo = max(cmin, 1);
#pragma unroll 1
  for (int h = 0; h < 4; h++) {
    const uint32_t kb = kvb + (h & 1) * (KVBUF >> 4);
    const uint4 q = lds128(qst + h * 2048 + (wi * 32 + lane) * 16);
    float O[8], l0, l1;
    uint32_t nm;
    asm volatile("ld.shared.u32 %0, [%1];" : "=r"(nm) : "r"(sbase + OFF_NM + ((aw * 4 + wi) * 32 + (lane & 28) + h) * 4) : "memory");
    float n0 = __uint_as_float(nm << 16), n1 = __uint_as_float(nm & 0xffff0000u);
    mbar_wait(bars + 8 * (BAR_KVFULL + (h & 1)), h >> 1, t0);
#pragma unroll 1
    for (int attempt = 0; attempt < 2; attempt++) {
      float l[4] = {0.f, 0.f, 0.f, 0.f};
      uint32_t P[16];
      {
        float S[32], F[32];
        wgmma_fence();
        wgmma_qk64(S, q.x, q.y, q.z, q.w, desc_sw64(kb + 4 * 256));
        wgmma_qk64(F, q.x, q.y, q.z, q.w, desc_sw64(kb));
        wgmma_commit();
        wgmma_wait<0>();
        for (int r = 0; r < (cmin > 0 ? 1 : 0); r++) kill32(F);
        float M[32];
#pragma unroll
        for (int i = 0; i < 32; i++) M[i] = ((i >> 2) * 8 + (i & 1) > rowc + (i & 2) * 4) ? F[i] : S[i];
        for (int r = 0; r < attempt; r++) {
          row_max(M, n0, n1);
          quad_max(n0, n1);
          n0 *= -SC; n1 *= -SC;
        }
        exp32(M, M, n0, n1, l);
        pack32(M, P);
        uint32_t PF[16];
#pragma unroll
        for (int i = 0; i < 16; i++) {
          const int col = (i >> 1) * 8, r = rowc + (i & 1) * 8;
          const uint32_t m = (col > r ? 0xFFFFu : 0u) | (col + 1 > r ? 0xFFFF0000u : 0u);
          PF[i] = P[i] & m; P[i] &= ~m;
        }
        wgmma_fence();
        pv4<true>(O, PF, kb + 2);
        wgmma_commit();
#ifndef NOPFW
        wgmma_wait<0>();
#endif
      }
      int t = 3;
#pragma unroll 1
      for (; t >= tlo; t--) {
        float S[32];
        wgmma_fence();
        wgmma_qk64(S, q.x, q.y, q.z, q.w, desc_sw64(kb + t * 256));
        wgmma_commit();
        pv4<false>(O, P, kb + (t + 1) * 256 + 2);
        wgmma_commit();
        wgmma_wait<1>();
        ONCE { exp32(S, S, n0, n1, l); }
        wgmma_wait<0>();
        pack32(S, P);
      }
      wgmma_fence();
      pv4<false>(O, P, kb + (t + 1) * 256 + 2);
      wgmma_commit();
      l0 = l[0] + l[1]; l1 = l[2] + l[3];
      l0 += __shfl_xor_sync(0xffffffffu, l0, 1); l1 += __shfl_xor_sync(0xffffffffu, l1, 1);
      l0 += __shfl_xor_sync(0xffffffffu, l0, 2); l1 += __shfl_xor_sync(0xffffffffu, l1, 2);
      const bool redo = wg_any(aw, attempt == 0 && !(l0 > 1e-6f && l0 < 1e18f && l1 > 1e-6f && l1 < 1e18f));
      wgmma_wait<0>();
      if (!redo) break;
      n0 = NINF; n1 = NINF;
#pragma unroll 1
      for (int u = 3; u >= tlo; u--) {
        float S[32];
        wgmma_fence();
        wgmma_qk64(S, q.x, q.y, q.z, q.w, desc_sw64(kb + u * 256));
        wgmma_commit();
        wgmma_wait<0>();
        row_max(S, n0, n1);
      }
    }
    if (lane == 0) mbar_arrive(bars + 8 * (BAR_KVEMPTY + (h & 1)));
    Gate g;
    get_gate(g, sbase, aw * 4 + wi, lane, t0);
    const float c0 = __fdividef(g.g0, l0), c1 = __fdividef(g.g1, l1);
    const int mi = lane >> 3;
    const int srow = wi * 16 + (lane & 7) + 8 * (mi & 1);
    stsm_x4(qst + h * 2048 + srow * 32 + (mi >> 1) * 16, pack_bf16(O[0] * c0, O[1] * c0), pack_bf16(O[2] * c1, O[3] * c1),
            pack_bf16(O[4] * c0, O[5] * c0), pack_bf16(O[6] * c1, O[7] * c1));
    fence_async_smem();
    __syncwarp();
    if (lane == 0) mbar_arrive(bars + 8 * (BAR_OST + aw));
  }
}

template <int CH, int N>
DEVI void store_h_chunk(Acc<N>& acc, uint32_t base  , int lane, float s0, float s1) {
  const int mi = lane >> 3;
#pragma unroll
  for (int tp = 0; tp < 4; tp++) {
    const int t = CH * 8 + tp * 2;
    const uint32_t r0 = pack_bf16(fmaxf(acc[4 * t + 0], 0.f) * s0, fmaxf(acc[4 * t + 1], 0.f) * s0);
    const uint32_t r1 = pack_bf16(fmaxf(acc[4 * t + 2], 0.f) * s1, fmaxf(acc[4 * t + 3], 0.f) * s1);
    const uint32_t r2 = pack_bf16(fmaxf(acc[4 * t + 4], 0.f) * s0, fmaxf(acc[4 * t + 5], 0.f) * s0);
    const uint32_t r3 = pack_bf16(fmaxf(acc[4 * t + 6], 0.f) * s1, fmaxf(acc[4 * t + 7], 0.f) * s1);
    stsm_x4(base + (((tp * 2 + (mi >> 1)) ^ (lane & 7)) << 4), r0, r1, r2, r3);
  }
}

template <int N>
DEVI void phase_q(Ctx& c, int warp) {
  Acc<N> acc;
#pragma unroll
  for (int i = 0; i < N / 2; i++) acc[i] = 0.f;
  bare_groups<N>(acc, c, 0, 16);
  drain(c);
  const int lane = c.lane, mi = lane >> 3;
  const int row = warp * 16 + (lane & 7) + 8 * (mi & 1);
  const int sw = (row >> 1) & 3;
#pragma unroll
  for (int hh = 0; hh < 4; hh++) {
    const uint32_t base = c.sbase + OFF_KV + hh * 8192 + row * 64;
#pragma unroll
    for (int kv = 0; kv < 2; kv++) {
      const int t = 8 + kv * 8 + 2 * hh;
      stsm_x4(base + (((kv * 2 + (mi >> 1)) ^ sw) << 4),
              pack_bf16(acc[4 * t + 0], acc[4 * t + 1]), pack_bf16(acc[4 * t + 2], acc[4 * t + 3]),
              pack_bf16(acc[4 * t + 4], acc[4 * t + 5]), pack_bf16(acc[4 * t + 6], acc[4 * t + 7]));
    }
  }
  fence_async_smem();
  __syncwarp();
  if (lane == 0) mbar_arrive(c.bars + 8 * BAR_STG);
#pragma unroll
  for (int hh = 0; hh < 4; hh++)
    sts128(c.sbase + OFF_A + c.wg * 8192 + hh * 2048 + ((warp & 3) * 32 + lane) * 16,
           pack_bf16(acc[8 * hh], acc[8 * hh + 1]), pack_bf16(acc[8 * hh + 2], acc[8 * hh + 3]),
           pack_bf16(acc[8 * hh + 4], acc[8 * hh + 5]), pack_bf16(acc[8 * hh + 6], acc[8 * hh + 7]));
#pragma unroll
  for (int hh = 0; hh < 4; hh++) {
    const int q = 8 * hh, k = 32 + 8 * hh;
    float d0 = acc[q] * acc[k] + acc[q + 1] * acc[k + 1] + acc[q + 4] * acc[k + 4] + acc[q + 5] * acc[k + 5];
    float d1 = acc[q + 2] * acc[k + 2] + acc[q + 3] * acc[k + 3] + acc[q + 6] * acc[k + 6] + acc[q + 7] * acc[k + 7];
    d0 += __shfl_xor_sync(0xffffffffu, d0, 1); d1 += __shfl_xor_sync(0xffffffffu, d1, 1);
    d0 += __shfl_xor_sync(0xffffffffu, d0, 2); d1 += __shfl_xor_sync(0xffffffffu, d1, 2);
    if ((lane & 3) == hh)
      asm volatile("st.shared.u32 [%0], %1;" ::"r"(c.sbase + OFF_NM + (warp * 32 + lane) * 4), "r"(pack_bf16(-d0 * SC, -d1 * SC)) : "memory");
  }
  __syncwarp();
  if (lane == 0) mbar_arrive(c.bars + 8 * (BAR_QRDY + c.wg));
  if constexpr (N == 256) {
    Gate g;
    get_gate(g, c.sbase, warp, lane, c.t0);
    store_h_chunk<3>(acc, c.sbase + OFF_KV + 32768 + row * 128, lane, 1.f - g.g0, 1.f - g.g1);
    fence_async_smem();
    __syncwarp();
    if (lane == 0) mbar_arrive(c.bars + 8 * BAR_STE);
  }
}

DEVI void first_loads(const Params& P, uint32_t sbase, int e, int j, int rb) {
  const uint32_t bars = sbase + OFF_BAR, fb = bars + 8 * (BAR_FULLB + e), fa = bars + 8 * (BAR_FULLA + 1 + e);
  mbar_expect_tx(fa, 16384);
  mbar_expect_tx(fb, (j & 1) ? 12288 : 16384);
  if (e == 0) tma_load_2d(sbase + OFF_A + SLOT, &P.tmX, 0, rb * 128, fa);
#pragma unroll
  for (int r = 0; r < 2; r++) {
    tma_load_3d(sbase + OFF_B + e * SLOT + r * 8192, &P.tmWqkv, 64 * j, e * 32 + r * 16, 0, fb);
    if (!(j & 1)) tma_load_3d(sbase + OFF_B + e * SLOT + r * 8192 + 6144, &P.tmW1a, 0, e * 32 + r * 16, 24 + (j >> 1), fb);
  }
  if (e == 1) tma_load_2d(sbase + OFF_A + 2 * SLOT, &P.tmX, 64, rb * 128, fa);
}

__global__ void __cluster_dims__(2, 1, 1) __launch_bounds__(640, 1) fused_kernel(const __grid_constant__ Params P) {
  extern __shared__ __align__(1024) uint8_t smem_raw[];
  const uint32_t sbase = smem_u32(smem_raw);
  const uint32_t bars = sbase + OFF_BAR;
  const int tid = threadIdx.x, warp = tid >> 5, lane = tid & 31;
  const uint32_t rank = blockIdx.x & 1, peer = rank ^ 1;
  const int j = (blockIdx.x >> 1) & 7, rb = ((blockIdx.x >> 4) << 1) | rank;
  const uint32_t t0 = clk32();
#ifdef TRACE
  uint32_t gt0; asm volatile("mov.u32 %0, %%globaltimer_lo;" : "=r"(gt0));
#endif

  const int typeB = j & 1;
  if (tid == 544) {
    for (int s = 0; s < NA2; s++) mbar_init(bars + 8 * (BAR_FULLA + s), 1);
    for (int s = 0; s < NB; s++) mbar_init(bars + 8 * (BAR_FULLB + s), 1);
    fence_async_smem();
  } else if (tid < 8) {
    asm volatile("prefetch.tensormap [%0];" ::"l"(&P.tmX + tid) : "memory");
  } else if (tid == 512) {
    for (int s = 0; s < NA2; s++) mbar_init(bars + 8 * (BAR_EMPTYA + s), 9);
    for (int s = 0; s < NB; s++) mbar_init(bars + 8 * (BAR_EMPTYB + s), 16);
  } else if (tid == 576) {
    for (int s = 0; s < 2; s++) { mbar_init(bars + 8 * (BAR_KVFULL + s), 1); mbar_init(bars + 8 * (BAR_KVEMPTY + s), 8); mbar_init(bars + 8 * (BAR_OST + s), 4); mbar_init(bars + 8 * (BAR_QRDY + s), 4); }
    mbar_init(bars + 8 * BAR_STG, 8); mbar_init(bars + 8 * BAR_STE, 8); mbar_init(bars + 8 * BAR_KVOK, 1);
    mbar_init(bars + 8 * BAR_PIN, 1); mbar_init(bars + 8 * BAR_PFREE, 8); mbar_init(bars + 8 * BAR_GIN, 1);
  }
  if (tid >= 512 && lane == 0) asm volatile("fence.mbarrier_init.release.cluster;" ::: "memory");
#ifdef TRACE
  if (tid < 64) asm volatile("st.shared.u32 [%0], %1;" ::"r"(sbase + OFF_BAR + 640 + 4 * tid), "r"(0));
#endif
  const unsigned ep1 = ld_relaxed(&g_epoch) + 1;
  __syncwarp();
  cluster_arrive();
  if (tid == 544) { first_loads(P, sbase, 0, j, rb); first_loads(P, sbase, 1, j, rb); }
#if PF0 == 1
  if (tid == 544) { l2_prefetch(P.x + (size_t)(rb * 128 + j * 16) * DM, 16384); l2_prefetch((const uint8_t*)P.wqkv + blockIdx.x * 12288, 12288); }
#elif PF0 == 2
  if (tid == 320) { l2_prefetch(P.x + (size_t)(rb * 128 + j * 16) * DM, 16384); l2_prefetch((const uint8_t*)P.wqkv + blockIdx.x * 12288, 12288); }
#endif
  __syncwarp();

  const int on = 12 + 4 * typeB;

  if (warp < 8) {
    asm volatile("setmaxnreg.inc.sync.aligned.u32 160;");
    cluster_wait();
    const int wg = __shfl_sync(0xffffffffu, warp >> 2, 0);
    Ctx c{sbase, bars, peer, t0, ((sbase & 0x3FFFF) + OFF_A + wg * 8192) >> 4, ((sbase & 0x3FFFF) + OFF_B) >> 4, wg, lane, 1, 0, 0u, 0u, 32 + on + 4 - NB, 0, -1, -1};
    if (tid == 0) TR(0);
    if (typeB) phase_q<192>(c, warp);
    else phase_q<256>(c, warp);
    asm volatile("setmaxnreg.dec.sync.aligned.u32 128;");
    if (tid == 0) TR(2);
    {
      Acc<192> acc;
#pragma unroll
      for (int i = 0; i < 96; i++) acc[i] = 0.f;
      bare_groups<192>(acc, c, 0, SHS);
      bare_groups<192, SH>(acc, c, SHS, 16);
      Gate at;
      get_gate(at, sbase, warp, lane, t0);
      drain(c);
      if (tid == 0) TR(1);
      const uint32_t rowoff = (warp * 16 + (lane & 7) + 8 * ((lane >> 3) & 1)) * 128;
      const float s0 = 1.f - at.g0, s1 = 1.f - at.g1;
      constexpr int e0 = 1, e1 = 2, e2 = 3;
      mbar_wait(bars + 8 * (BAR_FULLA + e0), 0, t0);
      store_h_chunk<0>(acc, sbase + OFF_A + e0 * SLOT + rowoff, lane, s0, s1);
      mbar_wait(bars + 8 * (BAR_FULLA + e1), 0, t0);
      store_h_chunk<1>(acc, sbase + OFF_A + e1 * SLOT + rowoff, lane, s0, s1);
      mbar_wait(bars + 8 * (BAR_FULLA + e2), 0, t0);
      store_h_chunk<2>(acc, sbase + OFF_A + e2 * SLOT + rowoff, lane, s0, s1);
    }
    fence_async_smem();
    wg_bar(wg);
    if (lane == 0) mbar_arrive(bars + 8 * BAR_STG);
    if (tid == 0) TR(4);
    float own[32];
    {
      Acc<128> acc;
#pragma unroll
      for (int i = 0; i < 64; i++) acc[i] = 0.f;
      bare_groups<128, SHO>(acc, c, 0, on);
      drain(c);
      if (tid == 0) TR(5);
      if (lane == 0) mbar_arrive(bars + 8 * BAR_PFREE);
      named_bar<3>(256);
      const uint32_t pst = sbase + OFF_B + ((30 + on) % NB) * SLOT + wg * 8192 + (tid & 127) * 16;
#pragma unroll
      for (int i = 0; i < 4; i++) {
        uint32_t r[4];
#pragma unroll
        for (int k = 0; k < 4; k++) {
          const int idx = 8 * i + 2 * k;
          const float lo = typeB ? acc[idx] : acc[32 + idx], hi = typeB ? acc[idx + 1] : acc[32 + idx + 1];
          r[k] = pack_bf16(lo, hi);
        }
        sts128(pst + i * 2048, r[0], r[1], r[2], r[3]);
      }
#pragma unroll
      for (int i = 0; i < 32; i++) own[i] = typeB ? acc[32 + i] : acc[i];
      fence_async_smem();
      __syncwarp();
      if (lane == 0) mbar_arrive(bars + 8 * BAR_STG);
    }
#pragma unroll 1
    for (int g = 0; g < 8; g++) {
      const uint32_t a16 = c.a16 + c.ai * (SLOT >> 4);
      const uint32_t b16 = c.b16 + c.bi * (SLOT >> 4) + (g & 1) * 512;
      if (g == 6) {
        mbar_wait(bars + 8 * BAR_PIN, 0, t0);
        const uint32_t pin = sbase + OFF_B + ((31 + on) % NB) * SLOT + wg * 8192 + (tid & 127) * 16;
#pragma unroll
        for (int i = 0; i < 4; i++) {
          const uint4 v = lds128(pin + i * 2048);
          const uint32_t r[4] = {v.x, v.y, v.z, v.w};
#pragma unroll
          for (int k = 0; k < 4; k++) { own[8 * i + 2 * k] += __uint_as_float(r[k] << 16); own[8 * i + 2 * k + 1] += __uint_as_float(r[k] & 0xffff0000u); }
        }
        named_bar<3>(256);
        if (tid == 0) TR(7);
      }
      gemm_wait(c);
      wgmma_fence();
#pragma unroll
      for (int s = 0; s < 4; s++) wgmma_ss_n64(own, desc_sw128<16>(a16 + s * 2), desc_sw128<2048>(b16 + s * 128));
      wgmma_commit();
      wgmma_wait<0>();
      if (lane == 2) mbar_arrive(bars + 8 * (BAR_EMPTYA + c.ai));
      c.aph ^= 1u << c.ai;
      c.ae++; c.ai = a_slot(c.ae, 0);
      if (g & 1) { if (++c.bi == NB) { c.bi = 0; c.bph ^= 1; } }
    }
    if (tid == 0) TR(6);
    {
      const uint32_t ob = sbase + OFF_B + ((31 + on) % NB) * SLOT;
      const uint32_t wb = ob + warp * 2048;
      const uint32_t orow = wb + ((lane & 7) + 8 * ((lane >> 3) & 1)) * 128;
#pragma unroll
      for (int i = 0; i < 4; i++)
        stsm_x4(orow + (((i * 2 + (lane >> 4)) ^ (lane & 7)) << 4), pack_bf16(own[8 * i], own[8 * i + 1]), pack_bf16(own[8 * i + 2], own[8 * i + 3]),
                pack_bf16(own[8 * i + 4], own[8 * i + 5]), pack_bf16(own[8 * i + 6], own[8 * i + 7]));
      __syncwarp();
      uint4* o = (uint4*)(P.out + (size_t)(rb * 128 + warp * 16 + (lane >> 3)) * DM + j * 64) + (lane & 7);
#pragma unroll
      for (int i = 0; i < 4; i++) {
        const int r = i * 4 + (lane >> 3);
        o[i * 4 * (DM / 8)] = lds128(wb + r * 128 + (((lane & 7) ^ (r & 7)) << 4));
      }
    }
    if (tid == 0) TR(8);
#ifdef TRACE
    named_bar<3>(256);
    if (tid < 64) { uint32_t v; asm volatile("ld.shared.u32 %0, [%1];" : "=r"(v) : "r"(sbase + OFF_BAR + 640 + 4 * tid));
      if (tid == 16) v = gt0;
      if (tid == 17) asm volatile("mov.u32 %0, %%globaltimer_lo;" : "=r"(v));
      if (tid == 18) v = clk32() - t0;
      g_trace[blockIdx.x * 64 + tid] = v; }
#endif
  } else if (warp < 16) {
    asm volatile("setmaxnreg.dec.sync.aligned.u32 56;");
    cluster_wait();
    const int aw = __shfl_sync(0xffffffffu, (warp >> 2) & 1, 0);
    {
      const int rowg = rb * 128 + j * 16 + (warp - 8) * 2;
      const uint4* gw = (const uint4*)P.gate_w;
      const uint4* xr = (const uint4*)(P.x + (size_t)rowg * DM);
      mbar_wait(bars + 8 * (BAR_FULLB + 1), 0, t0);
      const uint4 w0 = __ldg(gw + lane), w1 = __ldg(gw + 32 + lane);
      const uint4 xa0 = __ldg(xr + lane), xa1 = __ldg(xr + 32 + lane), xb0 = __ldg(xr + 64 + lane), xb1 = __ldg(xr + 96 + lane);
#pragma unroll
      for (int i = 0; i < 4; i++) sts128(sbase + OFF_KV + 32768 + i * 4096 + (tid - 256) * 16, 0u, 0u, 0u, 0u);
      const uint32_t wa[8] = {w0.x, w0.y, w0.z, w0.w, w1.x, w1.y, w1.z, w1.w};
      const uint32_t xa[8] = {xa0.x, xa0.y, xa0.z, xa0.w, xa1.x, xa1.y, xa1.z, xa1.w};
      const uint32_t xb[8] = {xb0.x, xb0.y, xb0.z, xb0.w, xb1.x, xb1.y, xb1.z, xb1.w};
      float za = 0.f, zb = 0.f;
#pragma unroll
      for (int e = 0; e < 8; e++) {
        const float wl = __uint_as_float(wa[e] << 16), wh = __uint_as_float(wa[e] & 0xffff0000u);
        za = fmaf(__uint_as_float(xa[e] << 16), wl, za); za = fmaf(__uint_as_float(xa[e] & 0xffff0000u), wh, za);
        zb = fmaf(__uint_as_float(xb[e] << 16), wl, zb); zb = fmaf(__uint_as_float(xb[e] & 0xffff0000u), wh, zb);
      }
#pragma unroll
      for (int o = 16; o > 0; o >>= 1) { za += __shfl_xor_sync(0xffffffffu, za, o); zb += __shfl_xor_sync(0xffffffffu, zb, o); }
      if (lane < 2) asm volatile("st.shared.f32 [%0], %1;" ::"r"(sbase + OFF_GST + (warp - 8) * 8 + lane * 4), "f"(1.f / (1.f + __expf(-(lane ? zb : za)))) : "memory");
      fence_async_smem();
      named_bar<6>(256);
      if (tid == 256) {
        bulk_store(&g_gate[rb * 128 + j * 16], sbase + OFF_GST, 64);
        bulk_commit(); bulk_wait_all();
        flag_add(&g_flag_g[rb * FS]);
        flag_wait(&g_flag_g[rb * FS], ep1 * 8, t0);
        fence_async_global();
        mbar_expect_tx(bars + 8 * BAR_GIN, 512);
        bulk_load(sbase + OFF_GIN, &g_gate[rb * 128], 512, bars + 8 * BAR_GIN);
        TR(10);
      }
      __syncwarp();
    }
    mbar_wait(bars + 8 * (BAR_QRDY + aw), 0, t0);
    asm volatile("setmaxnreg.inc.sync.aligned.u32 96;");
    attention(sbase, aw, warp & 3, lane, rb, t0);
    if (tid == 256) TR(3);
  } else {
    asm volatile("setmaxnreg.dec.sync.aligned.u32 32;");
    if (warp == 16) {
      __syncwarp();
      cluster_wait();
#ifdef TRACE3
      if (lane == 0) TR(51);
#endif
      if (lane == 0) {
        int bi = 2; uint32_t bph = 1;
        const int nb = 32 + on + 4;
        for (int eb = 2; eb < nb; eb++) {
          if (eb == 4 || eb == 6) {
            const int ea = eb >> 1;
            mbar_expect_tx(bars + 8 * (BAR_FULLA + 1 + ea), 16384);
            tma_load_2d(sbase + OFF_A + (1 + ea) * SLOT, &P.tmX, ea * 64, rb * 128, bars + 8 * (BAR_FULLA + 1 + ea));
          }
          const uint32_t fb = bars + 8 * (BAR_FULLB + bi), dst = sbase + OFF_B + bi * SLOT + rank * 8192;
          mbar_wait(bars + 8 * (BAR_EMPTYB + bi), bph, t0);
          if (eb < 16) {
            mbar_expect_tx(fb, typeB ? 12288 : 16384);
            tma_load_3d_mc(dst, &P.tmWqkv, 64 * j, eb * 32 + rank * 16, 0, fb);
            if (!typeB) tma_load_3d_mc(dst + 6144, &P.tmW1a, 0, eb * 32 + rank * 16, 24 + (j >> 1), fb);
          }
          else if (eb < 32) { mbar_expect_tx(fb, 12288); tma_load_3d_mc(dst, &P.tmW1b, 0, (eb - 16) * 32 + rank * 16, 3 * j, fb); }
          else if (eb < 32 + on) { int ow; const int ch = oh_chunk(j, eb - 32, ow); mbar_expect_tx(fb, 16384); tma_load_3d_mc(dst, &P.tmW2, 0, ch * 64 + rank * 32, (j >> 1) * 2, fb); }
          else { mbar_expect_tx(fb, 16384); tma_load_4d_mc(dst, &P.tmWo, 64 * j, 0, eb - 32 - on, rank * 4, fb); }
#ifdef TRACE3
          if (eb < 6) TR(32 + eb);
#endif
          if (++bi == NB) { bi = 0; bph ^= 1; }
#ifndef NOPF
          if (eb == PFAT) {
            const int b = blockIdx.x;
             int ch = ea & 7, need = -1;
          if (ea >= 16 + on) { need = 8 + ea - 16 - on; ch = 20 + need; }
          else if (ea >= 19) ch = oh_chunk(j, ea - 16, need);
          if (need >= 0 && !((ready >> need) & 1)) {
            const unsigned* fp = need < 8 ? &g_flag_h[rb * 8 * FS] : need < 16 ? &g_flag_o[rb * 8 * FS] : &g_flag_e[rb * 8 * FS];
            const unsigned tgt = (need & 8) ? ep1 * 4 : ep1;
            do {
              unsigned v[8];
#pragma unroll
              for (int i = 0; i < 8; i++) v[i] = ld_relaxed(fp + i * FS);
#pragma unroll
              for (int i = 0; i < 8; i++) if ((int)(v[i] - tgt) >= 0) ready |= 1u << (i + (need & 24));
            } while (!((ready >> need) & 1) && clk32() - t0 < TIMEOUT);
            fence_async_global();
          }
 1; ea < 5; ea++) mbar_arrive(bars + 8 * (BAR_EMPTYA + ea));
        uint32_t aph = 0xE1;
        const int na = 16 + on + 8;
        unsigned ready = 0;
        for (int ea = 4; ea < na; ea++) {
          const int ai = a_slot(ea, 20 + on);
          const uint32_t fb = bars + 8 * (BAR_FULLA + ai), dst = sbase + OFF_A + ai * SLOT;
          int ch = ea & 7;
          if (ea >= 19) {
            ch = ea >= 16 + on ? 12 - on + ea : oh_chunk(j, ea - 16);
            while (!((ready >> ch) & 1) && clk32() - t0 < TIMEOUT) {
              const unsigned* fp = ch < 24 ? &g_flag_h[rb * 8 * FS] : ch < 28 ? &g_flag_e[rb * 8 * FS] : &g_flag_o[rb * 8 * FS];
              unsigned v[8];
#pragma unroll
              for (int i = 0; i < 8; i++) v[i] = ld_relaxed(fp + i * FS);
#pragma unroll
              for (int i = 0; i < 8; i++) {
                if (ch < 24) ready |= (uint64_t)((1u << min(max((int)(v[i] - (ep1 - 1) * 3), 0), 3)) - 1) << (3 * i);
                else if (ch < 28) { if (!(i & 1) && (int)(v[i] - ep1) >= 0) ready |= 1ull << (24 + (i >> 1)); }
                else if ((int)(v[i] - ep1 * 4) >= 0) ready |= 1ull << (28 + i);
              }
              fence_async_global();
            }
          }
          mbar_wait(bars + 8 * (BAR_EMPTYA + ai), (aph >> ai) & 1, t0);
          if (ea >= 16 && ea < 19) mbar_arrive(fb);
          else {
            mbar_arrive(bars + 8 * (BAR_EMPTYA + ai));
            mbar_expect_tx(fb, 16384);
            tma_load_2d(dst, ea < 16 ? &P.tmX : &P.tmHO, ch * 64, rb * 128, fb);
          }
#if !defined(TRACE2) && !defined(TRACE3)
          TR(24 + ea);
#endif
          aph ^= 1u << ai;
        }
      }
    } else {
      const int wg = warp - 18;
      cluster_wait();
      if (lane == 0 && wg == 0) {
        const uint32_t stg = bars + 8 * BAR_STG;
        mbar_wait(stg, 0, t0);
        for (int hh = 0; hh < 4; hh++) bulk_store(g_kv + ((size_t)(4 * j + hh) * SEQ + rb * 128) * 64, sbase + OFF_KV + hh * 8192, 8192);
        bulk_commit(); bulk_wait_all();
        flag_add(&g_flag_kv[(rb * 8 + j) * FS]);
        TR(21);
        if (!typeB) {
          mbar_wait(bars + 8 * BAR_STE, 0, t0);
          tma_store_2d(&P.tmHO, (24 + (j >> 1)) * 64, rb * 128, sbase + OFF_KV + 32768);
          bulk_commit(); bulk_wait_all();
          flag_add(&g_flag_e[(rb * 8 + j) * FS]);
        }
        mbar_arrive(bars + 8 * BAR_KVOK);
        mbar_wait(stg, 1, t0);
        for (int i = 0; i < 3; i++) { tma_store_2d(&P.tmHO, (3 * j + i) * 64, rb * 128, sbase + OFF_A + (1 + i) * SLOT); bulk_commit(); }
        asm volatile("cp.async.bulk.wait_group.read 2;" ::: "memory");
        mbar_arrive(bars + 8 * (BAR_EMPTYA + 1));
        asm volatile("cp.async.bulk.wait_group.read 1;" ::: "memory");
        mbar_arrive(bars + 8 * (BAR_EMPTYA + 2));
        bulk_wait_all();
        flag_add(&g_flag_h[(rb * 8 + j) * FS]); mbar_arrive(bars + 8 * (BAR_EMPTYA + 3));
        TR(22);
        {
          const unsigned old = atomicAdd(&g_done, 1u);
          if (old == gridDim.x - 1) { g_done = 0; *(volatile unsigned*)&g_epoch = ep1; }
        }
        mbar_wait(stg, 0, t0);
        bulk_store(g_part + (size_t)(rb * 8 + (j ^ 1)) * 16384, sbase + OFF_B + ((30 + on) % NB) * SLOT, 16384);
        bulk_commit(); bulk_wait_all();
        flag_add(&g_flag_p[(rb * 8 + (j ^ 1)) * FS]);
        TR(23);
      } else if (lane == 0) {
        const int nblk = rb >= 2 ? 3 : rb + 1;
        const uint32_t kvbytes = nblk * 8192;
        const uint8_t* kvsrc = g_kv + ((size_t)(4 * j) * SEQ + (rb + 1 - nblk) * 128) * 64;
        const uint32_t kvdst = sbase + OFF_KV + (3 - nblk) * 8192;
        {
          const unsigned* f0 = &g_flag_kv[(rb * 8 + j) * FS];
          const unsigned* f1 = rb >= 1 ? f0 - 8 * FS : f0;
          const unsigned* f2 = rb >= 2 ? f0 - 16 * FS : f0;
          unsigned v0, v1, v2;
          do { v0 = ld_relaxed(f0); v1 = ld_relaxed(f1); v2 = ld_relaxed(f2); }
          while (((int)(v0 - ep1) < 0 || (int)(v1 - ep1) < 0 || (int)(v2 - ep1) < 0) && clk32() - t0 < TIMEOUT);
        }
        TR(11);
        mbar_wait(bars + 8 * BAR_GIN, 0, t0);
        fence_async_global();
        mbar_expect_tx(bars + 8 * BAR_KVFULL, kvbytes);
        bulk_load(kvdst, kvsrc, kvbytes, bars + 8 * BAR_KVFULL);
        mbar_wait(bars + 8 * BAR_KVOK, 0, t0);
        mbar_expect_tx(bars + 8 * (BAR_KVFULL + 1), kvbytes);
        bulk_load(kvdst + KVBUF, kvsrc + (size_t)SEQ * 64, kvbytes, bars + 8 * (BAR_KVFULL + 1));
        for (int hh = 0; hh < 4; hh++) {
          for (int aw = 0; aw < 2; aw++) {
            mbar_wait(bars + 8 * (BAR_OST + aw), hh & 1, t0);
            tma_store_2d(&P.tmOs, DFF + hh * 128 + j * 16, rb * 128 + aw * 64, sbase + OFF_A + aw * 8192 + hh * 2048);
          }
          bulk_commit();
          if (hh < 2) {
            mbar_wait(bars + 8 * (BAR_KVEMPTY + hh), 0, t0);
            mbar_expect_tx(bars + 8 * (BAR_KVFULL + hh), kvbytes);
            bulk_load(kvdst + hh * KVBUF, kvsrc + (size_t)(hh + 2) * SEQ * 64, kvbytes, bars + 8 * (BAR_KVFULL + hh));
          }
          bulk_wait_all();
          flag_add(&g_flag_o[(rb * 8 + hh * 2 + (j >> 2)) * FS]);
          TR(12 + hh);
        }
      }
    }
  }
}

typedef CUresult (*EncodeFn)(CUtensorMap*, CUtensorMapDataType, cuuint32_t, void*, const cuuint64_t*, const cuuint64_t*, const cuuint32_t*,
                             const cuuint32_t*, CUtensorMapInterleave, CUtensorMapSwizzle, CUtensorMapL2promotion, CUtensorMapFloatOOBfill);

void make_map(EncodeFn enc, CUtensorMap* m, const void* ptr, int rank, const cuuint64_t* dims, const cuuint64_t* strides, const cuuint32_t* box,
              CUtensorMapSwizzle sw = CU_TENSOR_MAP_SWIZZLE_128B) {
  cuuint32_t es[4] = {1, 1, 1, 1};
  enc(m, CU_TENSOR_MAP_DATA_TYPE_BFLOAT16, rank, const_cast<void*>(ptr), dims, strides, box, es, CU_TENSOR_MAP_INTERLEAVE_NONE, sw,
      CU_TENSOR_MAP_L2_PROMOTION_L2_256B, CU_TENSOR_MAP_FLOAT_OOB_FILL_NONE);
}

}

extern "C" void kernel_launch(void* const* d_in, const int* in_sizes, int n_in, void* d_out, int out_size) {
  (void)in_sizes; (void)n_in; (void)out_size;
  static EncodeFn enc = nullptr;
  static void* ho_ptr = nullptr;
  if (!enc) {
    void* fn = nullptr; cudaDriverEntryPointQueryResult st;
    cudaGetDriverEntryPoint("cuTensorMapEncodeTiled", &fn, cudaEnableDefault, &st);
    enc = (EncodeFn)fn;
    cudaGetSymbolAddress(&ho_ptr, g_ho);
    cudaFuncSetAttribute(fused_kernel, cudaFuncAttributeMaxDynamicSharedMemorySize, SMEM_BYTES);
  }
  const __nv_bfloat16* x = (const __nv_bfloat16*)d_in[0];
  const __nv_bfloat16* wqkv = (const __nv_bfloat16*)d_in[1];
  const __nv_bfloat16* wo = (const __nv_bfloat16*)d_in[2];
  const __nv_bfloat16* w1 = (const __nv_bfloat16*)d_in[4];
  const __nv_bfloat16* w2 = (const __nv_bfloat16*)d_in[5];
  const __nv_bfloat16* gate_w = (const __nv_bfloat16*)d_in[6];
  Params P;
  { cuuint64_t d[2] = {DM, SEQ}, s[1] = {DM * 2}; cuuint32_t b[2] = {64, 128}; make_map(enc, &P.tmX, x, 2, d, s, b); }
  { cuuint64_t d[3] = {512, 512, 3}, s[2] = {1536 * 2, 512 * 2}; cuuint32_t b[3] = {64, 16, 3}; make_map(enc, &P.tmWqkv, wqkv, 3, d, s, b); }
  { cuuint64_t d[3] = {64, 512, 28}, s[2] = {DFF * 2, 128}; cuuint32_t b[3] = {64, 16, 1}; make_map(enc, &P.tmW1a, w1, 3, d, s, b);
    b[2] = 3; make_map(enc, &P.tmW1b, w1, 3, d, s, b); }
  { cuuint64_t d[3] = {64, DFF, 8}, s[2] = {DM * 2, 128}; cuuint32_t b[3] = {64, 32, 2}; make_map(enc, &P.tmW2, w2, 3, d, s, b); }
  { cuuint64_t d[4] = {DM, 16, 4, 8}, s[3] = {DM * 2, 16 * DM * 2, 64 * DM * 2}; cuuint32_t b[4] = {64, 16, 1, 4}; make_map(enc, &P.tmWo, wo, 4, d, s, b); }
  { cuuint64_t d[2] = {KHO, SEQ}, s[1] = {KHO * 2}; cuuint32_t b[2] = {64, 128}; make_map(enc, &P.tmHO, ho_ptr, 2, d, s, b);
    b[1] = 64; b[0] = 16; make_map(enc, &P.tmOs, ho_ptr, 2, d, s, b, CU_TENSOR_MAP_SWIZZLE_NONE); }
  P.x = x; P.gate_w = gate_w; P.w1 = w1; P.w2 = w2; P.wo = wo; P.wqkv = wqkv; P.out = (__nv_bfloat16*)d_out;
  fused_kernel<<<128, 640, SMEM_BYTES>>>(P);
}

#ifdef TRACE
extern "C" void dbg_trace(unsigned* host) { cudaDeviceSynchronize(); cudaMemcpyFromSymbol(host, g_trace, sizeof(g_trace)); }
#endif
#ifdef DEBUG_EXPORTS
extern "C" void dbg_copy(int which, void* dst) {
  cudaDeviceSynchronize();
  if (which == 0) cudaMemcpyFromSymbol(dst, g_kv, sizeof(g_kv), 0, cudaMemcpyDeviceToDevice);
  if (which == 2) cudaMemcpyFromSymbol(dst, g_ho, sizeof(g_ho), 0, cudaMemcpyDeviceToDevice);
  if (which == 3) cudaMemcpyFromSymbol(dst, g_gate, sizeof(g_gate), 0, cudaMemcpyDeviceToDevice);
  cudaDeviceSynchronize();
}
#endif
```

```cpp
#include <cuda_runtime.h>
#include <cuda_bf16.h>
#include <cuda.h>
#include <stdint.h>

#define DEVI __device__ __forceinline__

namespace {

constexpr int SEQ = 2048, DM = 512, DFF = 1792, KHO = 2304;
constexpr int NA = 5, NB = 6, SLOT = 16384, KVBUF = 24576;
constexpr int NA2 = 8;
constexpr int OFF_B = 0, OFF_A = NB * SLOT, OFF_KV = OFF_A + NA * SLOT, OFF_BAR = OFF_KV + 2 * KVBUF;
constexpr int OFF_GST = OFF_BAR + 512;
constexpr int OFF_GIN = OFF_BAR + 1024;
constexpr int OFF_NM = OFF_BAR + 1536;
constexpr int SMEM_BYTES = OFF_BAR + 2560;
constexpr uint32_t TIMEOUT = 1u << 28;
#ifndef WAIT_HINT_NS
#define WAIT_HINT_NS 20000u
#endif
#ifndef PFAT
#define PFAT 8
#endif
#ifndef SH
#define SH true
#endif
#ifndef SHW
#define SHW 0
#endif
#ifndef SHG
#define SHG 1
#endif
#ifndef PF0
#define PF0 0
#endif
#ifndef SHO
#define SHO true
#endif
#ifndef SHS
#define SHS 6
#endif
#ifndef TB
#define TB 0
#endif
#ifndef SHSB
#define SHSB SHS
#endif
#ifndef HT
#define HT 3
#endif
constexpr int FS = 8;

constexpr int BAR_FULLA = 0, BAR_EMPTYA = BAR_FULLA + NA2, BAR_FULLB = BAR_EMPTYA + NA2, BAR_EMPTYB = BAR_FULLB + NB,
              BAR_KVFULL = BAR_EMPTYB + NB, BAR_KVEMPTY = BAR_KVFULL + 4, BAR_STG = BAR_KVEMPTY + 2, BAR_PIN = BAR_STG + 2, BAR_GATE = BAR_PIN + 1, BAR_STE = BAR_GATE + 2, BAR_PFREE = BAR_STE + 2, BAR_GIN = BAR_PFREE + 1, BAR_OST = BAR_GIN + 1, BAR_QRDY = BAR_OST + 2, BAR_KVOK = BAR_QRDY + 2, BAR_HELP = BAR_KVOK + 1;

__device__ __align__(1024) uint8_t g_kv[32 * SEQ * 64];
__device__ __align__(1024) __nv_bfloat16 g_ho[SEQ * KHO];
__device__ __align__(1024) uint8_t g_part[128 * 16384];
__device__ __align__(128) float g_gate[SEQ];
__device__ __align__(128) float4 g_help[128 * 3 * 256];
__device__ unsigned g_flag_kv[128 * FS], g_flag_h[128 * FS], g_flag_o[128 * FS], g_flag_g[16 * FS], g_flag_p[128 * FS], g_flag_e[128 * FS];
__device__ unsigned g_epoch, g_done;
#ifdef TRACE
__device__ unsigned g_trace[128 * 64];
#define TR(i) do { asm volatile("st.shared.u32 [%0], %1;" ::"r"(sbase + OFF_BAR + 640 + 4 * (i)), "r"(clk32() - t0)); } while (0)
#else
#define TR(i) do {} while (0)
#endif

struct Params {
  CUtensorMap tmX, tmWqkv, tmW1a, tmW1b, tmW2, tmWo, tmHO, tmOs;
  const __nv_bfloat16* x;
  const __nv_bfloat16* gate_w;
  const __nv_bfloat16* w1;
  const __nv_bfloat16* w2;
  const __nv_bfloat16* wo;
  const __nv_bfloat16* wqkv;
  __nv_bfloat16* out;
};

DEVI uint32_t smem_u32(const void* p) { return (uint32_t)__cvta_generic_to_shared(p); }
DEVI uint32_t clk32() { uint32_t c; asm volatile("mov.u32 %0, %%clock;" : "=r"(c)); return c; }
DEVI void mbar_init(uint32_t bar, uint32_t cnt) { asm volatile("mbarrier.init.shared::cta.b64 [%0], %1;" ::"r"(bar), "r"(cnt)); }
DEVI void mbar_expect_tx(uint32_t bar, uint32_t bytes) { asm volatile("mbarrier.arrive.expect_tx.shared::cta.b64 _, [%0], %1;" ::"r"(bar), "r"(bytes) : "memory"); }
DEVI void mbar_arrive(uint32_t bar) { asm volatile("mbarrier.arrive.shared::cta.b64 _, [%0];" ::"r"(bar) : "memory"); }
DEVI void mbar_arrive_cluster(uint32_t bar, uint32_t cta) {
  asm volatile("{ .reg .b32 ra; mapa.shared::cluster.u32 ra, %0, %1; mbarrier.arrive.shared::cluster.b64 _, [ra]; }" ::"r"(bar), "r"(cta) : "memory");
}
DEVI void mbar_wait(uint32_t bar, uint32_t parity, uint32_t t0) {
  asm volatile("{ .reg .pred p; .reg .u32 c;\n"
               "mbarrier.try_wait.parity.shared::cta.b64 p, [%0], %1;\n"
               "@p bra DONE_%=;\n"
               "WAIT_%=:\n"
               "mbarrier.try_wait.parity.shared::cta.b64 p, [%0], %1, %4;\n"
               "@p bra DONE_%=;\n"
               "mov.u32 c, %%clock; sub.u32 c, c, %2; setp.lt.u32 p, c, %3;\n"
               "@p bra WAIT_%=;\n"
               "DONE_%=: }" ::"r"(bar), "r"(parity), "r"(t0), "n"(TIMEOUT), "r"(WAIT_HINT_NS) : "memory");
}
DEVI unsigned ld_relaxed(const unsigned* p) { unsigned v; asm volatile("ld.relaxed.gpu.global.u32 %0, [%1];" : "=r"(v) : "l"(p) : "memory"); return v; }
DEVI void flag_wait(const unsigned* p, unsigned target, uint32_t t0) {
  while ((int)(ld_relaxed(p) - target) < 0) { if (clk32() - t0 > TIMEOUT) break; }
}
DEVI void flag_add(unsigned* p) { asm volatile("red.relaxed.gpu.global.add.u32 [%0], 1;" ::"l"(p) : "memory"); }
DEVI void fence_async_smem() { asm volatile("fence.proxy.async.shared::cta;" ::: "memory"); }
DEVI void fence_async_global() { asm volatile("fence.proxy.async.global;" ::: "memory"); }
DEVI void tma_load_2d(uint32_t dst, const CUtensorMap* m, int c0, int c1, uint32_t bar) {
  asm volatile("cp.async.bulk.tensor.2d.shared::cluster.global.mbarrier::complete_tx::bytes [%0], [%1, {%3, %4}], [%2];" ::"r"(dst), "l"(m), "r"(bar), "r"(c0), "r"(c1) : "memory");
}
DEVI void tma_load_3d(uint32_t dst, const CUtensorMap* m, int c0, int c1, int c2, uint32_t bar) {
  asm volatile("cp.async.bulk.tensor.3d.shared::cluster.global.mbarrier::complete_tx::bytes [%0], [%1, {%3, %4, %5}], [%2];"
               ::"r"(dst), "l"(m), "r"(bar), "r"(c0), "r"(c1), "r"(c2) : "memory");
}
DEVI void tma_load_3d_mc(uint32_t dst, const CUtensorMap* m, int c0, int c1, int c2, uint32_t bar) {
  asm volatile("cp.async.bulk.tensor.3d.shared::cluster.global.mbarrier::complete_tx::bytes.multicast::cluster [%0], [%1, {%3, %4, %5}], [%2], %6;"
               ::"r"(dst), "l"(m), "r"(bar), "r"(c0), "r"(c1), "r"(c2), "h"((uint16_t)3) : "memory");
}
DEVI void tma_load_4d_mc(uint32_t dst, const CUtensorMap* m, int c0, int c1, int c2, int c3, uint32_t bar) {
  asm volatile("cp.async.bulk.tensor.4d.shared::cluster.global.mbarrier::complete_tx::bytes.multicast::cluster [%0], [%1, {%3, %4, %5, %6}], [%2], %7;"
               ::"r"(dst), "l"(m), "r"(bar), "r"(c0), "r"(c1), "r"(c2), "r"(c3), "h"((uint16_t)3) : "memory");
}
DEVI void tma_store_2d(const CUtensorMap* m, int c0, int c1, uint32_t src) {
  asm volatile("cp.async.bulk.tensor.2d.global.shared::cta.bulk_group [%0, {%1, %2}], [%3];" ::"l"(m), "r"(c0), "r"(c1), "r"(src) : "memory");
}
DEVI void bulk_store(void* dst, uint32_t src, uint32_t bytes) {
  asm volatile("cp.async.bulk.global.shared::cta.bulk_group [%0], [%1], %2;" ::"l"(dst), "r"(src), "r"(bytes) : "memory");
}
DEVI void bulk_load(uint32_t dst, const void* src, uint32_t bytes, uint32_t bar) {
  asm volatile("cp.async.bulk.shared::cluster.global.mbarrier::complete_tx::bytes [%0], [%1], %2, [%3];" ::"r"(dst), "l"(src), "r"(bytes), "r"(bar) : "memory");
}
DEVI void bulk_commit() { asm volatile("cp.async.bulk.commit_group;" ::: "memory"); }
DEVI void bulk_wait_all() { asm volatile("cp.async.bulk.wait_group 0;" ::: "memory"); }
DEVI void l2_prefetch(const void* p, uint32_t bytes) { asm volatile("cp.async.bulk.prefetch.L2.global [%0], %1;" ::"l"(p), "r"(bytes) : "memory"); }
DEVI void cluster_arrive() { asm volatile("barrier.cluster.arrive.relaxed.aligned;" ::: "memory"); }
DEVI void cluster_wait() { asm volatile("barrier.cluster.wait.aligned;" ::: "memory"); }
template <int ID> DEVI void named_bar(int n) { asm volatile("bar.sync %0, %1;" ::"n"(ID), "r"(n) : "memory"); }
DEVI void wg_bar(int wg) { if (wg == 0) named_bar<1>(128); else named_bar<2>(128); }
DEVI void wgmma_fence() { asm volatile("wgmma.fence.sync.aligned;" ::: "memory"); }
DEVI void wgmma_commit() { asm volatile("wgmma.commit_group.sync.aligned;" ::: "memory"); }
template <int N> DEVI void wgmma_wait() { asm volatile("wgmma.wait_group.sync.aligned %0;" ::"n"(N) : "memory"); }
template <uint32_t LBO> DEVI uint64_t desc_sw128(uint32_t a16) {
  return ((uint64_t)(0x40000000u | (1024 >> 4)) << 32) | (a16 + ((LBO >> 4) << 16));
}
DEVI uint64_t desc_sw64(uint32_t a16) {
  return ((uint64_t)(0x80000000u | (512 >> 4)) << 32) | (a16 + ((512 >> 4) << 16));
}
DEVI uint32_t pack_bf16(float lo, float hi) { uint32_t r; asm("cvt.rn.bf16x2.f32 %0, %1, %2;" : "=r"(r) : "f"(hi), "f"(lo)); return r; }
DEVI void stsm_x4(uint32_t addr, uint32_t r0, uint32_t r1, uint32_t r2, uint32_t r3) {
  asm volatile("stmatrix.sync.aligned.m8n8.x4.shared.b16 [%0], {%1, %2, %3, %4};" ::"r"(addr), "r"(r0), "r"(r1), "r"(r2), "r"(r3) : "memory");
}
DEVI void sts128(uint32_t addr, uint32_t r0, uint32_t r1, uint32_t r2, uint32_t r3) {
  asm volatile("st.shared.v4.b32 [%0], {%1, %2, %3, %4};" ::"r"(addr), "r"(r0), "r"(r1), "r"(r2), "r"(r3) : "memory");
}
DEVI uint4 lds128(uint32_t addr) {
  uint4 v; asm volatile("ld.shared.v4.b32 {%0, %1, %2, %3}, [%4];" : "=r"(v.x), "=r"(v.y), "=r"(v.z), "=r"(v.w) : "r"(addr) : "memory"); return v;
}
DEVI float ex2(float x) { float y; asm("ex2.approx.ftz.f32 %0, %1;" : "=f"(y) : "f"(x)); return y; }

DEVI void wgmma_ss_n64(float (&d)[32], uint64_t da, uint64_t db) {
  asm volatile("wgmma.mma_async.sync.aligned.m64n64k16.f32.bf16.bf16 {%0, %1, %2, %3, %4, %5, %6, %7, %8, %9, %10, %11, %12, %13, %14, %15, %16, %17, %18, %19, %20, %21, %22, %23, %24, %25, %26, %27, %28, %29, %30, %31}, %32, %33, 1, 1, 1, 0, 1;"
    : "+f"(d[0]), "+f"(d[1]), "+f"(d[2]), "+f"(d[3]), "+f"(d[4]), "+f"(d[5]), "+f"(d[6]), "+f"(d[7]), "+f"(d[8]), "+f"(d[9]), "+f"(d[10]), "+f"(d[11]), "+f"(d[12]), "+f"(d[13]), "+f"(d[14]), "+f"(d[15]), "+f"(d[16]), "+f"(d[17]), "+f"(d[18]), "+f"(d[19]), "+f"(d[20]), "+f"(d[21]), "+f"(d[22]), "+f"(d[23]), "+f"(d[24]), "+f"(d[25]), "+f"(d[26]), "+f"(d[27]), "+f"(d[28]), "+f"(d[29]), "+f"(d[30]), "+f"(d[31])
    : "l"(da), "l"(db));
}
DEVI void wgmma_ss_n128(float (&d)[64], uint64_t da, uint64_t db) {
  asm volatile("wgmma.mma_async.sync.aligned.m64n128k16.f32.bf16.bf16 {%0, %1, %2, %3, %4, %5, %6, %7, %8, %9, %10, %11, %12, %13, %14, %15, %16, %17, %18, %19, %20, %21, %22, %23, %24, %25, %26, %27, %28, %29, %30, %31, %32, %33, %34, %35, %36, %37, %38, %39, %40, %41, %42, %43, %44, %45, %46, %47, %48, %49, %50, %51, %52, %53, %54, %55, %56, %57, %58, %59, %60, %61, %62, %63}, %64, %65, 1, 1, 1, 0, 1;"
    : "+f"(d[0]), "+f"(d[1]), "+f"(d[2]), "+f"(d[3]), "+f"(d[4]), "+f"(d[5]), "+f"(d[6]), "+f"(d[7]), "+f"(d[8]), "+f"(d[9]), "+f"(d[10]), "+f"(d[11]), "+f"(d[12]), "+f"(d[13]), "+f"(d[14]), "+f"(d[15]), "+f"(d[16]), "+f"(d[17]), "+f"(d[18]), "+f"(d[19]), "+f"(d[20]), "+f"(d[21]), "+f"(d[22]), "+f"(d[23]), "+f"(d[24]), "+f"(d[25]), "+f"(d[26]), "+f"(d[27]), "+f"(d[28]), "+f"(d[29]), "+f"(d[30]), "+f"(d[31]), "+f"(d[32]), "+f"(d[33]), "+f"(d[34]), "+f"(d[35]), "+f"(d[36]), "+f"(d[37]), "+f"(d[38]), "+f"(d[39]), "+f"(d[40]), "+f"(d[41]), "+f"(d[42]), "+f"(d[43]), "+f"(d[44]), "+f"(d[45]), "+f"(d[46]), "+f"(d[47]), "+f"(d[48]), "+f"(d[49]), "+f"(d[50]), "+f"(d[51]), "+f"(d[52]), "+f"(d[53]), "+f"(d[54]), "+f"(d[55]), "+f"(d[56]), "+f"(d[57]), "+f"(d[58]), "+f"(d[59]), "+f"(d[60]), "+f"(d[61]), "+f"(d[62]), "+f"(d[63])
    : "l"(da), "l"(db));
}
DEVI void wgmma_qk64(float (&d)[32], uint32_t a0, uint32_t a1, uint32_t a2, uint32_t a3, uint64_t db) {
  asm volatile("wgmma.mma_async.sync.aligned.m64n64k16.f32.bf16.bf16 {%0, %1, %2, %3, %4, %5, %6, %7, %8, %9, %10, %11, %12, %13, %14, %15, %16, %17, %18, %19, %20, %21, %22, %23, %24, %25, %26, %27, %28, %29, %30, %31}, {%32, %33, %34, %35}, %36, 0, 1, 1, 0;"
    : "=f"(d[0]), "=f"(d[1]), "=f"(d[2]), "=f"(d[3]), "=f"(d[4]), "=f"(d[5]), "=f"(d[6]), "=f"(d[7]), "=f"(d[8]), "=f"(d[9]), "=f"(d[10]), "=f"(d[11]), "=f"(d[12]), "=f"(d[13]), "=f"(d[14]), "=f"(d[15]), "=f"(d[16]), "=f"(d[17]), "=f"(d[18]), "=f"(d[19]), "=f"(d[20]), "=f"(d[21]), "=f"(d[22]), "=f"(d[23]), "=f"(d[24]), "=f"(d[25]), "=f"(d[26]), "=f"(d[27]), "=f"(d[28]), "=f"(d[29]), "=f"(d[30]), "=f"(d[31])
    : "r"(a0), "r"(a1), "r"(a2), "r"(a3), "l"(db));
}
DEVI void wgmma_pv(float (&d)[8], uint32_t a0, uint32_t a1, uint32_t a2, uint32_t a3, uint64_t db) {
  asm volatile("wgmma.mma_async.sync.aligned.m64n16k16.f32.bf16.bf16 {%0, %1, %2, %3, %4, %5, %6, %7}, {%8, %9, %10, %11}, %12, 1, 1, 1, 1;"
    : "+f"(d[0]), "+f"(d[1]), "+f"(d[2]), "+f"(d[3]), "+f"(d[4]), "+f"(d[5]), "+f"(d[6]), "+f"(d[7])
    : "r"(a0), "r"(a1), "r"(a2), "r"(a3), "l"(db));
}
DEVI void wgmma_pv0(float (&d)[8], uint32_t a0, uint32_t a1, uint32_t a2, uint32_t a3, uint64_t db) {
  asm volatile("wgmma.mma_async.sync.aligned.m64n16k16.f32.bf16.bf16 {%0, %1, %2, %3, %4, %5, %6, %7}, {%8, %9, %10, %11}, %12, 0, 1, 1, 1;"
    : "=f"(d[0]), "=f"(d[1]), "=f"(d[2]), "=f"(d[3]), "=f"(d[4]), "=f"(d[5]), "=f"(d[6]), "=f"(d[7])
    : "r"(a0), "r"(a1), "r"(a2), "r"(a3), "l"(db));
}


template <int N> struct Acc { float a[64]; float b[(N - 128) / 2]; DEVI float& operator[](int i) { return i < 64 ? a[i] : b[i - 64]; } };
template <> struct Acc<128> { float a[64]; DEVI float& operator[](int i) { return a[i]; } };
template <int N> DEVI void wgmma_ss(Acc<N>& d, uint64_t da, uint64_t db) {
  wgmma_ss_n128(d.a, da, db);
  if constexpr (N == 192) wgmma_ss_n64(d.b, da, db + 256);
  if constexpr (N == 256) wgmma_ss_n128(d.b, da, db + 256);
}

DEVI int oh_chunk(inDEVI int oh_chunk(int j, int i, int& need) {
  if (i >= 3 && i < 5) { const int e = (j & 1) * 2 + i - 3; need = 16 + 2 * e; return 24 + e; }
  if (i >= 5) i -= 2;
  int o, r;
  if (i >= 12) { o = (j + 5) & 7; r = i - 11; }
  else { const int g = i / 3; o = (j + 2 * g) & 7; r = i - 3 * g; }
  need = o;
  return 3 * o + r;
}

 int k = i - 5;
    r = k < 3 ? 0 : k < 5 ? 1 : 2; g = k < 3 ? 1 + k : 1 + ((k - 3) & 1);
  }
  return 3 * ((j + 2 * g) & 7) + r;
}

DEVI int a_slot(int e, int) { return 1 + (e & 3); }

struct Ctx {
  uint32_t sbase, bars, peer, t0, a16, b16;
  int wg, lane;
  int ai, bi; uint32_t aph, bph;
  int brem, ae;
  int pa, pb;
};

DEVI void release_prev(Ctx& c) {
  if (c.pb >= 0) {
    if (c.lane == 0) mbar_arrive(c.bars + 8 * (BAR_EMPTYB + c.pb));
    if (c.lane == 1) mbar_arrive_cluster(c.bars + 8 * (BAR_EMPTYB + c.pb), c.peer);
  }
  if (c.pa >= 0 && c.lane == 2) mbar_arrive(c.bars + 8 * (BAR_EMPTYA + c.pa));
}

DEVI void gemm_wait(Ctx& c) {
  asm volatile("{ .reg .pred p, q; .reg .u32 c;\n"
               "mbarrier.try_wait.parity.shared::cta.b64 p, [%0], %1;\n"
               "mbarrier.try_wait.parity.shared::cta.b64 q, [%2], %3;\n"
               "and.pred p, p, q;\n"
               "@p bra DONE_%=;\n"
               "WAIT_%=:\n"
               "mbarrier.try_wait.parity.shared::cta.b64 p, [%0], %1, %6;\n"
               "mbarrier.try_wait.parity.shared::cta.b64 q, [%2], %3, %6;\n"
               "and.pred p, p, q;\n"
               "@p bra DONE_%=;\n"
               "mov.u32 c, %%clock; sub.u32 c, c, %4; setp.lt.u32 p, c, %5;\n"
               "@p bra WAIT_%=;\n"
               "DONE_%=: }" ::"r"(c.bars + 8 * (BAR_FULLA + c.ai)), "r"((c.aph >> c.ai) & 1), "r"(c.bars + 8 * (BAR_FULLB + c.bi)), "r"(c.bph), "r"(c.t0),
               "n"(TIMEOUT), "r"(WAIT_HINT_NS) : "memory");
}
template <int N, bool SHALLOW>
DEVI void gemm_group(Acc<N>& acc, Ctx& c, int g, int& npa, int& npb) {
  const uint32_t a16 = c.a16 + c.ai * (SLOT >> 4);
  const uint32_t b16 = c.b16 + c.bi * (SLOT >> 4);
  bool adv;
  if constexpr (N >= 192) {
    const uint32_t a2 = a16 + (g & 1) * 4;
    wgmma_ss<N>(acc, desc_sw128<16>(a2), desc_sw128<2048>(b16));
    if (SHALLOW) { wgmma_commit(); wgmma_wait<SHW>(); }
    wgmma_ss<N>(acc, desc_sw128<16>(a2 + 2), desc_sw128<2048>(b16 + 512));
    adv = g & 1;
  } else {
#pragma unroll
    for (int s = 0; s < 4; s++) {
      wgmma_ss<N>(acc, desc_sw128<16>(a16 + s * 2), desc_sw128<4096>(b16 + (s >> 1) * 512 + (s & 1) * 128));
      if (SHALLOW && s < 3 && (SHG == 1 || s == 1)) { wgmma_commit(); wgmma_wait<SHW>(); }
    }
    adv = true;
  }
  wgmma_commit();
  npb = c.brem > 0 ? c.bi : -1;
  c.brem--;
  if (++c.bi == NB) { c.bi = 0; c.bph ^= 1; }
  npa = -1;
  if (adv) { npa = c.ai; c.aph ^= 1u << c.ai; c.ae++; c.ai = 1 + (c.ae & 3); }
}

template <int N, bool SHALLOW = false>
DEVI void bare_groups(Acc<N>& acc, Ctx& c, int g0, int g1) {
  for (int g = g0; g < g1; g++) {
    int npa, npb;
#ifdef TRACE3
    { const uint32_t sbase = c.sbase, t0 = c.t0;
      if (c.brem > 30 && threadIdx.x == 0 && g < 6) { mbar_wait(c.bars + 8 * (BAR_FULLA + c.ai), (c.aph >> c.ai) & 1, c.t0); TR(40 + g); } }
#endif
    gemm_wait(c);
#ifdef TRACE3
    { const uint32_t sbase = c.sbase, t0 = c.t0; if (c.brem > 30 && threadIdx.x == 0 && g < 8) TR(24 + g); }
#endif
    wgmma_fence();
    gemm_group<N, SHALLOW>(acc, c, g, npa, npb);
    wgmma_wait<SHALLOW ? SHW : 1>();
    release_prev(c);
    c.pa = npa; c.pb = npb;
  }
}
DEVI void drain(Ctx& c) {
  wgmma_wait<0>();
  release_prev(c);
  c.pa = c.pb = -1;
}

constexpr float SC = 0.25f * 1.4426950408889634f;

#define ONCE _Pragma("unroll 1") for (unsigned once_ = 0; once_ < gridDim.y; once_++)

struct Gate { float g0, g1; };

DEVI void kill32(float (&S)[32]) {
#pragma unroll
  for (int i = 0; i < 32; i++) S[i] = __int_as_float(0xff800000);
}
DEVI void row_max(const float (&S)[32], float& x0, float& x1) {
  float y0 = S[1], y1 = S[3];
  x0 = fmaxf(x0, S[0]); x1 = fmaxf(x1, S[2]);
#pragma unroll
  for (int n = 1; n < 8; n++) {
    x0 = fmaxf(x0, S[4 * n]); y0 = fmaxf(y0, S[4 * n + 1]); x1 = fmaxf(x1, S[4 * n + 2]); y1 = fmaxf(y1, S[4 * n + 3]);
  }
  x0 = fmaxf(x0, y0); x1 = fmaxf(x1, y1);
}
DEVI void quad_max(float& x0, float& x1) {
  x0 = fmaxf(x0, __shfl_xor_sync(0xffffffffu, x0, 1)); x1 = fmaxf(x1, __shfl_xor_sync(0xffffffffu, x1, 1));
  x0 = fmaxf(x0, __shfl_xor_sync(0xffffffffu, x0, 2)); x1 = fmaxf(x1, __shfl_xor_sync(0xffffffffu, x1, 2));
}
DEVI void exp32(const float (&S)[32], float (&E)[32], float n0, float n1, float (&l)[4]) {
#pragma unroll
  for (int i = 0; i < 32; i++) { E[i] = ex2(fmaf(S[i], SC, (i & 2) ? n1 : n0)); l[i & 3] += E[i]; }
}
DEVI void pack32(const float (&E)[32], uint32_t (&P)[16]) {
#pragma unroll
  for (int i = 0; i < 16; i++) P[i] = pack_bf16(E[2 * i], E[2 * i + 1]);
}
template <bool FIRST> DEVI void pv4(float (&O)[8], const uint32_t (&P)[16], uint32_t v16) {
  if (FIRST) wgmma_pv0(O, P[0], P[1], P[2], P[3], desc_sw64(v16)); else wgmma_pv(O, P[0], P[1], P[2], P[3], desc_sw64(v16));
#pragma unroll
  for (int k = 1; k < 4; k++) wgmma_pv(O, P[4 * k], P[4 * k + 1], P[4 * k + 2], P[4 * k + 3], desc_sw64(v16 + k * 64));
}
DEVI bool wg_any(int wg, bool v) {
  uint32_t r;
  if (wg == 0) asm volatile("{ .reg .pred p, q; setp.ne.u32 p, %1, 0; bar.red.or.pred q, 4, 128, p; selp.u32 %0, 1, 0, q; }" : "=r"(r) : "r"((uint32_t)v) : "memory");
  else asm volatile("{ .reg .pred p, q; setp.ne.u32 p, %1, 0; bar.red.or.pred q, 5, 128, p; selp.u32 %0, 1, 0, q; }" : "=r"(r) : "r"((uint32_t)v) : "memory");
  return r != 0;
}
DEVI void get_gate(Gate& g, uint32_t sbase, int row16, int lane, uint32_t t0) {
  mbar_wait(sbase + OFF_BAR + 8 * BAR_GIN, 0, t0);
  const uint32_t a = sbase + OFF_GIN + (row16 * 16 + (lane >> 2)) * 4;
  asm volatile("ld.shared.f32 %0, [%1];" : "=f"(g.g0) : "r"(a) : "memory");
  asm volatile("ld.shared.f32 %0, [%1];" : "=f"(g.g1) : "r"(a + 32) : "memory");
}

constexpr int HELP_HEAD = 2;
DEVI void attention_help(uint32_t sbase, int wg, int wi, int lane, int rb, uint32_t t0) {
  const uint32_t bars = sbase + OFF_BAR;
  const uint32_t kb = (((sbase & 0x3FFFF) + OFF_KV + wg * 4096) >> 4) + (HELP_HEAD & 1) * (KVBUF >> 4);
  const int tlo = max(4 - 2 * rb - wg, 1);
  const uint4 q = lds128(sbase + OFF_A + wg * 8192 + HELP_HEAD * 2048 + (wi * 32 + lane) * 16);
  uint32_t nm;
  asm volatile("ld.shared.u32 %0, [%1];" : "=r"(nm) : "r"(sbase + OFF_NM + ((wg * 4 + wi) * 32 + (lane & 28) + HELP_HEAD) * 4) : "memory");
  const float n0 = __uint_as_float(nm << 16), n1 = __uint_as_float(nm & 0xffff0000u);
  float O[8], l[4] = {0.f, 0.f, 0.f, 0.f};
  uint32_t P[16];
#pragma unroll
  for (int i = 0; i < 8; i++) O[i] = 0.f;
#pragma unroll
  for (int i = 0; i < 16; i++) P[i] = 0u;
  mbar_wait(bars + 8 * (BAR_KVFULL + HELP_HEAD), 0, t0);
  int t = HT;
#pragma unroll 1
  for (; t >= tlo; t--) {
    float S[32];
    wgmma_fence();
    wgmma_qk64(S, q.x, q.y, q.z, q.w, desc_sw64(kb + t * 256));
    wgmma_commit();
    pv4<false>(O, P, kb + (t + 1) * 256 + 2);
    wgmma_commit();
    wgmma_wait<1>();
    ONCE { exp32(S, S, n0, n1, l); }
    wgmma_wait<0>();
    pack32(S, P);
  }
  wgmma_fence();
  pv4<false>(O, P, kb + max(t + 1, tlo) * 256 + 2);
  wgmma_commit();
  wgmma_wait<0>();
  float4* d = g_help + blockIdx.x * 768 + wg * 128 + wi * 32 + lane;
  __stcg(d, make_float4(O[0], O[1], O[2], O[3]));
  __stcg(d + 256, make_float4(O[4], O[5], O[6], O[7]));
  __stcg(d + 512, make_float4(l[0], l[1], l[2], l[3]));
  __syncwarp();
  if (lane == 0) mbar_arrive(bars + 8 * (BAR_HELP + wg));
}

DEVI void attention(uint32_t sbase, int aw, int wi, int lane, int rb, uint32_t t0) {
  const uint32_t bars = sbase + OFF_BAR;
  const uint32_t kvb = ((sbase & 0x3FFFF) + OFF_KV + aw * 4096) >> 4;
  const int cmin = 4 - 2 * rb - aw;
  const int rowc = wi * 16 + (lane >> 2) - (lane & 3) * 2;
  const uint32_t qst = sbase + OFF_A + aw * 8192;
  const float NINF = __int_as_float(0xff800000);
  const int tlo = max(cmin, 1);
#pragma unroll 1
  for (int h = 0; h < 4; h++) {
    const uint32_t kb = kvb + (h & 1) * (KVBUF >> 4);
    const uint4 q = lds128(qst + h * 2048 + (wi * 32 + lane) * 16);
    float R[8], l0, l1;
    uint32_t nm;
    asm volatile("ld.shared.u32 %0, [%1];" : "=r"(nm) : "r"(sbase + OFF_NM + ((aw * 4 + wi) * 32 + (lane & 28) + h) * 4) : "memory");
    float n0 = __uint_as_float(nm << 16), n1 = __uint_as_float(nm & 0xffff0000u);
    mbar_wait(bars + 8 * (BAR_KVFULL + h), 0, t0);
#ifdef SKEW
    if (h == 0 && aw == 1) { const uint32_t ts = clk32(); while (clk32() - ts < SKEW) {} }
#endif
#pragma unroll 1
    for (int attempt = 0; attempt < 2; attempt++) {
      float O[8], l[4] = {0.f, 0.f, 0.f, 0.f};
      uint32_t P[16];
      {
        float S[32], F[32];
        wgmma_fence();
        wgmma_qk64(S, q.x, q.y, q.z, q.w, desc_sw64(kb + 4 * 256));
        wgmma_qk64(F, q.x, q.y, q.z, q.w, desc_sw64(kb));
        wgmma_commit();
        wgmma_wait<0>();
        for (int r = 0; r < (cmin > 0 ? 1 : 0); r++) kill32(F);
        float M[32];
#pragma unroll
        for (int i = 0; i < 32; i++) M[i] = ((i >> 2) * 8 + (i & 1) > rowc + (i & 2) * 4) ? F[i] : S[i];
        for (int r = 0; r < attempt; r++) {
          row_max(M, n0, n1);
          quad_max(n0, n1);
          n0 *= -SC; n1 *= -SC;
        }
        exp32(M, M, n0, n1, l);
        pack32(M, P);
        uint32_t PF[16];
#pragma unroll
        for (int i = 0; i < 16; i++) {
          const int col = (i >> 1) * 8, r = rowc + (i & 1) * 8;
          const uint32_t m = (col > r ? 0xFFFFu : 0u) | (col + 1 > r ? 0xFFFF0000u : 0u);
          PF[i] = P[i] & m; P[i] &= ~m;
        }
        wgmma_fence();
        pv4<true>(O, PF, kb + 2);
        wgmma_commit();
#ifndef NOPFW
        wgmma_wait<0>();
#endif
      }
      int t = 3;
      const bool helped = h == HELP_HEAD && attempt == 0;
      const int tend = helped ? max(tlo, HT + 1) : tlo;
#pragma unroll 1
      for (; t >= tend; t--) {
        float S[32];
        wgmma_fence();
        wgmma_qk64(S, q.x, q.y, q.z, q.w, desc_sw64(kb + t * 256));
        wgmma_commit();
        pv4<false>(O, P, kb + (t + 1) * 256 + 2);
        wgmma_commit();
        wgmma_wait<1>();
        ONCE { exp32(S, S, n0, n1, l); }
        wgmma_wait<0>();
        pack32(S, P);
      }
      wgmma_fence();
      pv4<false>(O, P, kb + (t + 1) * 256 + 2);
      wgmma_commit();
      float4 ha = make_float4(0.f, 0.f, 0.f, 0.f), hb = ha;
      if (helped) {
        mbar_wait(bars + 8 * (BAR_HELP + aw), 0, t0);
        const float4* d = g_help + blockIdx.x * 768 + aw * 128 + wi * 32 + lane;
        ha = __ldcg(d); hb = __ldcg(d + 256);
        const float4 hl = __ldcg(d + 512);
        l[0] += hl.x; l[1] += hl.y; l[2] += hl.z; l[3] += hl.w;
      }
      l0 = l[0] + l[1]; l1 = l[2] + l[3];
      l0 += __shfl_xor_sync(0xffffffffu, l0, 1); l1 += __shfl_xor_sync(0xffffffffu, l1, 1);
      l0 += __shfl_xor_sync(0xffffffffu, l0, 2); l1 += __shfl_xor_sync(0xffffffffu, l1, 2);
      const bool redo = wg_any(aw, attempt == 0 && !(l0 > 1e-6f && l0 < 1e18f && l1 > 1e-6f && l1 < 1e18f));
      wgmma_wait<0>();
      R[0] = O[0] + ha.x; R[1] = O[1] + ha.y; R[2] = O[2] + ha.z; R[3] = O[3] + ha.w;
      R[4] = O[4] + hb.x; R[5] = O[5] + hb.y; R[6] = O[6] + hb.z; R[7] = O[7] + hb.w;
      if (!redo) break;
      n0 = NINF; n1 = NINF;
#pragma unroll 1
      for (int u = 3; u >= tlo; u--) {
        float S[32];
        wgmma_fence();
        wgmma_qk64(S, q.x, q.y, q.z, q.w, desc_sw64(kb + u * 256));
        wgmma_commit();
        wgmma_wait<0>();
        row_max(S, n0, n1);
      }
    }
    if (lane == 0) mbar_arrive(bars + 8 * (BAR_KVEMPTY + (h & 1)));
    Gate g;
    get_gate(g, sbase, aw * 4 + wi, lane, t0);
    const float c0 = __fdividef(g.g0, l0), c1 = __fdividef(g.g1, l1);
    const int mi = lane >> 3;
    const int srow = wi * 16 + (lane & 7) + 8 * (mi & 1);
    stsm_x4(qst + h * 2048 + srow * 32 + (mi >> 1) * 16, pack_bf16(R[0] * c0, R[1] * c0), pack_bf16(R[2] * c1, R[3] * c1),
            pack_bf16(R[4] * c0, R[5] * c0), pack_bf16(R[6] * c1, R[7] * c1));
    fence_async_smem();
    __syncwarp();
    if (lane == 0) mbar_arrive(bars + 8 * (BAR_OST + aw));
  }
}

template <int CH, int N>
DEVI void store_h_chunk(Acc<N>& acc, uint32_t base  , int lane, float s0, float s1) {
  const int mi = lane >> 3;
#pragma unroll
  for (int tp = 0; tp < 4; tp++) {
    const int t = CH * 8 + tp * 2;
    const uint32_t r0 = pack_bf16(fmaxf(acc[4 * t + 0], 0.f) * s0, fmaxf(acc[4 * t + 1], 0.f) * s0);
    const uint32_t r1 = pack_bf16(fmaxf(acc[4 * t + 2], 0.f) * s1, fmaxf(acc[4 * t + 3], 0.f) * s1);
    const uint32_t r2 = pack_bf16(fmaxf(acc[4 * t + 4], 0.f) * s0, fmaxf(acc[4 * t + 5], 0.f) * s0);
    const uint32_t r3 = pack_bf16(fmaxf(acc[4 * t + 6], 0.f) * s1, fmaxf(acc[4 * t + 7], 0.f) * s1);
    stsm_x4(base + (((tp * 2 + (mi >> 1)) ^ (lane & 7)) << 4), r0, r1, r2, r3);
  }
}

template <int N>
DEVI void phase_q(Ctx& c, int warp) {
  Acc<N> acc;
#pragma unroll
  for (int i = 0; i < N / 2; i++) acc[i] = 0.f;
  bare_groups<N>(acc, c, 0, 16);
  drain(c);
  const int lane = c.lane, mi = lane >> 3;
  const int row = warp * 16 + (lane & 7) + 8 * (mi & 1);
  const int sw = (row >> 1) & 3;
#pragma unroll
  for (int hh = 0; hh < 4; hh++) {
    const uint32_t base = c.sbase + OFF_KV + hh * 8192 + row * 64;
#pragma unroll
    for (int kv = 0; kv < 2; kv++) {
      const int t = 8 + kv * 8 + 2 * hh;
      stsm_x4(base + (((kv * 2 + (mi >> 1)) ^ sw) << 4),
              pack_bf16(acc[4 * t + 0], acc[4 * t + 1]), pack_bf16(acc[4 * t + 2], acc[4 * t + 3]),
              pack_bf16(acc[4 * t + 4], acc[4 * t + 5]), pack_bf16(acc[4 * t + 6], acc[4 * t + 7]));
    }
  }
  fence_async_smem();
  __syncwarp();
  if (lane == 0) mbar_arrive(c.bars + 8 * BAR_STG);
#pragma unroll
  for (int hh = 0; hh < 4; hh++)
    sts128(c.sbase + OFF_A + c.wg * 8192 + hh * 2048 + ((warp & 3) * 32 + lane) * 16,
           pack_bf16(acc[8 * hh], acc[8 * hh + 1]), pack_bf16(acc[8 * hh + 2], acc[8 * hh + 3]),
           pack_bf16(acc[8 * hh + 4], acc[8 * hh + 5]), pack_bf16(acc[8 * hh + 6], acc[8 * hh + 7]));
#pragma unroll
  for (int hh = 0; hh < 4; hh++) {
    const int q = 8 * hh, k = 32 + 8 * hh;
    float d0 = acc[q] * acc[k] + acc[q + 1] * acc[k + 1] + acc[q + 4] * acc[k + 4] + acc[q + 5] * acc[k + 5];
    float d1 = acc[q + 2] * acc[k + 2] + acc[q + 3] * acc[k + 3] + acc[q + 6] * acc[k + 6] + acc[q + 7] * acc[k + 7];
    d0 += __shfl_xor_sync(0xffffffffu, d0, 1); d1 += __shfl_xor_sync(0xffffffffu, d1, 1);
    d0 += __shfl_xor_sync(0xffffffffu, d0, 2); d1 += __shfl_xor_sync(0xffffffffu, d1, 2);
    if ((lane & 3) == hh)
      asm volatile("st.shared.u32 [%0], %1;" ::"r"(c.sbase + OFF_NM + (warp * 32 + lane) * 4), "r"(pack_bf16(-d0 * SC, -d1 * SC)) : "memory");
  }
  __syncwarp();
  if (lane == 0) mbar_arrive(c.bars + 8 * (BAR_QRDY + c.wg));
  if constexpr (N == 256) {
    Gate g;
    get_gate(g, c.sbase, warp, lane, c.t0);
    store_h_chunk<3>(acc, c.sbase + OFF_KV + 32768 + row * 128, lane, 1.f - g.g0, 1.f - g.g1);
    fence_async_smem();
    __syncwarp();
    if (lane == 0) mbar_arrive(c.bars + 8 * BAR_STE);
  }
}

DEVI void first_loads(const Params& P, uint32_t sbase, int e, int j, int rb) {
  const uint32_t bars = sbase + OFF_BAR, fb = bars + 8 * (BAR_FULLB + e), fa = bars + 8 * (BAR_FULLA + 1 + e);
  mbar_expect_tx(fa, 16384);
  mbar_expect_tx(fb, (j & 1) ? 12288 : 16384);
  if (e == 0) tma_load_2d(sbase + OFF_A + SLOT, &P.tmX, 0, rb * 128, fa);
#pragma unroll
  for (int r = 0; r < 2; r++) {
    tma_load_3d(sbase + OFF_B + e * SLOT + r * 8192, &P.tmWqkv, 64 * j, e * 32 + r * 16, 0, fb);
    if (!(j & 1)) tma_load_3d(sbase + OFF_B + e * SLOT + r * 8192 + 6144, &P.tmW1a, 0, e * 32 + r * 16, 24 + (j >> 1), fb);
  }
  if (e == 1) tma_load_2d(sbase + OFF_A + 2 * SLOT, &P.tmX, 64, rb * 128, fa);
}

__global__ void __cluster_dims__(2, 1, 1) __launch_bounds__(640, 1) fused_kernel(const __grid_constant__ Params P) {
  extern __shared__ __align__(1024) uint8_t smem_raw[];
  const uint32_t sbase = smem_u32(smem_raw);
  const uint32_t bars = sbase + OFF_BAR;
  const int tid = threadIdx.x, warp = tid >> 5, lane = tid & 31;
  const uint32_t rank = blockIdx.x & 1, peer = rank ^ 1;
  const int j = (blockIdx.x >> 1) & 7, rb = ((blockIdx.x >> 4) << 1) | rank;
  const uint32_t t0 = clk32();
#ifdef TRACE
  uint32_t gt0; asm volatile("mov.u32 %0, %%globaltimer_lo;" : "=r"(gt0));
#endif

  const int typeB = j & 1;
  if (tid == 544) {
    for (int s = 0; s < NA2; s++) mbar_init(bars + 8 * (BAR_FULLA + s), 1);
    for (int s = 0; s < NB; s++) mbar_init(bars + 8 * (BAR_FULLB + s), 1);
    fence_async_smem();
  } else if (tid < 8) {
    asm volatile("prefetch.tensormap [%0];" ::"l"(&P.tmX + tid) : "memory");
  } else if (tid == 512) {
    for (int s = 0; s < NA2; s++) mbar_init(bars + 8 * (BAR_EMPTYA + s), 9);
    for (int s = 0; s < NB; s++) mbar_init(bars + 8 * (BAR_EMPTYB + s), 16);
  } else if (tid == 576) {
    for (int s = 0; s < 2; s++) { mbar_init(bars + 8 * (BAR_KVFULL + s), 1); mbar_init(bars + 8 * (BAR_KVFULL + 2 + s), 1); mbar_init(bars + 8 * (BAR_KVEMPTY + s), 8); mbar_init(bars + 8 * (BAR_OST + s), 4); mbar_init(bars + 8 * (BAR_QRDY + s), 4); mbar_init(bars + 8 * (BAR_HELP + s), 4); }
    mbar_init(bars + 8 * BAR_STG, 8); mbar_init(bars + 8 * BAR_STE, 8); mbar_init(bars + 8 * BAR_KVOK, 1);
    mbar_init(bars + 8 * BAR_PIN, 1); mbar_init(bars + 8 * BAR_PFREE, 8); mbar_init(bars + 8 * BAR_GIN, 1);
  }
  if (tid >= 512 && lane == 0) asm volatile("fence.mbarrier_init.release.cluster;" ::: "memory");
#ifdef TRACE
  if (tid < 64) asm volatile("st.shared.u32 [%0], %1;" ::"r"(sbase + OFF_BAR + 640 + 4 * tid), "r"(0));
#endif
  const unsigned ep1 = ld_relaxed(&g_epoch) + 1;
  __syncwarp();
  cluster_arrive();
  if (tid == 544) { first_loads(P, sbase, 0, j, rb); first_loads(P, sbase, 1, j, rb); }
#if PF0 == 1
  if (tid == 544) { l2_prefetch(P.x + (size_t)(rb * 128 + j * 16) * DM, 16384); l2_prefetch((const uint8_t*)P.wqkv + blockIdx.x * 12288, 12288); }
#elif PF0 == 2
  if (tid == 320) { l2_prefetch(P.x + (size_t)(rb * 128 + j * 16) * DM, 16384); l2_prefetch((const uint8_t*)P.wqkv + blockIdx.x * 12288, 12288); }
#endif
  __syncwarp();

  const int on = 12 + 4 * typeB;

  if (warp < 8) {
    asm volatile("setmaxnreg.inc.sync.aligned.u32 160;");
    cluster_wait();
    const int wg = __shfl_sync(0xffffffffu, warp >> 2, 0);
    Ctx c{sbase, bars, peer, t0, ((sbase & 0x3FFFF) + OFF_A + wg * 8192) >> 4, ((sbase & 0x3FFFF) + OFF_B) >> 4, wg, lane, 1, 0, 0u, 0u, 32 + on + 4 - NB, 0, -1, -1};
    if (tid == 0) TR(0);
    if (typeB) phase_q<192>(c, warp);
    else phase_q<256>(c, warp);
    asm volatile("setmaxnreg.dec.sync.aligned.u32 128;");
    if (tid == 0) TR(2);
    {
      Acc<192> acc;
#pragma unroll
      for (int i = 0; i < 96; i++) acc[i] = 0.f;
      bare_groups<192>(acc, c, 0, typeB ? SHSB : SHS);
      bare_groups<192, SH>(acc, c, typeB ? SHSB : SHS, 16);
      Gate at;
      get_gate(at, sbase, warp, lane, t0);
      drain(c);
      if (tid == 0) TR(1);
      const uint32_t rowoff = (warp * 16 + (lane & 7) + 8 * ((lane >> 3) & 1)) * 128;
      const float s0 = 1.f - at.g0, s1 = 1.f - at.g1;
      constexpr int e0 = 1, e1 = 2, e2 = 3;
      mbar_wait(bars + 8 * (BAR_FULLA + e0), 0, t0);
      store_h_chunk<0>(acc, sbase + OFF_A + e0 * SLOT + rowoff, lane, s0, s1);
      mbar_wait(bars + 8 * (BAR_FULLA + e1), 0, t0);
      store_h_chunk<1>(acc, sbase + OFF_A + e1 * SLOT + rowoff, lane, s0, s1);
      mbar_wait(bars + 8 * (BAR_FULLA + e2), 0, t0);
      store_h_chunk<2>(acc, sbase + OFF_A + e2 * SLOT + rowoff, lane, s0, s1);
    }
    fence_async_smem();
    wg_bar(wg);
    if (lane == 0) mbar_arrive(bars + 8 * BAR_STG);
    if (tid == 0) TR(4);
    attention_help(sbase, wg, warp & 3, lane, rb, t0);
    if (tid == 0) TR(9);
    float own[32];
    {
      Acc<128> acc;
#pragma unroll
      for (int i = 0; i < 64; i++) acc[i] = 0.f;
#if TB == 1
      if (typeB) bare_groups<128, false>(acc, c, 0, on); else bare_groups<128, true>(acc, c, 0, on);
#elif TB == 2
      bare_groups<128, true>(acc, c, 0, typeB ? 8 : on);
      bare_groups<128, false>(acc, c, typeB ? 8 : on, on);
#else
      bare_groups<128, SHO>(acc, c, 0, on);
#endif
      drain(c);
      if (tid == 0) TR(5);
      if (lane == 0) mbar_arrive(bars + 8 * BAR_PFREE);
      named_bar<3>(256);
      const uint32_t pst = sbase + OFF_B + ((30 + on) % NB) * SLOT + wg * 8192 + (tid & 127) * 16;
#pragma unroll
      for (int i = 0; i < 4; i++) {
        uint32_t r[4];
#pragma unroll
        for (int k = 0; k < 4; k++) {
          const int idx = 8 * i + 2 * k;
          const float lo = typeB ? acc[idx] : acc[32 + idx], hi = typeB ? acc[idx + 1] : acc[32 + idx + 1];
          r[k] = pack_bf16(lo, hi);
        }
        sts128(pst + i * 2048, r[0], r[1], r[2], r[3]);
      }
#pragma unroll
      for (int i = 0; i < 32; i++) own[i] = typeB ? acc[32 + i] : acc[i];
      fence_async_smem();
      __syncwarp();
      if (lane == 0) mbar_arrive(bars + 8 * BAR_STG);
    }
#pragma unroll 1
    for (int g = 0; g < 8; g++) {
      const uint32_t a16 = c.a16 + c.ai * (SLOT >> 4);
      const uint32_t b16 = c.b16 + c.bi * (SLOT >> 4) + (g & 1) * 512;
      if (g == 6) {
        mbar_wait(bars + 8 * BAR_PIN, 0, t0);
        const uint32_t pin = sbase + OFF_B + ((31 + on) % NB) * SLOT + wg * 8192 + (tid & 127) * 16;
#pragma unroll
        for (int i = 0; i < 4; i++) {
          const uint4 v = lds128(pin + i * 2048);
          const uint32_t r[4] = {v.x, v.y, v.z, v.w};
#pragma unroll
          for (int k = 0; k < 4; k++) { own[8 * i + 2 * k] += __uint_as_float(r[k] << 16); own[8 * i + 2 * k + 1] += __uint_as_float(r[k] & 0xffff0000u); }
        }
        named_bar<3>(256);
        if (tid == 0) TR(7);
      }
      gemm_wait(c);
      wgmma_fence();
#pragma unroll
      for (int s = 0; s < 4; s++) wgmma_ss_n64(own, desc_sw128<16>(a16 + s * 2), desc_sw128<2048>(b16 + s * 128));
      wgmma_commit();
      wgmma_wait<0>();
      if (lane == 2) mbar_arrive(bars + 8 * (BAR_EMPTYA + c.ai));
      c.aph ^= 1u << c.ai;
      c.ae++; c.ai = a_slot(c.ae, 0);
      if (g & 1) { if (++c.bi == NB) { c.bi = 0; c.bph ^= 1; } }
    }
    if (tid == 0) TR(6);
    {
      const uint32_t ob = sbase + OFF_B + ((31 + on) % NB) * SLOT;
      const uint32_t wb = ob + warp * 2048;
      const uint32_t orow = wb + ((lane & 7) + 8 * ((lane >> 3) & 1)) * 128;
#pragma unroll
      for (int i = 0; i < 4; i++)
        stsm_x4(orow + (((i * 2 + (lane >> 4)) ^ (lane & 7)) << 4), pack_bf16(own[8 * i], own[8 * i + 1]), pack_bf16(own[8 * i + 2], own[8 * i + 3]),
                pack_bf16(own[8 * i + 4], own[8 * i + 5]), pack_bf16(own[8 * i + 6], own[8 * i + 7]));
      __syncwarp();
      uint4* o = (uint4*)(P.out + (size_t)(rb * 128 + warp * 16 + (lane >> 3)) * DM + j * 64) + (lane & 7);
#pragma unroll
      for (int i = 0; i < 4; i++) {
        const int r = i * 4 + (lane >> 3);
        o[i * 4 * (DM / 8)] = lds128(wb + r * 128 + (((lane & 7) ^ (r & 7)) << 4));
      }
    }
    if (tid == 0) TR(8);
#ifdef TRACE
    named_bar<3>(256);
    if (tid < 64) { uint32_t v; asm volatile("ld.shared.u32 %0, [%1];" : "=r"(v) : "r"(sbase + OFF_BAR + 640 + 4 * tid));
      if (tid == 16) v = gt0;
      if (tid == 17) asm volatile("mov.u32 %0, %%globaltimer_lo;" : "=r"(v));
      if (tid == 18) v = clk32() - t0;
      g_trace[blockIdx.x * 64 + tid] = v; }
#endif
  } else if (warp < 16) {
    asm volatile("setmaxnreg.dec.sync.aligned.u32 56;");
    cluster_wait();
    const int aw = __shfl_sync(0xffffffffu, (warp >> 2) & 1, 0);
    {
      const int rowg = rb * 128 + j * 16 + (warp - 8) * 2;
      const uint4* gw = (const uint4*)P.gate_w;
      const uint4* xr = (const uint4*)(P.x + (size_t)rowg * DM);
      mbar_wait(bars + 8 * (BAR_FULLB + 1), 0, t0);
      const uint4 w0 = __ldg(gw + lane), w1 = __ldg(gw + 32 + lane);
      const uint4 xa0 = __ldg(xr + lane), xa1 = __ldg(xr + 32 + lane), xb0 = __ldg(xr + 64 + lane), xb1 = __ldg(xr + 96 + lane);
#pragma unroll
      for (int i = 0; i < 4; i++) sts128(sbase + OFF_KV + 32768 + i * 4096 + (tid - 256) * 16, 0u, 0u, 0u, 0u);
      const uint32_t wa[8] = {w0.x, w0.y, w0.z, w0.w, w1.x, w1.y, w1.z, w1.w};
      const uint32_t xa[8] = {xa0.x, xa0.y, xa0.z, xa0.w, xa1.x, xa1.y, xa1.z, xa1.w};
      const uint32_t xb[8] = {xb0.x, xb0.y, xb0.z, xb0.w, xb1.x, xb1.y, xb1.z, xb1.w};
      float za = 0.f, zb = 0.f;
#pragma unroll
      for (int e = 0; e < 8; e++) {
        const float wl = __uint_as_float(wa[e] << 16), wh = __uint_as_float(wa[e] & 0xffff0000u);
        za = fmaf(__uint_as_float(xa[e] << 16), wl, za); za = fmaf(__uint_as_float(xa[e] & 0xffff0000u), wh, za);
        zb = fmaf(__uint_as_float(xb[e] << 16), wl, zb); zb = fmaf(__uint_as_float(xb[e] & 0xffff0000u), wh, zb);
      }
#pragma unroll
      for (int o = 16; o > 0; o >>= 1) { za += __shfl_xor_sync(0xffffffffu, za, o); zb += __shfl_xor_sync(0xffffffffu, zb, o); }
      if (lane < 2) asm volatile("st.shared.f32 [%0], %1;" ::"r"(sbase + OFF_GST + (warp - 8) * 8 + lane * 4), "f"(1.f / (1.f + __expf(-(lane ? zb : za)))) : "memory");
      fence_async_smem();
      named_bar<6>(256);
      if (tid == 256) {
        bulk_store(&g_gate[rb * 128 + j * 16], sbase + OFF_GST, 64);
        bulk_commit(); bulk_wait_all();
        flag_add(&g_flag_g[rb * FS]);
        flag_wait(&g_flag_g[rb * FS], ep1 * 8, t0);
        fence_async_global();
        mbar_expect_tx(bars + 8 * BAR_GIN, 512);
        bulk_load(sbase + OFF_GIN, &g_gate[rb * 128], 512, bars + 8 * BAR_GIN);
        TR(10);
      }
      __syncwarp();
    }
    mbar_wait(bars + 8 * (BAR_QRDY + aw), 0, t0);
    asm volatile("setmaxnreg.inc.sync.aligned.u32 96;");
    attention(sbase, aw, warp & 3, lane, rb, t0);
    if (tid == 256) TR(3);
  } else {
    asm volatile("setmaxnreg.dec.sync.aligned.u32 32;");
    if (warp == 16) {
      __syncwarp();
      cluster_wait();
#ifdef TRACE3
      if (lane == 0) TR(51);
#endif
      if (lane == 0) {
        int bi = 2; uint32_t bph = 1;
        const int nb = 32 + on + 4;
        for (int eb = 2; eb < nb; eb++) {
          if (eb == 4 || eb == 6) {
            const int ea = eb >> 1;
            mbar_expect_tx(bars + 8 * (BAR_FULLA + 1 + ea), 16384);
            tma_load_2d(sbase + OFF_A + (1 + ea) * SLOT, &P.tmX, ea * 64, rb * 128, bars + 8 * (BAR_FULLA + 1 + ea));
          }
          const uint32_t fb = bars + 8 * (BAR_FULLB + bi), dst = sbase + OFF_B + bi * SLOT + rank * 8192;
          mbar_wait(bars + 8 * (BAR_EMPTYB + bi), bph, t0);
          if (eb < 16) {
            mbar_expect_tx(fb, typeB ? 12288 : 16384);
            tma_load_3d_mc(dst, &P.tmWqkv, 64 * j, eb * 32 + rank * 16, 0, fb);
            if (!typeB) tma_load_3d_mc(dst + 6144, &P.tmW1a, 0, eb * 32 + rank * 16, 24 + (j >> 1), fb);
          }
          else if (eb < 32) { mbar_expect_tx(fb, 12288); tma_load_3d_mc(dst, &P.tmW1b, 0, (eb - 16) * 32 + rank * 16, 3 * j, fb); }
          else if (eb < 32 + on) { int ow; const int ch = oh_chunk(j, eb - 32, ow); mbar_expect_tx(fb, 16384); tma_load_3d_mc(dst, &P.tmW2, 0, ch * 64 + rank * 32, (j >> 1) * 2, fb); }
          else { mbar_expect_tx(fb, 16384); tma_load_4d_mc(dst, &P.tmWo, 64 * j, 0, eb - 32 - on, rank * 4, fb); }
#ifdef TRACE3
          if (eb < 6) TR(32 + eb);
#endif
          if (++bi == NB) { bi = 0; bph ^= 1; }
#ifndef NOPF
          if (eb == PFAT) {
            const int b = blockIdx.x;
             int ch = ea & 7, need = -1;
          if (ea >= 16 + on) { need = 8 + ea - 16 - on; ch = 20 + need; }
          else if (ea >= 19) ch = oh_chunk(j, ea - 16, need);
          if (need >= 0 && !((ready >> need) & 1)) {
            const unsigned* fp = need < 8 ? &g_flag_h[rb * 8 * FS] : need < 16 ? &g_flag_o[rb * 8 * FS] : &g_flag_e[rb * 8 * FS];
            const unsigned tgt = (need & 8) ? ep1 * 4 : ep1;
            do {
              unsigned v[8];
#pragma unroll
              for (int i = 0; i < 8; i++) v[i] = ld_relaxed(fp + i * FS);
#pragma unroll
              for (int i = 0; i < 8; i++) if ((int)(v[i] - tgt) >= 0) ready |= 1u << (i + (need & 24));
            } while (!((ready >> need) & 1) && clk32() - t0 < TIMEOUT);
            fence_async_global();
          }
 1; ea < 5; ea++) mbar_arrive(bars + 8 * (BAR_EMPTYA + ea));
        uint32_t aph = 0xE1;
        const int na = 16 + on + 8;
        unsigned ready = 0;
        for (int ea = 4; ea < na; ea++) {
          const int ai = a_slot(ea, 20 + on);
          const uint32_t fb = bars + 8 * (BAR_FULLA + ai), dst = sbase + OFF_A + ai * SLOT;
          int ch = ea & 7;
          if (ea >= 19) {
            ch = ea >= 16 + on ? 12 - on + ea : oh_chunk(j, ea - 16);
            while (!((ready >> ch) & 1) && clk32() - t0 < TIMEOUT) {
              const unsigned* fp = ch < 24 ? &g_flag_h[rb * 8 * FS] : ch < 28 ? &g_flag_e[rb * 8 * FS] : &g_flag_o[rb * 8 * FS];
              unsigned v[8];
#pragma unroll
              for (int i = 0; i < 8; i++) v[i] = ld_relaxed(fp + i * FS);
#pragma unroll
              for (int i = 0; i < 8; i++) {
                if (ch < 24) ready |= (uint64_t)((1u << min(max((int)(v[i] - (ep1 - 1) * 3), 0), 3)) - 1) << (3 * i);
                else if (ch < 28) { if (!(i & 1) && (int)(v[i] - ep1) >= 0) ready |= 1ull << (24 + (i >> 1)); }
                else if ((int)(v[i] - ep1 * 4) >= 0) ready |= 1ull << (28 + i);
              }
              fence_async_global();
            }
          }
          mbar_wait(bars + 8 * (BAR_EMPTYA + ai), (aph >> ai) & 1, t0);
          if (ea >= 16 && ea < 19) mbar_arrive(fb);
          else {
            mbar_arrive(bars + 8 * (BAR_EMPTYA + ai));
            mbar_expect_tx(fb, 16384);
            tma_load_2d(dst, ea < 16 ? &P.tmX : &P.tmHO, ch * 64, rb * 128, fb);
          }
#if !defined(TRACE2) && !defined(TRACE3)
          TR(24 + ea);
#endif
          aph ^= 1u << ai;
        }
      }
    } else {
      const int wg = warp - 18;
      cluster_wait();
      if (lane == 0 && wg == 0) {
        const uint32_t stg = bars + 8 * BAR_STG;
        mbar_wait(stg, 0, t0);
        for (int hh = 0; hh < 4; hh++) bulk_store(g_kv + ((size_t)(4 * j + hh) * SEQ + rb * 128) * 64, sbase + OFF_KV + hh * 8192, 8192);
        bulk_commit(); bulk_wait_all();
        flag_add(&g_flag_kv[(rb * 8 + j) * FS]);
        TR(21);
        if (!typeB) {
          mbar_wait(bars + 8 * BAR_STE, 0, t0);
          tma_store_2d(&P.tmHO, (24 + (j >> 1)) * 64, rb * 128, sbase + OFF_KV + 32768);
          bulk_commit(); bulk_wait_all();
          flag_add(&g_flag_e[(rb * 8 + j) * FS]);
        }
        mbar_arrive(bars + 8 * BAR_KVOK);
        mbar_wait(stg, 1, t0);
        for (int i = 0; i < 3; i++) { tma_store_2d(&P.tmHO, (3 * j + i) * 64, rb * 128, sbase + OFF_A + (1 + i) * SLOT); bulk_commit(); }
        asm volatile("cp.async.bulk.wait_group.read 2;" ::: "memory");
        mbar_arrive(bars + 8 * (BAR_EMPTYA + 1));
        asm volatile("cp.async.bulk.wait_group.read 1;" ::: "memory");
        mbar_arrive(bars + 8 * (BAR_EMPTYA + 2));
        bulk_wait_all();
        flag_add(&g_flag_h[(rb * 8 + j) * FS]); mbar_arrive(bars + 8 * (BAR_EMPTYA + 3));
        TR(22);
        {
          const unsigned old = atomicAdd(&g_done, 1u);
          if (old == gridDim.x - 1) { g_done = 0; *(volatile unsigned*)&g_epoch = ep1; }
        }
        mbar_wait(stg, 0, t0);
        bulk_store(g_part + (size_t)(rb * 8 + (j ^ 1)) * 16384, sbase + OFF_B + ((30 + on) % NB) * SLOT, 16384);
        bulk_commit(); bulk_wait_all();
        flag_add(&g_flag_p[(rb * 8 + (j ^ 1)) * FS]);
        TR(23);
      } else if (lane == 0) {
        const int nblk = rb >= 2 ? 3 : rb + 1;
        const uint32_t kvbytes = nblk * 8192;
        const uint8_t* kvsrc = g_kv + ((size_t)(4 * j) * SEQ + (rb + 1 - nblk) * 128) * 64;
        const uint32_t kvdst = sbase + OFF_KV + (3 - nblk) * 8192;
        {
          const unsigned* f0 = &g_flag_kv[(rb * 8 + j) * FS];
          const unsigned* f1 = rb >= 1 ? f0 - 8 * FS : f0;
          const unsigned* f2 = rb >= 2 ? f0 - 16 * FS : f0;
          unsigned v0, v1, v2;
          do { v0 = ld_relaxed(f0); v1 = ld_relaxed(f1); v2 = ld_relaxed(f2); }
          while (((int)(v0 - ep1) < 0 || (int)(v1 - ep1) < 0 || (int)(v2 - ep1) < 0) && clk32() - t0 < TIMEOUT);
        }
        TR(11);
        mbar_wait(bars + 8 * BAR_GIN, 0, t0);
        fence_async_global();
        mbar_expect_tx(bars + 8 * BAR_KVFULL, kvbytes);
        bulk_load(kvdst, kvsrc, kvbytes, bars + 8 * BAR_KVFULL);
        mbar_wait(bars + 8 * BAR_KVOK, 0, t0);
        mbar_expect_tx(bars + 8 * (BAR_KVFULL + 1), kvbytes);
        bulk_load(kvdst + KVBUF, kvsrc + (size_t)SEQ * 64, kvbytes, bars + 8 * (BAR_KVFULL + 1));
        for (int hh = 0; hh < 4; hh++) {
          for (int aw = 0; aw < 2; aw++) {
            mbar_wait(bars + 8 * (BAR_OST + aw), hh & 1, t0);
            tma_store_2d(&P.tmOs, DFF + hh * 128 + j * 16, rb * 128 + aw * 64, sbase + OFF_A + aw * 8192 + hh * 2048);
          }
          bulk_commit();
          if (hh < 2) {
            mbar_wait(bars + 8 * (BAR_KVEMPTY + hh), 0, t0);
            mbar_expect_tx(bars + 8 * (BAR_KVFULL + 2 + hh), kvbytes);
            bulk_load(kvdst + hh * KVBUF, kvsrc + (size_t)(hh + 2) * SEQ * 64, kvbytes, bars + 8 * (BAR_KVFULL + 2 + hh));
          }
          bulk_wait_all();
          flag_add(&g_flag_o[(rb * 8 + hh * 2 + (j >> 2)) * FS]);
          TR(12 + hh);
        }
      }
    }
  }
}

typedef CUresult (*EncodeFn)(CUtensorMap*, CUtensorMapDataType, cuuint32_t, void*, const cuuint64_t*, const cuuint64_t*, const cuuint32_t*,
                             const cuuint32_t*, CUtensorMapInterleave, CUtensorMapSwizzle, CUtensorMapL2promotion, CUtensorMapFloatOOBfill);

void make_map(EncodeFn enc, CUtensorMap* m, const void* ptr, int rank, const cuuint64_t* dims, const cuuint64_t* strides, const cuuint32_t* box,
              CUtensorMapSwizzle sw = CU_TENSOR_MAP_SWIZZLE_128B) {
  cuuint32_t es[4] = {1, 1, 1, 1};
  enc(m, CU_TENSOR_MAP_DATA_TYPE_BFLOAT16, rank, const_cast<void*>(ptr), dims, strides, box, es, CU_TENSOR_MAP_INTERLEAVE_NONE, sw,
      CU_TENSOR_MAP_L2_PROMOTION_L2_256B, CU_TENSOR_MAP_FLOAT_OOB_FILL_NONE);
}

}

extern "C" void kernel_launch(void* const* d_in, const int* in_sizes, int n_in, void* d_out, int out_size) {
  (void)in_sizes; (void)n_in; (void)out_size;
  static EncodeFn enc = nullptr;
  static void* ho_ptr = nullptr;
  if (!enc) {
    void* fn = nullptr; cudaDriverEntryPointQueryResult st;
    cudaGetDriverEntryPoint("cuTensorMapEncodeTiled", &fn, cudaEnableDefault, &st);
    enc = (EncodeFn)fn;
    cudaGetSymbolAddress(&ho_ptr, g_ho);
    cudaFuncSetAttribute(fused_kernel, cudaFuncAttributeMaxDynamicSharedMemorySize, SMEM_BYTES);
  }
  const __nv_bfloat16* x = (const __nv_bfloat16*)d_in[0];
  const __nv_bfloat16* wqkv = (const __nv_bfloat16*)d_in[1];
  const __nv_bfloat16* wo = (const __nv_bfloat16*)d_in[2];
  const __nv_bfloat16* w1 = (const __nv_bfloat16*)d_in[4];
  const __nv_bfloat16* w2 = (const __nv_bfloat16*)d_in[5];
  const __nv_bfloat16* gate_w = (const __nv_bfloat16*)d_in[6];
  Params P;
  { cuuint64_t d[2] = {DM, SEQ}, s[1] = {DM * 2}; cuuint32_t b[2] = {64, 128}; make_map(enc, &P.tmX, x, 2, d, s, b); }
  { cuuint64_t d[3] = {512, 512, 3}, s[2] = {1536 * 2, 512 * 2}; cuuint32_t b[3] = {64, 16, 3}; make_map(enc, &P.tmWqkv, wqkv, 3, d, s, b); }
  { cuuint64_t d[3] = {64, 512, 28}, s[2] = {DFF * 2, 128}; cuuint32_t b[3] = {64, 16, 1}; make_map(enc, &P.tmW1a, w1, 3, d, s, b);
    b[2] = 3; make_map(enc, &P.tmW1b, w1, 3, d, s, b); }
  { cuuint64_t d[3] = {64, DFF, 8}, s[2] = {DM * 2, 128}; cuuint32_t b[3] = {64, 32, 2}; make_map(enc, &P.tmW2, w2, 3, d, s, b); }
  { cuuint64_t d[4] = {DM, 16, 4, 8}, s[3] = {DM * 2, 16 * DM * 2, 64 * DM * 2}; cuuint32_t b[4] = {64, 16, 1, 4}; make_map(enc, &P.tmWo, wo, 4, d, s, b); }
  { cuuint64_t d[2] = {KHO, SEQ}, s[1] = {KHO * 2}; cuuint32_t b[2] = {64, 128}; make_map(enc, &P.tmHO, ho_ptr, 2, d, s, b);
    b[1] = 64; b[0] = 16; make_map(enc, &P.tmOs, ho_ptr, 2, d, s, b, CU_TENSOR_MAP_SWIZZLE_NONE); }
  P.x = x; P.gate_w = gate_w; P.w1 = w1; P.w2 = w2; P.wo = wo; P.wqkv = wqkv; P.out = (__nv_bfloat16*)d_out;
  fused_kernel<<<128, 640, SMEM_BYTES>>>(P);
}

#ifdef TRACE
extern "C" void dbg_trace(unsigned* host) { cudaDeviceSynchronize(); cudaMemcpyFromSymbol(host, g_trace, sizeof(g_trace)); }
#endif
#ifdef DEBUG_EXPORTS
extern "C" void dbg_copy(int which, void* dst) {
  cudaDeviceSynchronize();
  if (which == 0) cudaMemcpyFromSymbol(dst, g_kv, sizeof(g_kv), 0, cudaMemcpyDeviceToDevice);
  if (which == 2) cudaMemcpyFromSymbol(dst, g_ho, sizeof(g_ho), 0, cudaMemcpyDeviceToDevice);
  if (which == 3) cudaMemcpyFromSymbol(dst, g_gate, sizeof(g_gate), 0, cudaMemcpyDeviceToDevice);
  cudaDeviceSynchronize();
}
#endif
```

```cpp
#include <cuda_runtime.h>
#include <cuda_bf16.h>
#include <cuda.h>
#include <stdint.h>

#define DEVI __device__ __forceinline__

namespace {

constexpr int SEQ = 2048, DM = 512, DFF = 1792, KHO = 2304;
constexpr int NA = 5, NB = 6, SLOT = 16384, KVBUF = 24576;
constexpr int NA2 = 8;
constexpr int OFF_B = 0, OFF_A = NB * SLOT, OFF_KV = OFF_A + NA * SLOT, OFF_BAR = OFF_KV + 2 * KVBUF;
constexpr int OFF_GST = OFF_BAR + 512;
constexpr int OFF_GIN = OFF_BAR + 1024;
constexpr int OFF_NM = OFF_BAR + 1536;
constexpr int SMEM_BYTES = OFF_BAR + 2560;
constexpr uint32_t TIMEOUT = 1u << 28;
#ifndef WAIT_HINT_NS
#define WAIT_HINT_NS 20000u
#endif
#ifndef PFAT
#define PFAT 8
#endif
#ifndef SH
#define SH true
#endif
#ifndef SHW
#define SHW 0
#endif
#ifndef SHG
#define SHG 1
#endif
#ifndef PF0
#define PF0 0
#endif
#ifndef SHO
#define SHO true
#endif
#ifndef SHS
#define SHS 6
#endif
#ifndef TB
#define TB 0
#endif
#ifndef SHSB
#define SHSB SHS
#endif
constexpr int FS = 8;

constexpr int BAR_FULLA = 0, BAR_EMPTYA = BAR_FULLA + NA2, BAR_FULLB = BAR_EMPTYA + NA2, BAR_EMPTYB = BAR_FULLB + NB,
              BAR_KVFULL = BAR_EMPTYB + NB, BAR_KVEMPTY = BAR_KVFULL + 2, BAR_STG = BAR_KVEMPTY + 2, BAR_PIN = BAR_STG + 2, BAR_GATE = BAR_PIN + 1, BAR_STE = BAR_GATE + 2, BAR_PFREE = BAR_STE + 2, BAR_GIN = BAR_PFREE + 1, BAR_OST = BAR_GIN + 1, BAR_QRDY = BAR_OST + 4, BAR_KVOK = BAR_QRDY + 2;

__device__ __align__(1024) uint8_t g_kv[32 * SEQ * 64];
__device__ __align__(1024) __nv_bfloat16 g_ho[SEQ * KHO];
__device__ __align__(1024) uint8_t g_part[128 * 16384];
__device__ __align__(128) float g_gate[SEQ];
__device__ unsigned g_flag_kv[128 * FS], g_flag_h[128 * FS], g_flag_o[128 * FS], g_flag_g[16 * FS], g_flag_p[128 * FS], g_flag_e[128 * FS];
__device__ unsigned g_epoch, g_done;
#ifdef TRACE
__device__ unsigned g_trace[128 * 64];
#define TR(i) do { asm volatile("st.shared.u32 [%0], %1;" ::"r"(sbase + OFF_BAR + 640 + 4 * (i)), "r"(clk32() - t0)); } while (0)
#else
#define TR(i) do {} while (0)
#endif

struct Params {
  CUtensorMap tmX, tmWqkv, tmW1a, tmW1b, tmW2, tmWo, tmHO, tmOs;
  const __nv_bfloat16* x;
  const __nv_bfloat16* gate_w;
  const __nv_bfloat16* w1;
  const __nv_bfloat16* w2;
  const __nv_bfloat16* wo;
  const __nv_bfloat16* wqkv;
  __nv_bfloat16* out;
};

DEVI uint32_t smem_u32(const void* p) { return (uint32_t)__cvta_generic_to_shared(p); }
DEVI uint32_t clk32() { uint32_t c; asm volatile("mov.u32 %0, %%clock;" : "=r"(c)); return c; }
DEVI void mbar_init(uint32_t bar, uint32_t cnt) { asm volatile("mbarrier.init.shared::cta.b64 [%0], %1;" ::"r"(bar), "r"(cnt)); }
DEVI void mbar_expect_tx(uint32_t bar, uint32_t bytes) { asm volatile("mbarrier.arrive.expect_tx.shared::cta.b64 _, [%0], %1;" ::"r"(bar), "r"(bytes) : "memory"); }
DEVI void mbar_arrive(uint32_t bar) { asm volatile("mbarrier.arrive.shared::cta.b64 _, [%0];" ::"r"(bar) : "memory"); }
DEVI void mbar_arrive_cluster(uint32_t bar, uint32_t cta) {
  asm volatile("{ .reg .b32 ra; mapa.shared::cluster.u32 ra, %0, %1; mbarrier.arrive.shared::cluster.b64 _, [ra]; }" ::"r"(bar), "r"(cta) : "memory");
}
DEVI void mbar_wait(uint32_t bar, uint32_t parity, uint32_t t0) {
  asm volatile("{ .reg .pred p; .reg .u32 c;\n"
               "mbarrier.try_wait.parity.shared::cta.b64 p, [%0], %1;\n"
               "@p bra DONE_%=;\n"
               "WAIT_%=:\n"
               "mbarrier.try_wait.parity.shared::cta.b64 p, [%0], %1, %4;\n"
               "@p bra DONE_%=;\n"
               "mov.u32 c, %%clock; sub.u32 c, c, %2; setp.lt.u32 p, c, %3;\n"
               "@p bra WAIT_%=;\n"
               "DONE_%=: }" ::"r"(bar), "r"(parity), "r"(t0), "n"(TIMEOUT), "r"(WAIT_HINT_NS) : "memory");
}
DEVI unsigned ld_relaxed(const unsigned* p) { unsigned v; asm volatile("ld.relaxed.gpu.global.u32 %0, [%1];" : "=r"(v) : "l"(p) : "memory"); return v; }
DEVI void flag_wait(const unsigned* p, unsigned target, uint32_t t0) {
  while ((int)(ld_relaxed(p) - target) < 0) { if (clk32() - t0 > TIMEOUT) break; }
}
#ifndef FENCEW
#define FENCEW 1
#endif
DEVI void flag_add(unsigned* p) {
#if FENCEW == 1
  asm volatile("fence.proxy.async.global;\n red.release.gpu.global.add.u32 [%0], 1;" ::"l"(p) : "memory");
#elif FENCEW == 2
  asm volatile("fence.proxy.async;\n red.release.gpu.global.add.u32 [%0], 1;" ::"l"(p) : "memory");
#else
  asm volatile("red.relaxed.gpu.global.add.u32 [%0], 1;" ::"l"(p) : "memory");
#endif
}
DEVI void fence_async_smem() { asm volatile("fence.proxy.async.shared::cta;" ::: "memory"); }
DEVI void fence_async_global() {
  asm volatile("fence.acquire.gpu;" ::: "memory");
  asm volatile("fence.proxy.async.global;" ::: "memory");
}
DEVI void tma_load_2d(uint32_t dst, const CUtensorMap* m, int c0, int c1, uint32_t bar) {
  asm volatile("cp.async.bulk.tensor.2d.shared::cluster.global.mbarrier::complete_tx::bytes [%0], [%1, {%3, %4}], [%2];" ::"r"(dst), "l"(m), "r"(bar), "r"(c0), "r"(c1) : "memory");
}
DEVI void tma_load_3d(uint32_t dst, const CUtensorMap* m, int c0, int c1, int c2, uint32_t bar) {
  asm volatile("cp.async.bulk.tensor.3d.shared::cluster.global.mbarrier::complete_tx::bytes [%0], [%1, {%3, %4, %5}], [%2];"
               ::"r"(dst), "l"(m), "r"(bar), "r"(c0), "r"(c1), "r"(c2) : "memory");
}
DEVI void tma_load_3d_mc(uint32_t dst, const CUtensorMap* m, int c0, int c1, int c2, uint32_t bar) {
  asm volatile("cp.async.bulk.tensor.3d.shared::cluster.global.mbarrier::complete_tx::bytes.multicast::cluster [%0], [%1, {%3, %4, %5}], [%2], %6;"
               ::"r"(dst), "l"(m), "r"(bar), "r"(c0), "r"(c1), "r"(c2), "h"((uint16_t)3) : "memory");
}
DEVI void tma_load_4d_mc(uint32_t dst, const CUtensorMap* m, int c0, int c1, int c2, int c3, uint32_t bar) {
  asm volatile("cp.async.bulk.tensor.4d.shared::cluster.global.mbarrier::complete_tx::bytes.multicast::cluster [%0], [%1, {%3, %4, %5, %6}], [%2], %7;"
               ::"r"(dst), "l"(m), "r"(bar), "r"(c0), "r"(c1), "r"(c2), "r"(c3), "h"((uint16_t)3) : "memory");
}
DEVI void tma_store_2d(const CUtensorMap* m, int c0, int c1, uint32_t src) {
  asm volatile("cp.async.bulk.tensor.2d.global.shared::cta.bulk_group [%0, {%1, %2}], [%3];" ::"l"(m), "r"(c0), "r"(c1), "r"(src) : "memory");
}
DEVI void bulk_store(void* dst, uint32_t src, uint32_t bytes) {
  asm volatile("cp.async.bulk.global.shared::cta.bulk_group [%0], [%1], %2;" ::"l"(dst), "r"(src), "r"(bytes) : "memory");
}
DEVI void bulk_load(uint32_t dst, const void* src, uint32_t bytes, uint32_t bar) {
  asm volatile("cp.async.bulk.shared::cluster.global.mbarrier::complete_tx::bytes [%0], [%1], %2, [%3];" ::"r"(dst), "l"(src), "r"(bytes), "r"(bar) : "memory");
}
DEVI void bulk_commit() { asm volatile("cp.async.bulk.commit_group;" ::: "memory"); }
DEVI void bulk_wait_all() { asm volatile("cp.async.bulk.wait_group 0;" ::: "memory"); }
DEVI void l2_prefetch(const void* p, uint32_t bytes) { asm volatile("cp.async.bulk.prefetch.L2.global [%0], %1;" ::"l"(p), "r"(bytes) : "memory"); }
DEVI void cluster_arrive() { asm volatile("barrier.cluster.arrive.relaxed.aligned;" ::: "memory"); }
DEVI void cluster_wait() { asm volatile("barrier.cluster.wait.aligned;" ::: "memory"); }
template <int ID> DEVI void named_bar(int n) { asm volatile("bar.sync %0, %1;" ::"n"(ID), "r"(n) : "memory"); }
DEVI void wg_bar(int wg) { if (wg == 0) named_bar<1>(128); else named_bar<2>(128); }
DEVI void wgmma_fence() { asm volatile("wgmma.fence.sync.aligned;" ::: "memory"); }
DEVI void wgmma_commit() { asm volatile("wgmma.commit_group.sync.aligned;" ::: "memory"); }
template <int N> DEVI void wgmma_wait() { asm volatile("wgmma.wait_group.sync.aligned %0;" ::"n"(N) : "memory"); }
template <uint32_t LBO> DEVI uint64_t desc_sw128(uint32_t a16) {
  return ((uint64_t)(0x40000000u | (1024 >> 4)) << 32) | (a16 + ((LBO >> 4) << 16));
}
DEVI uint64_t desc_sw64(uint32_t a16) {
  return ((uint64_t)(0x80000000u | (512 >> 4)) << 32) | (a16 + ((512 >> 4) << 16));
}
DEVI uint32_t pack_bf16(float lo, float hi) { uint32_t r; asm("cvt.rn.bf16x2.f32 %0, %1, %2;" : "=r"(r) : "f"(hi), "f"(lo)); return r; }
DEVI void stsm_x4(uint32_t addr, uint32_t r0, uint32_t r1, uint32_t r2, uint32_t r3) {
  asm volatile("stmatrix.sync.aligned.m8n8.x4.shared.b16 [%0], {%1, %2, %3, %4};" ::"r"(addr), "r"(r0), "r"(r1), "r"(r2), "r"(r3) : "memory");
}
DEVI void sts128(uint32_t addr, uint32_t r0, uint32_t r1, uint32_t r2, uint32_t r3) {
  asm volatile("st.shared.v4.b32 [%0], {%1, %2, %3, %4};" ::"r"(addr), "r"(r0), "r"(r1), "r"(r2), "r"(r3) : "memory");
}
DEVI uint4 lds128(uint32_t addr) {
  uint4 v; asm volatile("ld.shared.v4.b32 {%0, %1, %2, %3}, [%4];" : "=r"(v.x), "=r"(v.y), "=r"(v.z), "=r"(v.w) : "r"(addr) : "memory"); return v;
}
DEVI float ex2(float x) { float y; asm("ex2.approx.ftz.f32 %0, %1;" : "=f"(y) : "f"(x)); return y; }

DEVI void wgmma_ss_n64(float (&d)[32], uint64_t da, uint64_t db) {
  asm volatile("wgmma.mma_async.sync.aligned.m64n64k16.f32.bf16.bf16 {%0, %1, %2, %3, %4, %5, %6, %7, %8, %9, %10, %11, %12, %13, %14, %15, %16, %17, %18, %19, %20, %21, %22, %23, %24, %25, %26, %27, %28, %29, %30, %31}, %32, %33, 1, 1, 1, 0, 1;"
    : "+f"(d[0]), "+f"(d[1]), "+f"(d[2]), "+f"(d[3]), "+f"(d[4]), "+f"(d[5]), "+f"(d[6]), "+f"(d[7]), "+f"(d[8]), "+f"(d[9]), "+f"(d[10]), "+f"(d[11]), "+f"(d[12]), "+f"(d[13]), "+f"(d[14]), "+f"(d[15]), "+f"(d[16]), "+f"(d[17]), "+f"(d[18]), "+f"(d[19]), "+f"(d[20]), "+f"(d[21]), "+f"(d[22]), "+f"(d[23]), "+f"(d[24]), "+f"(d[25]), "+f"(d[26]), "+f"(d[27]), "+f"(d[28]), "+f"(d[29]), "+f"(d[30]), "+f"(d[31])
    : "l"(da), "l"(db));
}
DEVI void wgmma_ss_n128(float (&d)[64], uint64_t da, uint64_t db) {
  asm volatile("wgmma.mma_async.sync.aligned.m64n128k16.f32.bf16.bf16 {%0, %1, %2, %3, %4, %5, %6, %7, %8, %9, %10, %11, %12, %13, %14, %15, %16, %17, %18, %19, %20, %21, %22, %23, %24, %25, %26, %27, %28, %29, %30, %31, %32, %33, %34, %35, %36, %37, %38, %39, %40, %41, %42, %43, %44, %45, %46, %47, %48, %49, %50, %51, %52, %53, %54, %55, %56, %57, %58, %59, %60, %61, %62, %63}, %64, %65, 1, 1, 1, 0, 1;"
    : "+f"(d[0]), "+f"(d[1]), "+f"(d[2]), "+f"(d[3]), "+f"(d[4]), "+f"(d[5]), "+f"(d[6]), "+f"(d[7]), "+f"(d[8]), "+f"(d[9]), "+f"(d[10]), "+f"(d[11]), "+f"(d[12]), "+f"(d[13]), "+f"(d[14]), "+f"(d[15]), "+f"(d[16]), "+f"(d[17]), "+f"(d[18]), "+f"(d[19]), "+f"(d[20]), "+f"(d[21]), "+f"(d[22]), "+f"(d[23]), "+f"(d[24]), "+f"(d[25]), "+f"(d[26]), "+f"(d[27]), "+f"(d[28]), "+f"(d[29]), "+f"(d[30]), "+f"(d[31]), "+f"(d[32]), "+f"(d[33]), "+f"(d[34]), "+f"(d[35]), "+f"(d[36]), "+f"(d[37]), "+f"(d[38]), "+f"(d[39]), "+f"(d[40]), "+f"(d[41]), "+f"(d[42]), "+f"(d[43]), "+f"(d[44]), "+f"(d[45]), "+f"(d[46]), "+f"(d[47]), "+f"(d[48]), "+f"(d[49]), "+f"(d[50]), "+f"(d[51]), "+f"(d[52]), "+f"(d[53]), "+f"(d[54]), "+f"(d[55]), "+f"(d[56]), "+f"(d[57]), "+f"(d[58]), "+f"(d[59]), "+f"(d[60]), "+f"(d[61]), "+f"(d[62]), "+f"(d[63])
    : "l"(da), "l"(db));
}
DEVI void wgmma_qk64(float (&d)[32], uint32_t a0, uint32_t a1, uint32_t a2, uint32_t a3, uint64_t db) {
  asm volatile("wgmma.mma_async.sync.aligned.m64n64k16.f32.bf16.bf16 {%0, %1, %2, %3, %4, %5, %6, %7, %8, %9, %10, %11, %12, %13, %14, %15, %16, %17, %18, %19, %20, %21, %22, %23, %24, %25, %26, %27, %28, %29, %30, %31}, {%32, %33, %34, %35}, %36, 0, 1, 1, 0;"
    : "=f"(d[0]), "=f"(d[1]), "=f"(d[2]), "=f"(d[3]), "=f"(d[4]), "=f"(d[5]), "=f"(d[6]), "=f"(d[7]), "=f"(d[8]), "=f"(d[9]), "=f"(d[10]), "=f"(d[11]), "=f"(d[12]), "=f"(d[13]), "=f"(d[14]), "=f"(d[15]), "=f"(d[16]), "=f"(d[17]), "=f"(d[18]), "=f"(d[19]), "=f"(d[20]), "=f"(d[21]), "=f"(d[22]), "=f"(d[23]), "=f"(d[24]), "=f"(d[25]), "=f"(d[26]), "=f"(d[27]), "=f"(d[28]), "=f"(d[29]), "=f"(d[30]), "=f"(d[31])
    : "r"(a0), "r"(a1), "r"(a2), "r"(a3), "l"(db));
}
DEVI void wgmma_pv(float (&d)[8], uint32_t a0, uint32_t a1, uint32_t a2, uint32_t a3, uint64_t db) {
  asm volatile("wgmma.mma_async.sync.aligned.m64n16k16.f32.bf16.bf16 {%0, %1, %2, %3, %4, %5, %6, %7}, {%8, %9, %10, %11}, %12, 1, 1, 1, 1;"
    : "+f"(d[0]), "+f"(d[1]), "+f"(d[2]), "+f"(d[3]), "+f"(d[4]), "+f"(d[5]), "+f"(d[6]), "+f"(d[7])
    : "r"(a0), "r"(a1), "r"(a2), "r"(a3), "l"(db));
}
DEVI void wgmma_pv0(float (&d)[8], uint32_t a0, uint32_t a1, uint32_t a2, uint32_t a3, uint64_t db) {
  asm volatile("wgmma.mma_async.sync.aligned.m64n16k16.f32.bf16.bf16 {%0, %1, %2, %3, %4, %5, %6, %7}, {%8, %9, %10, %11}, %12, 0, 1, 1, 1;"
    : "=f"(d[0]), "=f"(d[1]), "=f"(d[2]), "=f"(d[3]), "=f"(d[4]), "=f"(d[5]), "=f"(d[6]), "=f"(d[7])
    : "r"(a0), "r"(a1), "r"(a2), "r"(a3), "l"(db));
}


template <int N> struct Acc { float a[64]; float b[(N - 128) / 2]; DEVI float& operator[](int i) { return i < 64 ? a[i] : b[i - 64]; } };
template <> struct Acc<128> { float a[64]; DEVI float& operator[](int i) { return a[i]; } };
template <int N> DEVI void wgmma_ss(Acc<N>& d, uint64_t da, uint64_t db) {
  wgmma_ss_n128(d.a, da, db);
  if constexpr (N == 192) wgmma_ss_n64(d.b, da, db + 256);
  if constexpr (N == 256) wgmma_ss_n128(d.b, da, db + 256);
}

DEVI int oh_chunk(inDEVI int oh_chunk(int j, int i, int& need) {
  if (i >= 3 && i < 5) { const int e = (j & 1) * 2 + i - 3; need = 16 + 2 * e; return 24 + e; }
  if (i >= 5) i -= 2;
  int o, r;
  if (i >= 12) { o = (j + 5) & 7; r = i - 11; }
  else { const int g = i / 3; o = (j + 2 * g) & 7; r = i - 3 * g; }
  need = o;
  return 3 * o + r;
}

 int k = i - 5;
    r = k < 3 ? 0 : k < 5 ? 1 : 2; g = k < 3 ? 1 + k : 1 + ((k - 3) & 1);
  }
  return 3 * ((j + 2 * g) & 7) + r;
}

DEVI int a_slot(int e, int) { return 1 + (e & 3); }

struct Ctx {
  uint32_t sbase, bars, peer, t0, a16, b16;
  int wg, lane;
  int ai, bi; uint32_t aph, bph;
  int brem, ae;
  int pa, pb;
};

DEVI void release_prev(Ctx& c) {
  if (c.pb >= 0) {
    if (c.lane == 0) mbar_arrive(c.bars + 8 * (BAR_EMPTYB + c.pb));
    if (c.lane == 1) mbar_arrive_cluster(c.bars + 8 * (BAR_EMPTYB + c.pb), c.peer);
  }
  if (c.pa >= 0 && c.lane == 2) mbar_arrive(c.bars + 8 * (BAR_EMPTYA + c.pa));
}

DEVI void gemm_wait(Ctx& c) {
  asm volatile("{ .reg .pred p, q; .reg .u32 c;\n"
               "mbarrier.try_wait.parity.shared::cta.b64 p, [%0], %1;\n"
               "mbarrier.try_wait.parity.shared::cta.b64 q, [%2], %3;\n"
               "and.pred p, p, q;\n"
               "@p bra DONE_%=;\n"
               "WAIT_%=:\n"
               "mbarrier.try_wait.parity.shared::cta.b64 p, [%0], %1, %6;\n"
               "mbarrier.try_wait.parity.shared::cta.b64 q, [%2], %3, %6;\n"
               "and.pred p, p, q;\n"
               "@p bra DONE_%=;\n"
               "mov.u32 c, %%clock; sub.u32 c, c, %4; setp.lt.u32 p, c, %5;\n"
               "@p bra WAIT_%=;\n"
               "DONE_%=: }" ::"r"(c.bars + 8 * (BAR_FULLA + c.ai)), "r"((c.aph >> c.ai) & 1), "r"(c.bars + 8 * (BAR_FULLB + c.bi)), "r"(c.bph), "r"(c.t0),
               "n"(TIMEOUT), "r"(WAIT_HINT_NS) : "memory");
}
template <int N, bool SHALLOW>
DEVI void gemm_group(Acc<N>& acc, Ctx& c, int g, int& npa, int& npb) {
  const uint32_t a16 = c.a16 + c.ai * (SLOT >> 4);
  const uint32_t b16 = c.b16 + c.bi * (SLOT >> 4);
  bool adv;
  if constexpr (N >= 192) {
    const uint32_t a2 = a16 + (g & 1) * 4;
    wgmma_ss<N>(acc, desc_sw128<16>(a2), desc_sw128<2048>(b16));
    if (SHALLOW) { wgmma_commit(); wgmma_wait<SHW>(); }
    wgmma_ss<N>(acc, desc_sw128<16>(a2 + 2), desc_sw128<2048>(b16 + 512));
    adv = g & 1;
  } else {
#pragma unroll
    for (int s = 0; s < 4; s++) {
      wgmma_ss<N>(acc, desc_sw128<16>(a16 + s * 2), desc_sw128<4096>(b16 + (s >> 1) * 512 + (s & 1) * 128));
      if (SHALLOW && s < 3 && (SHG == 1 || s == 1)) { wgmma_commit(); wgmma_wait<SHW>(); }
    }
    adv = true;
  }
  wgmma_commit();
  npb = c.brem > 0 ? c.bi : -1;
  c.brem--;
  if (++c.bi == NB) { c.bi = 0; c.bph ^= 1; }
  npa = -1;
  if (adv) { npa = c.ai; c.aph ^= 1u << c.ai; c.ae++; c.ai = 1 + (c.ae & 3); }
}

template <int N, bool SHALLOW = false>
DEVI void bare_groups(Acc<N>& acc, Ctx& c, int g0, int g1) {
  for (int g = g0; g < g1; g++) {
    int npa, npb;
#ifdef TRACE3
    { const uint32_t sbase = c.sbase, t0 = c.t0;
      if (c.brem > 30 && threadIdx.x == 0 && g < 6) { mbar_wait(c.bars + 8 * (BAR_FULLA + c.ai), (c.aph >> c.ai) & 1, c.t0); TR(40 + g); } }
#endif
    gemm_wait(c);
#ifdef TRACE3
    { const uint32_t sbase = c.sbase, t0 = c.t0; if (c.brem > 30 && threadIdx.x == 0 && g < 8) TR(24 + g); }
#endif
    wgmma_fence();
    gemm_group<N, SHALLOW>(acc, c, g, npa, npb);
    wgmma_wait<SHALLOW ? SHW : 1>();
    release_prev(c);
    c.pa = npa; c.pb = npb;
  }
}
DEVI void drain(Ctx& c) {
  wgmma_wait<0>();
  release_prev(c);
  c.pa = c.pb = -1;
}

constexpr float SC = 0.25f * 1.4426950408889634f;

#define ONCE _Pragma("unroll 1") for (unsigned once_ = 0; once_ < gridDim.y; once_++)

struct Gate { float g0, g1; };

DEVI void kill32(float (&S)[32]) {
#pragma unroll
  for (int i = 0; i < 32; i++) S[i] = __int_as_float(0xff800000);
}
DEVI void row_max(const float (&S)[32], float& x0, float& x1) {
  float y0 = S[1], y1 = S[3];
  x0 = fmaxf(x0, S[0]); x1 = fmaxf(x1, S[2]);
#pragma unroll
  for (int n = 1; n < 8; n++) {
    x0 = fmaxf(x0, S[4 * n]); y0 = fmaxf(y0, S[4 * n + 1]); x1 = fmaxf(x1, S[4 * n + 2]); y1 = fmaxf(y1, S[4 * n + 3]);
  }
  x0 = fmaxf(x0, y0); x1 = fmaxf(x1, y1);
}
DEVI void quad_max(float& x0, float& x1) {
  x0 = fmaxf(x0, __shfl_xor_sync(0xffffffffu, x0, 1)); x1 = fmaxf(x1, __shfl_xor_sync(0xffffffffu, x1, 1));
  x0 = fmaxf(x0, __shfl_xor_sync(0xffffffffu, x0, 2)); x1 = fmaxf(x1, __shfl_xor_sync(0xffffffffu, x1, 2));
}
DEVI void exp32(const float (&S)[32], float (&E)[32], float n0, float n1, float (&l)[4]) {
#pragma unroll
  for (int i = 0; i < 32; i++) { E[i] = ex2(fmaf(S[i], SC, (i & 2) ? n1 : n0)); l[i & 3] += E[i]; }
}
DEVI void pack32(const float (&E)[32], uint32_t (&P)[16]) {
#pragma unroll
  for (int i = 0; i < 16; i++) P[i] = pack_bf16(E[2 * i], E[2 * i + 1]);
}
template <bool FIRST> DEVI void pv4(float (&O)[8], const uint32_t (&P)[16], uint32_t v16) {
  if (FIRST) wgmma_pv0(O, P[0], P[1], P[2], P[3], desc_sw64(v16)); else wgmma_pv(O, P[0], P[1], P[2], P[3], desc_sw64(v16));
#pragma unroll
  for (int k = 1; k < 4; k++) wgmma_pv(O, P[4 * k], P[4 * k + 1], P[4 * k + 2], P[4 * k + 3], desc_sw64(v16 + k * 64));
}
DEVI bool wg_any(int wg, bool v) {
  uint32_t r;
  if (wg == 0) asm volatile("{ .reg .pred p, q; setp.ne.u32 p, %1, 0; bar.red.or.pred q, 4, 128, p; selp.u32 %0, 1, 0, q; }" : "=r"(r) : "r"((uint32_t)v) : "memory");
  else asm volatile("{ .reg .pred p, q; setp.ne.u32 p, %1, 0; bar.red.or.pred q, 5, 128, p; selp.u32 %0, 1, 0, q; }" : "=r"(r) : "r"((uint32_t)v) : "memory");
  return r != 0;
}
DEVI void get_gate(Gate& g, uint32_t sbase, int row16, int lane, uint32_t t0) {
  mbar_wait(sbase + OFF_BAR + 8 * BAR_GIN, 0, t0);
  const uint32_t a = sbase + OFF_GIN + (row16 * 16 + (lane >> 2)) * 4;
  asm volatile("ld.shared.f32 %0, [%1];" : "=f"(g.g0) : "r"(a) : "memory");
  asm volatile("ld.shared.f32 %0, [%1];" : "=f"(g.g1) : "r"(a + 32) : "memory");
}

DEVI void attention(uint32_t sbase, int aw, int wi, int lane, int rb, uint32_t t0) {
  const uint32_t bars = sbase + OFF_BAR;
  const uint32_t kvb = ((sbase & 0x3FFFF) + OFF_KV + aw * 4096) >> 4;
  const int cmin = 4 - 2 * rb - aw;
  const int rowc = wi * 16 + (lane >> 2) - (lane & 3) * 2;
  const uint32_t qst = sbase + OFF_A + aw * 8192;
  const float NINF = __int_as_float(0xff800000);
  const int tlo = max(cmin, 1);
#pragma unroll 1
  for (int h = 0; h < 4; h++) {
    const uint32_t kb = kvb + (h & 1) * (KVBUF >> 4);
    const uint4 q = lds128(qst + h * 2048 + (wi * 32 + lane) * 16);
    float O[8], l0, l1;
    uint32_t nm;
    asm volatile("ld.shared.u32 %0, [%1];" : "=r"(nm) : "r"(sbase + OFF_NM + ((aw * 4 + wi) * 32 + (lane & 28) + h) * 4) : "memory");
    float n0 = __uint_as_float(nm << 16), n1 = __uint_as_float(nm & 0xffff0000u);
    mbar_wait(bars + 8 * (BAR_KVFULL + (h & 1)), h >> 1, t0);
#ifdef SKEW
    if (h == 0 && aw == 1) { const uint32_t ts = clk32(); while (clk32() - ts < SKEW) {} }
#endif
#pragma unroll 1
    for (int attempt = 0; attempt < 2; attempt++) {
      float l[4] = {0.f, 0.f, 0.f, 0.f};
      uint32_t P[16];
      {
        float S[32], F[32];
        wgmma_fence();
        wgmma_qk64(S, q.x, q.y, q.z, q.w, desc_sw64(kb + 4 * 256));
        wgmma_qk64(F, q.x, q.y, q.z, q.w, desc_sw64(kb));
        wgmma_commit();
        wgmma_wait<0>();
        for (int r = 0; r < (cmin > 0 ? 1 : 0); r++) kill32(F);
        float M[32];
#pragma unroll
        for (int i = 0; i < 32; i++) M[i] = ((i >> 2) * 8 + (i & 1) > rowc + (i & 2) * 4) ? F[i] : S[i];
        for (int r = 0; r < attempt; r++) {
          row_max(M, n0, n1);
          quad_max(n0, n1);
          n0 *= -SC; n1 *= -SC;
        }
        exp32(M, M, n0, n1, l);
        pack32(M, P);
        uint32_t PF[16];
#pragma unroll
        for (int i = 0; i < 16; i++) {
          const int col = (i >> 1) * 8, r = rowc + (i & 1) * 8;
          const uint32_t m = (col > r ? 0xFFFFu : 0u) | (col + 1 > r ? 0xFFFF0000u : 0u);
          PF[i] = P[i] & m; P[i] &= ~m;
        }
        wgmma_fence();
        pv4<true>(O, PF, kb + 2);
        wgmma_commit();
#ifndef NOPFW
        wgmma_wait<0>();
#endif
      }
      int t = 3;
#pragma unroll 1
      for (; t >= tlo; t--) {
        float S[32];
        wgmma_fence();
        wgmma_qk64(S, q.x, q.y, q.z, q.w, desc_sw64(kb + t * 256));
        wgmma_commit();
        pv4<false>(O, P, kb + (t + 1) * 256 + 2);
        wgmma_commit();
        wgmma_wait<1>();
        ONCE { exp32(S, S, n0, n1, l); }
        wgmma_wait<0>();
        pack32(S, P);
      }
      wgmma_fence();
      pv4<false>(O, P, kb + (t + 1) * 256 + 2);
      wgmma_commit();
      l0 = l[0] + l[1]; l1 = l[2] + l[3];
      l0 += __shfl_xor_sync(0xffffffffu, l0, 1); l1 += __shfl_xor_sync(0xffffffffu, l1, 1);
      l0 += __shfl_xor_sync(0xffffffffu, l0, 2); l1 += __shfl_xor_sync(0xffffffffu, l1, 2);
      const bool redo = wg_any(aw, attempt == 0 && !(l0 > 1e-6f && l0 < 1e18f && l1 > 1e-6f && l1 < 1e18f));
      wgmma_wait<0>();
      if (!redo) break;
      n0 = NINF; n1 = NINF;
#pragma unroll 1
      for (int u = 3; u >= tlo; u--) {
        float S[32];
        wgmma_fence();
        wgmma_qk64(S, q.x, q.y, q.z, q.w, desc_sw64(kb + u * 256));
        wgmma_commit();
        wgmma_wait<0>();
        row_max(S, n0, n1);
      }
    }
    if (lane == 0) mbar_arrive(bars + 8 * (BAR_KVEMPTY + (h & 1)));
    Gate g;
    get_gate(g, sbase, aw * 4 + wi, lane, t0);
    const float c0 = __fdividef(g.g0, l0), c1 = __fdividef(g.g1, l1);
    const int mi = lane >> 3;
    const int srow = wi * 16 + (lane & 7) + 8 * (mi & 1);
    stsm_x4(qst + h * 2048 + srow * 32 + (mi >> 1) * 16, pack_bf16(O[0] * c0, O[1] * c0), pack_bf16(O[2] * c1, O[3] * c1),
            pack_bf16(O[4] * c0, O[5] * c0), pack_bf16(O[6] * c1, O[7] * c1));
    fence_async_smem();
    __syncwarp();
    if (lane == 0) mbar_arrive(bars + 8 * (BAR_OST + h));
  }
}

template <int CH, int N>
DEVI void store_h_chunk(Acc<N>& acc, uint32_t base  , int lane, float s0, float s1) {
  const int mi = lane >> 3;
#pragma unroll
  for (int tp = 0; tp < 4; tp++) {
    const int t = CH * 8 + tp * 2;
    const uint32_t r0 = pack_bf16(fmaxf(acc[4 * t + 0], 0.f) * s0, fmaxf(acc[4 * t + 1], 0.f) * s0);
    const uint32_t r1 = pack_bf16(fmaxf(acc[4 * t + 2], 0.f) * s1, fmaxf(acc[4 * t + 3], 0.f) * s1);
    const uint32_t r2 = pack_bf16(fmaxf(acc[4 * t + 4], 0.f) * s0, fmaxf(acc[4 * t + 5], 0.f) * s0);
    const uint32_t r3 = pack_bf16(fmaxf(acc[4 * t + 6], 0.f) * s1, fmaxf(acc[4 * t + 7], 0.f) * s1);
    stsm_x4(base + (((tp * 2 + (mi >> 1)) ^ (lane & 7)) << 4), r0, r1, r2, r3);
  }
}

template <int N>
DEVI void phase_q(Ctx& c, int warp) {
  Acc<N> acc;
#pragma unroll
  for (int i = 0; i < N / 2; i++) acc[i] = 0.f;
  bare_groups<N>(acc, c, 0, 16);
  drain(c);
  const int lane = c.lane, mi = lane >> 3;
  const int row = warp * 16 + (lane & 7) + 8 * (mi & 1);
  const int sw = (row >> 1) & 3;
#pragma unroll
  for (int hh = 0; hh < 4; hh++) {
    const uint32_t base = c.sbase + OFF_KV + hh * 8192 + row * 64;
#pragma unroll
    for (int kv = 0; kv < 2; kv++) {
      const int t = 8 + kv * 8 + 2 * hh;
      stsm_x4(base + (((kv * 2 + (mi >> 1)) ^ sw) << 4),
              pack_bf16(acc[4 * t + 0], acc[4 * t + 1]), pack_bf16(acc[4 * t + 2], acc[4 * t + 3]),
              pack_bf16(acc[4 * t + 4], acc[4 * t + 5]), pack_bf16(acc[4 * t + 6], acc[4 * t + 7]));
    }
  }
  fence_async_smem();
  __syncwarp();
  if (lane == 0) mbar_arrive(c.bars + 8 * BAR_STG);
#pragma unroll
  for (int hh = 0; hh < 4; hh++)
    sts128(c.sbase + OFF_A + c.wg * 8192 + hh * 2048 + ((warp & 3) * 32 + lane) * 16,
           pack_bf16(acc[8 * hh], acc[8 * hh + 1]), pack_bf16(acc[8 * hh + 2], acc[8 * hh + 3]),
           pack_bf16(acc[8 * hh + 4], acc[8 * hh + 5]), pack_bf16(acc[8 * hh + 6], acc[8 * hh + 7]));
#pragma unroll
  for (int hh = 0; hh < 4; hh++) {
    const int q = 8 * hh, k = 32 + 8 * hh;
    float d0 = acc[q] * acc[k] + acc[q + 1] * acc[k + 1] + acc[q + 4] * acc[k + 4] + acc[q + 5] * acc[k + 5];
    float d1 = acc[q + 2] * acc[k + 2] + acc[q + 3] * acc[k + 3] + acc[q + 6] * acc[k + 6] + acc[q + 7] * acc[k + 7];
    d0 += __shfl_xor_sync(0xffffffffu, d0, 1); d1 += __shfl_xor_sync(0xffffffffu, d1, 1);
    d0 += __shfl_xor_sync(0xffffffffu, d0, 2); d1 += __shfl_xor_sync(0xffffffffu, d1, 2);
    if ((lane & 3) == hh)
      asm volatile("st.shared.u32 [%0], %1;" ::"r"(c.sbase + OFF_NM + (warp * 32 + lane) * 4), "r"(pack_bf16(-d0 * SC, -d1 * SC)) : "memory");
  }
  __syncwarp();
  if (lane == 0) mbar_arrive(c.bars + 8 * (BAR_QRDY + c.wg));
  if constexpr (N == 256) {
    Gate g;
    get_gate(g, c.sbase, warp, lane, c.t0);
    store_h_chunk<3>(acc, c.sbase + OFF_KV + 32768 + row * 128, lane, 1.f - g.g0, 1.f - g.g1);
    fence_async_smem();
    __syncwarp();
    if (lane == 0) mbar_arrive(c.bars + 8 * BAR_STE);
  }
}

DEVI void first_loads(const Params& P, uint32_t sbase, int e, int j, int rb) {
  const uint32_t bars = sbase + OFF_BAR, fb = bars + 8 * (BAR_FULLB + e), fa = bars + 8 * (BAR_FULLA + 1 + e);
  mbar_expect_tx(fa, 16384);
  mbar_expect_tx(fb, (j & 1) ? 12288 : 16384);
  if (e == 0) tma_load_2d(sbase + OFF_A + SLOT, &P.tmX, 0, rb * 128, fa);
#pragma unroll
  for (int r = 0; r < 2; r++) {
    tma_load_3d(sbase + OFF_B + e * SLOT + r * 8192, &P.tmWqkv, 64 * j, e * 32 + r * 16, 0, fb);
    if (!(j & 1)) tma_load_3d(sbase + OFF_B + e * SLOT + r * 8192 + 6144, &P.tmW1a, 0, e * 32 + r * 16, 24 + (j >> 1), fb);
  }
  if (e == 1) tma_load_2d(sbase + OFF_A + 2 * SLOT, &P.tmX, 64, rb * 128, fa);
}

__global__ void __cluster_dims__(2, 1, 1) __launch_bounds__(640, 1) fused_kernel(const __grid_constant__ Params P) {
  extern __shared__ __align__(1024) uint8_t smem_raw[];
  const uint32_t sbase = smem_u32(smem_raw);
  const uint32_t bars = sbase + OFF_BAR;
  const int tid = threadIdx.x, warp = tid >> 5, lane = tid & 31;
  const uint32_t rank = blockIdx.x & 1, peer = rank ^ 1;
  const int j = (blockIdx.x >> 1) & 7, rb = ((blockIdx.x >> 4) << 1) | rank;
  const uint32_t t0 = clk32();
#ifdef TRACE
  uint32_t gt0; asm volatile("mov.u32 %0, %%globaltimer_lo;" : "=r"(gt0));
#endif

  const int typeB = j & 1;
  if (tid == 544) {
    for (int s = 0; s < NA2; s++) mbar_init(bars + 8 * (BAR_FULLA + s), 1);
    for (int s = 0; s < NB; s++) mbar_init(bars + 8 * (BAR_FULLB + s), 1);
    fence_async_smem();
  } else if (tid < 8) {
    asm volatile("prefetch.tensormap [%0];" ::"l"(&P.tmX + tid) : "memory");
  } else if (tid == 512) {
    for (int s = 0; s < NA2; s++) mbar_init(bars + 8 * (BAR_EMPTYA + s), 9);
    for (int s = 0; s < NB; s++) mbar_init(bars + 8 * (BAR_EMPTYB + s), 16);
  } else if (tid == 576) {
    for (int s = 0; s < 2; s++) { mbar_init(bars + 8 * (BAR_KVFULL + s), 1); mbar_init(bars + 8 * (BAR_KVEMPTY + s), 8); mbar_init(bars + 8 * (BAR_OST + s), 8); mbar_init(bars + 8 * (BAR_OST + 2 + s), 8); mbar_init(bars + 8 * (BAR_QRDY + s), 4); }
    mbar_init(bars + 8 * BAR_STG, 8); mbar_init(bars + 8 * BAR_STE, 8); mbar_init(bars + 8 * BAR_KVOK, 1);
    mbar_init(bars + 8 * BAR_PIN, 1); mbar_init(bars + 8 * BAR_PFREE, 8); mbar_init(bars + 8 * BAR_GIN, 1);
  }
  if (tid >= 512 && lane == 0) asm volatile("fence.mbarrier_init.release.cluster;" ::: "memory");
#ifdef TRACE
  if (tid < 64) asm volatile("st.shared.u32 [%0], %1;" ::"r"(sbase + OFF_BAR + 640 + 4 * tid), "r"(0));
#endif
  const unsigned ep1 = ld_relaxed(&g_epoch) + 1;
  __syncwarp();
  cluster_arrive();
  if (tid == 544) { first_loads(P, sbase, 0, j, rb); first_loads(P, sbase, 1, j, rb); }
#if PF0 == 1
  if (tid == 544) { l2_prefetch(P.x + (size_t)(rb * 128 + j * 16) * DM, 16384); l2_prefetch((const uint8_t*)P.wqkv + blockIdx.x * 12288, 12288); }
#elif PF0 == 2
  if (tid == 320) { l2_prefetch(P.x + (size_t)(rb * 128 + j * 16) * DM, 16384); l2_prefetch((const uint8_t*)P.wqkv + blockIdx.x * 12288, 12288); }
#endif
  __syncwarp();

  const int on = 12 + 4 * typeB;

  if (warp < 8) {
    asm volatile("setmaxnreg.inc.sync.aligned.u32 160;");
    cluster_wait();
    const int wg = __shfl_sync(0xffffffffu, warp >> 2, 0);
    Ctx c{sbase, bars, peer, t0, ((sbase & 0x3FFFF) + OFF_A + wg * 8192) >> 4, ((sbase & 0x3FFFF) + OFF_B) >> 4, wg, lane, 1, 0, 0u, 0u, 32 + on + 4 - NB, 0, -1, -1};
    if (tid == 0) TR(0);
    if (typeB) phase_q<192>(c, warp);
    else phase_q<256>(c, warp);
    asm volatile("setmaxnreg.dec.sync.aligned.u32 128;");
    if (tid == 0) TR(2);
    {
      Acc<192> acc;
#pragma unroll
      for (int i = 0; i < 96; i++) acc[i] = 0.f;
      bare_groups<192>(acc, c, 0, typeB ? SHSB : SHS);
      bare_groups<192, SH>(acc, c, typeB ? SHSB : SHS, 16);
      Gate at;
      get_gate(at, sbase, warp, lane, t0);
      drain(c);
      if (tid == 0) TR(1);
      const uint32_t rowoff = (warp * 16 + (lane & 7) + 8 * ((lane >> 3) & 1)) * 128;
      const float s0 = 1.f - at.g0, s1 = 1.f - at.g1;
      constexpr int e0 = 1, e1 = 2, e2 = 3;
      mbar_wait(bars + 8 * (BAR_FULLA + e0), 0, t0);
      store_h_chunk<0>(acc, sbase + OFF_A + e0 * SLOT + rowoff, lane, s0, s1);
      mbar_wait(bars + 8 * (BAR_FULLA + e1), 0, t0);
      store_h_chunk<1>(acc, sbase + OFF_A + e1 * SLOT + rowoff, lane, s0, s1);
      mbar_wait(bars + 8 * (BAR_FULLA + e2), 0, t0);
      store_h_chunk<2>(acc, sbase + OFF_A + e2 * SLOT + rowoff, lane, s0, s1);
    }
    fence_async_smem();
    wg_bar(wg);
    if (lane == 0) mbar_arrive(bars + 8 * BAR_STG);
    if (tid == 0) TR(4);
    float own[32];
    {
      Acc<128> acc;
#pragma unroll
      for (int i = 0; i < 64; i++) acc[i] = 0.f;
#if TB == 1
      if (typeB) bare_groups<128, false>(acc, c, 0, on); else bare_groups<128, true>(acc, c, 0, on);
#elif TB == 2
      bare_groups<128, true>(acc, c, 0, typeB ? 8 : on);
      bare_groups<128, false>(acc, c, typeB ? 8 : on, on);
#else
      bare_groups<128, SHO>(acc, c, 0, on);
#endif
      drain(c);
      if (tid == 0) TR(5);
      if (lane == 0) mbar_arrive(bars + 8 * BAR_PFREE);
      named_bar<3>(256);
      const uint32_t pst = sbase + OFF_B + ((30 + on) % NB) * SLOT + wg * 8192 + (tid & 127) * 16;
#pragma unroll
      for (int i = 0; i < 4; i++) {
        uint32_t r[4];
#pragma unroll
        for (int k = 0; k < 4; k++) {
          const int idx = 8 * i + 2 * k;
          const float lo = typeB ? acc[idx] : acc[32 + idx], hi = typeB ? acc[idx + 1] : acc[32 + idx + 1];
          r[k] = pack_bf16(lo, hi);
        }
        sts128(pst + i * 2048, r[0], r[1], r[2], r[3]);
      }
#pragma unroll
      for (int i = 0; i < 32; i++) own[i] = typeB ? acc[32 + i] : acc[i];
      fence_async_smem();
      __syncwarp();
      if (lane == 0) mbar_arrive(bars + 8 * BAR_STG);
    }
#pragma unroll 1
    for (int g = 0; g < 8; g++) {
      const uint32_t a16 = c.a16 + c.ai * (SLOT >> 4);
      const uint32_t b16 = c.b16 + c.bi * (SLOT >> 4) + (g & 1) * 512;
      if (g == 6) {
        mbar_wait(bars + 8 * BAR_PIN, 0, t0);
        const uint32_t pin = sbase + OFF_B + ((31 + on) % NB) * SLOT + wg * 8192 + (tid & 127) * 16;
#pragma unroll
        for (int i = 0; i < 4; i++) {
          const uint4 v = lds128(pin + i * 2048);
          const uint32_t r[4] = {v.x, v.y, v.z, v.w};
#pragma unroll
          for (int k = 0; k < 4; k++) { own[8 * i + 2 * k] += __uint_as_float(r[k] << 16); own[8 * i + 2 * k + 1] += __uint_as_float(r[k] & 0xffff0000u); }
        }
        named_bar<3>(256);
        if (tid == 0) TR(7);
      }
      gemm_wait(c);
      wgmma_fence();
#pragma unroll
      for (int s = 0; s < 4; s++) wgmma_ss_n64(own, desc_sw128<16>(a16 + s * 2), desc_sw128<2048>(b16 + s * 128));
      wgmma_commit();
      wgmma_wait<0>();
      if (lane == 2) mbar_arrive(bars + 8 * (BAR_EMPTYA + c.ai));
      c.aph ^= 1u << c.ai;
      c.ae++; c.ai = a_slot(c.ae, 0);
      if (g & 1) { if (++c.bi == NB) { c.bi = 0; c.bph ^= 1; } }
    }
    if (tid == 0) TR(6);
    {
      const uint32_t ob = sbase + OFF_B + ((31 + on) % NB) * SLOT;
      const uint32_t wb = ob + warp * 2048;
      const uint32_t orow = wb + ((lane & 7) + 8 * ((lane >> 3) & 1)) * 128;
#pragma unroll
      for (int i = 0; i < 4; i++)
        stsm_x4(orow + (((i * 2 + (lane >> 4)) ^ (lane & 7)) << 4), pack_bf16(own[8 * i], own[8 * i + 1]), pack_bf16(own[8 * i + 2], own[8 * i + 3]),
                pack_bf16(own[8 * i + 4], own[8 * i + 5]), pack_bf16(own[8 * i + 6], own[8 * i + 7]));
      __syncwarp();
      uint4* o = (uint4*)(P.out + (size_t)(rb * 128 + warp * 16 + (lane >> 3)) * DM + j * 64) + (lane & 7);
#pragma unroll
      for (int i = 0; i < 4; i++) {
        const int r = i * 4 + (lane >> 3);
        o[i * 4 * (DM / 8)] = lds128(wb + r * 128 + (((lane & 7) ^ (r & 7)) << 4));
      }
    }
    if (tid == 0) TR(8);
#ifdef TRACE
    named_bar<3>(256);
    if (tid < 64) { uint32_t v; asm volatile("ld.shared.u32 %0, [%1];" : "=r"(v) : "r"(sbase + OFF_BAR + 640 + 4 * tid));
      if (tid == 16) v = gt0;
      if (tid == 17) asm volatile("mov.u32 %0, %%globaltimer_lo;" : "=r"(v));
      if (tid == 18) v = clk32() - t0;
      g_trace[blockIdx.x * 64 + tid] = v; }
#endif
  } else if (warp < 16) {
    asm volatile("setmaxnreg.dec.sync.aligned.u32 56;");
    cluster_wait();
    const int aw = __shfl_sync(0xffffffffu, (warp >> 2) & 1, 0);
    {
      const int rowg = rb * 128 + j * 16 + (warp - 8) * 2;
      const uint4* gw = (const uint4*)P.gate_w;
      const uint4* xr = (const uint4*)(P.x + (size_t)rowg * DM);
      mbar_wait(bars + 8 * (BAR_FULLB + 1), 0, t0);
      const uint4 w0 = __ldg(gw + lane), w1 = __ldg(gw + 32 + lane);
      const uint4 xa0 = __ldg(xr + lane), xa1 = __ldg(xr + 32 + lane), xb0 = __ldg(xr + 64 + lane), xb1 = __ldg(xr + 96 + lane);
#pragma unroll
      for (int i = 0; i < 4; i++) sts128(sbase + OFF_KV + 32768 + i * 4096 + (tid - 256) * 16, 0u, 0u, 0u, 0u);
      const uint32_t wa[8] = {w0.x, w0.y, w0.z, w0.w, w1.x, w1.y, w1.z, w1.w};
      const uint32_t xa[8] = {xa0.x, xa0.y, xa0.z, xa0.w, xa1.x, xa1.y, xa1.z, xa1.w};
      const uint32_t xb[8] = {xb0.x, xb0.y, xb0.z, xb0.w, xb1.x, xb1.y, xb1.z, xb1.w};
      float za = 0.f, zb = 0.f;
#pragma unroll
      for (int e = 0; e < 8; e++) {
        const float wl = __uint_as_float(wa[e] << 16), wh = __uint_as_float(wa[e] & 0xffff0000u);
        za = fmaf(__uint_as_float(xa[e] << 16), wl, za); za = fmaf(__uint_as_float(xa[e] & 0xffff0000u), wh, za);
        zb = fmaf(__uint_as_float(xb[e] << 16), wl, zb); zb = fmaf(__uint_as_float(xb[e] & 0xffff0000u), wh, zb);
      }
#pragma unroll
      for (int o = 16; o > 0; o >>= 1) { za += __shfl_xor_sync(0xffffffffu, za, o); zb += __shfl_xor_sync(0xffffffffu, zb, o); }
      if (lane < 2) asm volatile("st.shared.f32 [%0], %1;" ::"r"(sbase + OFF_GST + (warp - 8) * 8 + lane * 4), "f"(1.f / (1.f + __expf(-(lane ? zb : za)))) : "memory");
      fence_async_smem();
      named_bar<6>(256);
      if (tid == 256) {
        bulk_store(&g_gate[rb * 128 + j * 16], sbase + OFF_GST, 64);
        bulk_commit(); bulk_wait_all();
        flag_add(&g_flag_g[rb * FS]);
        flag_wait(&g_flag_g[rb * FS], ep1 * 8, t0);
        fence_async_global();
        mbar_expect_tx(bars + 8 * BAR_GIN, 512);
        bulk_load(sbase + OFF_GIN, &g_gate[rb * 128], 512, bars + 8 * BAR_GIN);
        TR(10);
      }
      __syncwarp();
    }
    mbar_wait(bars + 8 * (BAR_QRDY + aw), 0, t0);
    asm volatile("setmaxnreg.inc.sync.aligned.u32 96;");
    attention(sbase, aw, warp & 3, lane, rb, t0);
    if (tid == 256) TR(3);
  } else {
    asm volatile("setmaxnreg.dec.sync.aligned.u32 32;");
    if (warp == 16) {
      __syncwarp();
      cluster_wait();
#ifdef TRACE3
      if (lane == 0) TR(51);
#endif
      if (lane == 0) {
        int bi = 2; uint32_t bph = 1;
        const int nb = 32 + on + 4;
        for (int eb = 2; eb < nb; eb++) {
          if (eb == 4 || eb == 6) {
            const int ea = eb >> 1;
            mbar_expect_tx(bars + 8 * (BAR_FULLA + 1 + ea), 16384);
            tma_load_2d(sbase + OFF_A + (1 + ea) * SLOT, &P.tmX, ea * 64, rb * 128, bars + 8 * (BAR_FULLA + 1 + ea));
          }
          const uint32_t fb = bars + 8 * (BAR_FULLB + bi), dst = sbase + OFF_B + bi * SLOT + rank * 8192;
          mbar_wait(bars + 8 * (BAR_EMPTYB + bi), bph, t0);
          if (eb < 16) {
            mbar_expect_tx(fb, typeB ? 12288 : 16384);
            tma_load_3d_mc(dst, &P.tmWqkv, 64 * j, eb * 32 + rank * 16, 0, fb);
            if (!typeB) tma_load_3d_mc(dst + 6144, &P.tmW1a, 0, eb * 32 + rank * 16, 24 + (j >> 1), fb);
          }
          else if (eb < 32) { mbar_expect_tx(fb, 12288); tma_load_3d_mc(dst, &P.tmW1b, 0, (eb - 16) * 32 + rank * 16, 3 * j, fb); }
          else if (eb < 32 + on) { int ow; const int ch = oh_chunk(j, eb - 32, ow); mbar_expect_tx(fb, 16384); tma_load_3d_mc(dst, &P.tmW2, 0, ch * 64 + rank * 32, (j >> 1) * 2, fb); }
          else { mbar_expect_tx(fb, 16384); tma_load_4d_mc(dst, &P.tmWo, 64 * j, 0, eb - 32 - on, rank * 4, fb); }
#ifdef TRACE3
          if (eb < 6) TR(32 + eb);
#endif
          if (++bi == NB) { bi = 0; bph ^= 1; }
#ifndef NOPF
          if (eb == PFAT) {
            const int b = blockIdx.x;
             int ch = ea & 7, need = -1;
          if (ea >= 16 + on) { need = 8 + ea - 16 - on; ch = 20 + need; }
          else if (ea >= 19) ch = oh_chunk(j, ea - 16, need);
          if (need >= 0 && !((ready >> need) & 1)) {
            const unsigned* fp = need < 8 ? &g_flag_h[rb * 8 * FS] : need < 16 ? &g_flag_o[rb * 8 * FS] : &g_flag_e[rb * 8 * FS];
            const unsigned tgt = (need & 8) ? ep1 * 4 : ep1;
            do {
              unsigned v[8];
#pragma unroll
              for (int i = 0; i < 8; i++) v[i] = ld_relaxed(fp + i * FS);
#pragma unroll
              for (int i = 0; i < 8; i++) if ((int)(v[i] - tgt) >= 0) ready |= 1u << (i + (need & 24));
            } while (!((ready >> need) & 1) && clk32() - t0 < TIMEOUT);
            fence_async_global();
          }
 1; ea < 5; ea++) mbar_arrive(bars + 8 * (BAR_EMPTYA + ea));
        uint32_t aph = 0xE1;
        const int na = 16 + on + 8;
        unsigned ready = 0;
        for (int ea = 4; ea < na; ea++) {
          const int ai = a_slot(ea, 20 + on);
          const uint32_t fb = bars + 8 * (BAR_FULLA + ai), dst = sbase + OFF_A + ai * SLOT;
          int ch = ea & 7;
          if (ea >= 19) {
            ch = ea >= 16 + on ? 12 - on + ea : oh_chunk(j, ea - 16);
            while (!((ready >> ch) & 1) && clk32() - t0 < TIMEOUT) {
              const unsigned* fp = ch < 24 ? &g_flag_h[rb * 8 * FS] : ch < 28 ? &g_flag_e[rb * 8 * FS] : &g_flag_o[rb * 8 * FS];
              unsigned v[8];
#pragma unroll
              for (int i = 0; i < 8; i++) v[i] = ld_relaxed(fp + i * FS);
#pragma unroll
              for (int i = 0; i < 8; i++) {
                if (ch < 24) ready |= (uint64_t)((1u << min(max((int)(v[i] - (ep1 - 1) * 3), 0), 3)) - 1) << (3 * i);
                else if (ch < 28) { if (!(i & 1) && (int)(v[i] - ep1) >= 0) ready |= 1ull << (24 + (i >> 1)); }
                else if ((int)(v[i] - ep1 * 4) >= 0) ready |= 1ull << (28 + i);
              }
              fence_async_global();
            }
          }
          mbar_wait(bars + 8 * (BAR_EMPTYA + ai), (aph >> ai) & 1, t0);
          if (ea >= 16 && ea < 19) mbar_arrive(fb);
          else {
            mbar_arrive(bars + 8 * (BAR_EMPTYA + ai));
            mbar_expect_tx(fb, 16384);
            tma_load_2d(dst, ea < 16 ? &P.tmX : &P.tmHO, ch * 64, rb * 128, fb);
          }
#if !defined(TRACE2) && !defined(TRACE3)
          TR(24 + ea);
#endif
          aph ^= 1u << ai;
        }
      }
    } else {
      const int wg = warp - 18;
      cluster_wait();
      if (lane == 0 && wg == 0) {
        const uint32_t stg = bars + 8 * BAR_STG;
        mbar_wait(stg, 0, t0);
        for (int hh = 0; hh < 4; hh++) bulk_store(g_kv + ((size_t)(4 * j + hh) * SEQ + rb * 128) * 64, sbase + OFF_KV + hh * 8192, 8192);
        bulk_commit(); bulk_wait_all();
        flag_add(&g_flag_kv[(rb * 8 + j) * FS]);
        TR(21);
        if (!typeB) {
          mbar_wait(bars + 8 * BAR_STE, 0, t0);
          tma_store_2d(&P.tmHO, (24 + (j >> 1)) * 64, rb * 128, sbase + OFF_KV + 32768);
          bulk_commit(); bulk_wait_all();
          flag_add(&g_flag_e[(rb * 8 + j) * FS]);
        }
        mbar_arrive(bars + 8 * BAR_KVOK);
        mbar_wait(stg, 1, t0);
        for (int i = 0; i < 3; i++) { tma_store_2d(&P.tmHO, (3 * j + i) * 64, rb * 128, sbase + OFF_A + (1 + i) * SLOT); bulk_commit(); }
        asm volatile("cp.async.bulk.wait_group.read 2;" ::: "memory");
        mbar_arrive(bars + 8 * (BAR_EMPTYA + 1));
        asm volatile("cp.async.bulk.wait_group.read 1;" ::: "memory");
        mbar_arrive(bars + 8 * (BAR_EMPTYA + 2));
        bulk_wait_all();
        flag_add(&g_flag_h[(rb * 8 + j) * FS]); mbar_arrive(bars + 8 * (BAR_EMPTYA + 3));
        TR(22);
        {
          const unsigned old = atomicAdd(&g_done, 1u);
          if (old == gridDim.x - 1) { g_done = 0; *(volatile unsigned*)&g_epoch = ep1; }
        }
        mbar_wait(stg, 0, t0);
        bulk_store(g_part + (size_t)(rb * 8 + (j ^ 1)) * 16384, sbase + OFF_B + ((30 + on) % NB) * SLOT, 16384);
        bulk_commit(); bulk_wait_all();
        flag_add(&g_flag_p[(rb * 8 + (j ^ 1)) * FS]);
        TR(23);
      } else if (lane == 0) {
        const int nblk = rb >= 2 ? 3 : rb + 1;
        const uint32_t kvbytes = nblk * 8192;
        const uint8_t* kvsrc = g_kv + ((size_t)(4 * j) * SEQ + (rb + 1 - nblk) * 128) * 64;
        const uint32_t kvdst = sbase + OFF_KV + (3 - nblk) * 8192;
        {
          const unsigned* f0 = &g_flag_kv[(rb * 8 + j) * FS];
          const unsigned* f1 = rb >= 1 ? f0 - 8 * FS : f0;
          const unsigned* f2 = rb >= 2 ? f0 - 16 * FS : f0;
          unsigned v0, v1, v2;
          do { v0 = ld_relaxed(f0); v1 = ld_relaxed(f1); v2 = ld_relaxed(f2); }
          while (((int)(v0 - ep1) < 0 || (int)(v1 - ep1) < 0 || (int)(v2 - ep1) < 0) && clk32() - t0 < TIMEOUT);
        }
        TR(11);
        mbar_wait(bars + 8 * BAR_GIN, 0, t0);
        fence_async_global();
        mbar_expect_tx(bars + 8 * BAR_KVFULL, kvbytes);
        bulk_load(kvdst, kvsrc, kvbytes, bars + 8 * BAR_KVFULL);
        mbar_wait(bars + 8 * BAR_KVOK, 0, t0);
        mbar_expect_tx(bars + 8 * (BAR_KVFULL + 1), kvbytes);
        bulk_load(kvdst + KVBUF, kvsrc + (size_t)SEQ * 64, kvbytes, bars + 8 * (BAR_KVFULL + 1));
        for (int hh = 0; hh < 4; hh++) {
          mbar_wait(bars + 8 * (BAR_OST + hh), 0, t0);
          for (int aw = 0; aw < 2; aw++) {
            tma_store_2d(&P.tmOs, DFF + hh * 128 + j * 16, rb * 128 + aw * 64, sbase + OFF_A + aw * 8192 + hh * 2048);
          }
          bulk_commit();
          if (hh < 2) {
            mbar_wait(bars + 8 * (BAR_KVEMPTY + hh), 0, t0);
            mbar_expect_tx(bars + 8 * (BAR_KVFULL + hh), kvbytes);
            bulk_load(kvdst + hh * KVBUF, kvsrc + (size_t)(hh + 2) * SEQ * 64, kvbytes, bars + 8 * (BAR_KVFULL + hh));
          }
          bulk_wait_all();
          flag_add(&g_flag_o[(rb * 8 + hh * 2 + (j >> 2)) * FS]);
          TR(12 + hh);
        }
      }
    }
  }
}

typedef CUresult (*EncodeFn)(CUtensorMap*, CUtensorMapDataType, cuuint32_t, void*, const cuuint64_t*, const cuuint64_t*, const cuuint32_t*,
                             const cuuint32_t*, CUtensorMapInterleave, CUtensorMapSwizzle, CUtensorMapL2promotion, CUtensorMapFloatOOBfill);

void make_map(EncodeFn enc, CUtensorMap* m, const void* ptr, int rank, const cuuint64_t* dims, const cuuint64_t* strides, const cuuint32_t* box,
              CUtensorMapSwizzle sw = CU_TENSOR_MAP_SWIZZLE_128B) {
  cuuint32_t es[4] = {1, 1, 1, 1};
  enc(m, CU_TENSOR_MAP_DATA_TYPE_BFLOAT16, rank, const_cast<void*>(ptr), dims, strides, box, es, CU_TENSOR_MAP_INTERLEAVE_NONE, sw,
      CU_TENSOR_MAP_L2_PROMOTION_L2_256B, CU_TENSOR_MAP_FLOAT_OOB_FILL_NONE);
}

}

extern "C" void kernel_launch(void* const* d_in, const int* in_sizes, int n_in, void* d_out, int out_size) {
  (void)in_sizes; (void)n_in; (void)out_size;
  static EncodeFn enc = nullptr;
  static void* ho_ptr = nullptr;
  if (!enc) {
    void* fn = nullptr; cudaDriverEntryPointQueryResult st;
    cudaGetDriverEntryPoint("cuTensorMapEncodeTiled", &fn, cudaEnableDefault, &st);
    enc = (EncodeFn)fn;
    cudaGetSymbolAddress(&ho_ptr, g_ho);
    cudaFuncSetAttribute(fused_kernel, cudaFuncAttributeMaxDynamicSharedMemorySize, SMEM_BYTES);
  }
  const __nv_bfloat16* x = (const __nv_bfloat16*)d_in[0];
  const __nv_bfloat16* wqkv = (const __nv_bfloat16*)d_in[1];
  const __nv_bfloat16* wo = (const __nv_bfloat16*)d_in[2];
  const __nv_bfloat16* w1 = (const __nv_bfloat16*)d_in[4];
  const __nv_bfloat16* w2 = (const __nv_bfloat16*)d_in[5];
  const __nv_bfloat16* gate_w = (const __nv_bfloat16*)d_in[6];
  Params P;
  { cuuint64_t d[2] = {DM, SEQ}, s[1] = {DM * 2}; cuuint32_t b[2] = {64, 128}; make_map(enc, &P.tmX, x, 2, d, s, b); }
  { cuuint64_t d[3] = {512, 512, 3}, s[2] = {1536 * 2, 512 * 2}; cuuint32_t b[3] = {64, 16, 3}; make_map(enc, &P.tmWqkv, wqkv, 3, d, s, b); }
  { cuuint64_t d[3] = {64, 512, 28}, s[2] = {DFF * 2, 128}; cuuint32_t b[3] = {64, 16, 1}; make_map(enc, &P.tmW1a, w1, 3, d, s, b);
    b[2] = 3; make_map(enc, &P.tmW1b, w1, 3, d, s, b); }
  { cuuint64_t d[3] = {64, DFF, 8}, s[2] = {DM * 2, 128}; cuuint32_t b[3] = {64, 32, 2}; make_map(enc, &P.tmW2, w2, 3, d, s, b); }
  { cuuint64_t d[4] = {DM, 16, 4, 8}, s[3] = {DM * 2, 16 * DM * 2, 64 * DM * 2}; cuuint32_t b[4] = {64, 16, 1, 4}; make_map(enc, &P.tmWo, wo, 4, d, s, b); }
  { cuuint64_t d[2] = {KHO, SEQ}, s[1] = {KHO * 2}; cuuint32_t b[2] = {64, 128}; make_map(enc, &P.tmHO, ho_ptr, 2, d, s, b);
    b[1] = 64; b[0] = 16; make_map(enc, &P.tmOs, ho_ptr, 2, d, s, b, CU_TENSOR_MAP_SWIZZLE_NONE); }
  P.x = x; P.gate_w = gate_w; P.w1 = w1; P.w2 = w2; P.wo = wo; P.wqkv = wqkv; P.out = (__nv_bfloat16*)d_out;
  fused_kernel<<<128, 640, SMEM_BYTES>>>(P);
}

#ifdef TRACE
extern "C" void dbg_trace(unsigned* host) { cudaDeviceSynchronize(); cudaMemcpyFromSymbol(host, g_trace, sizeof(g_trace)); }
#endif
#ifdef DEBUG_EXPORTS
extern "C" void dbg_copy(int which, void* dst) {
  cudaDeviceSynchronize();
  if (which == 0) cudaMemcpyFromSymbol(dst, g_kv, sizeof(g_kv), 0, cudaMemcpyDeviceToDevice);
  if (which == 2) cudaMemcpyFromSymbol(dst, g_ho, sizeof(g_ho), 0, cudaMemcpyDeviceToDevice);
  if (which == 3) cudaMemcpyFromSymbol(dst, g_gate, sizeof(g_gate), 0, cudaMemcpyDeviceToDevice);
  cudaDeviceSynchronize();
}
#endif
```

```cpp
#include <cuda_runtime.h>
#include <cuda_bf16.h>
#include <cuda.h>
#include <stdint.h>

#define DEVI __device__ __forceinline__

namespace {

constexpr int SEQ = 2048, DM = 512, DFF = 1792, KHO = 2304;
constexpr int NA = 5, NB = 6, SLOT = 16384, KVBUF = 24576;
constexpr int NA2 = 8;
constexpr int OFF_B = 0, OFF_A = NB * SLOT, OFF_KV = OFF_A + NA * SLOT, OFF_BAR = OFF_KV + 2 * KVBUF;
constexpr int OFF_GST = OFF_BAR + 512;
constexpr int OFF_GIN = OFF_BAR + 1024;
constexpr int OFF_NM = OFF_BAR + 1536;
constexpr int SMEM_BYTES = OFF_BAR + 2560;
constexpr uint32_t TIMEOUT = 1u << 28;
#ifndef WAIT_HINT_NS
#define WAIT_HINT_NS 20000u
#endif
#ifndef PFAT
#define PFAT 8
#endif
#ifndef SH
#define SH true
#endif
#ifndef SHW
#define SHW 0
#endif
#ifndef SHG
#define SHG 1
#endif
#ifndef PF0
#define PF0 0
#endif
#ifndef SHO
#define SHO true
#endif
#ifndef SHS
#define SHS 6
#endif
#ifndef TB
#define TB 0
#endif
#ifndef SHSB
#define SHSB SHS
#endif
constexpr int FS = 8;

constexpr int BAR_FULLA = 0, BAR_EMPTYA = BAR_FULLA + NA2, BAR_FULLB = BAR_EMPTYA + NA2, BAR_EMPTYB = BAR_FULLB + NB,
              BAR_KVFULL = BAR_EMPTYB + NB, BAR_KVEMPTY = BAR_KVFULL + 2, BAR_STG = BAR_KVEMPTY + 2, BAR_PIN = BAR_STG + 2, BAR_GATE = BAR_PIN + 1, BAR_STE = BAR_GATE + 2, BAR_PFREE = BAR_STE + 2, BAR_GIN = BAR_PFREE + 1, BAR_OST = BAR_GIN + 1, BAR_QRDY = BAR_OST + 4, BAR_KVOK = BAR_QRDY + 2;

__device__ __align__(1024) uint8_t g_kv[32 * SEQ * 64];
__device__ __align__(1024) __nv_bfloat16 g_ho[SEQ * KHO];
__device__ __align__(1024) uint8_t g_part[128 * 16384];
__device__ __align__(128) float g_gate[SEQ];
__device__ unsigned g_flag_kv[128 * FS], g_flag_h[128 * FS], g_flag_o[128 * FS], g_flag_g[16 * FS], g_flag_p[128 * FS];
__device__ unsigned g_epoch, g_done;
#ifdef TRACE
__device__ unsigned g_trace[128 * 64];
#define TR(i) do { asm volatile("st.shared.u32 [%0], %1;" ::"r"(sbase + OFF_BAR + 640 + 4 * (i)), "r"(clk32() - t0)); } while (0)
#else
#define TR(i) do {} while (0)
#endif

struct Params {
  CUtensorMap tmX, tmWqkv, tmW1a, tmW1b, tmW2, tmWo, tmHO, tmOs;
  const __nv_bfloat16* x;
  const __nv_bfloat16* gate_w;
  const __nv_bfloat16* w1;
  const __nv_bfloat16* w2;
  const __nv_bfloat16* wo;
  const __nv_bfloat16* wqkv;
  __nv_bfloat16* out;
};

DEVI uint32_t smem_u32(const void* p) { return (uint32_t)__cvta_generic_to_shared(p); }
DEVI uint32_t clk32() { uint32_t c; asm volatile("mov.u32 %0, %%clock;" : "=r"(c)); return c; }
DEVI void mbar_init(uint32_t bar, uint32_t cnt) { asm volatile("mbarrier.init.shared::cta.b64 [%0], %1;" ::"r"(bar), "r"(cnt)); }
DEVI void mbar_expect_tx(uint32_t bar, uint32_t bytes) { asm volatile("mbarrier.arrive.expect_tx.shared::cta.b64 _, [%0], %1;" ::"r"(bar), "r"(bytes) : "memory"); }
DEVI void mbar_arrive(uint32_t bar) { asm volatile("mbarrier.arrive.shared::cta.b64 _, [%0];" ::"r"(bar) : "memory"); }
DEVI void mbar_arrive_cluster(uint32_t bar, uint32_t cta) {
  asm volatile("{ .reg .b32 ra; mapa.shared::cluster.u32 ra, %0, %1; mbarrier.arrive.shared::cluster.b64 _, [ra]; }" ::"r"(bar), "r"(cta) : "memory");
}
DEVI void mbar_wait(uint32_t bar, uint32_t parity, uint32_t t0) {
  asm volatile("{ .reg .pred p; .reg .u32 c;\n"
               "mbarrier.try_wait.parity.shared::cta.b64 p, [%0], %1;\n"
               "@p bra DONE_%=;\n"
               "WAIT_%=:\n"
               "mbarrier.try_wait.parity.shared::cta.b64 p, [%0], %1, %4;\n"
               "@p bra DONE_%=;\n"
               "mov.u32 c, %%clock; sub.u32 c, c, %2; setp.lt.u32 p, c, %3;\n"
               "@p bra WAIT_%=;\n"
               "DONE_%=: }" ::"r"(bar), "r"(parity), "r"(t0), "n"(TIMEOUT), "r"(WAIT_HINT_NS) : "memory");
}
DEVI unsigned ld_relaxed(const unsigned* p) { unsigned v; asm volatile("ld.relaxed.gpu.global.u32 %0, [%1];" : "=r"(v) : "l"(p) : "memory"); return v; }
DEVI void flag_wait(const unsigned* p, unsigned target, uint32_t t0) {
  while ((int)(ld_relaxed(p) - target) < 0) { if (clk32() - t0 > TIMEOUT) break; }
}
#ifndef FENCEW
#define FENCEW 1
#endif
DEVI void flag_add(unsigned* p) {
#if FENCEW == 1
  asm volatile("fence.proxy.async.global;\n red.release.gpu.global.add.u32 [%0], 1;" ::"l"(p) : "memory");
#elif FENCEW == 2
  asm volatile("fence.proxy.async;\n red.release.gpu.global.add.u32 [%0], 1;" ::"l"(p) : "memory");
#else
  asm volatile("red.relaxed.gpu.global.add.u32 [%0], 1;" ::"l"(p) : "memory");
#endif
}
DEVI void fence_async_smem() { asm volatile("fence.proxy.async.shared::cta;" ::: "memory"); }
DEVI void fence_async_global() {
  asm volatile("fence.acquire.gpu;" ::: "memory");
  asm volatile("fence.proxy.async.global;" ::: "memory");
}
DEVI void tma_load_2d(uint32_t dst, const CUtensorMap* m, int c0, int c1, uint32_t bar) {
  asm volatile("cp.async.bulk.tensor.2d.shared::cluster.global.mbarrier::complete_tx::bytes [%0], [%1, {%3, %4}], [%2];" ::"r"(dst), "l"(m), "r"(bar), "r"(c0), "r"(c1) : "memory");
}
DEVI void tma_load_3d(uint32_t dst, const CUtensorMap* m, int c0, int c1, int c2, uint32_t bar) {
  asm volatile("cp.async.bulk.tensor.3d.shared::cluster.global.mbarrier::complete_tx::bytes [%0], [%1, {%3, %4, %5}], [%2];"
               ::"r"(dst), "l"(m), "r"(bar), "r"(c0), "r"(c1), "r"(c2) : "memory");
}
DEVI void tma_load_3d_mc(uint32_t dst, const CUtensorMap* m, int c0, int c1, int c2, uint32_t bar) {
  asm volatile("cp.async.bulk.tensor.3d.shared::cluster.global.mbarrier::complete_tx::bytes.multicast::cluster [%0], [%1, {%3, %4, %5}], [%2], %6;"
               ::"r"(dst), "l"(m), "r"(bar), "r"(c0), "r"(c1), "r"(c2), "h"((uint16_t)3) : "memory");
}
DEVI void tma_load_4d_mc(uint32_t dst, const CUtensorMap* m, int c0, int c1, int c2, int c3, uint32_t bar) {
  asm volatile("cp.async.bulk.tensor.4d.shared::cluster.global.mbarrier::complete_tx::bytes.multicast::cluster [%0], [%1, {%3, %4, %5, %6}], [%2], %7;"
               ::"r"(dst), "l"(m), "r"(bar), "r"(c0), "r"(c1), "r"(c2), "r"(c3), "h"((uint16_t)3) : "memory");
}
DEVI void tma_store_2d(const CUtensorMap* m, int c0, int c1, uint32_t src) {
  asm volatile("cp.async.bulk.tensor.2d.global.shared::cta.bulk_group [%0, {%1, %2}], [%3];" ::"l"(m), "r"(c0), "r"(c1), "r"(src) : "memory");
}
DEVI void bulk_store(void* dst, uint32_t src, uint32_t bytes) {
  asm volatile("cp.async.bulk.global.shared::cta.bulk_group [%0], [%1], %2;" ::"l"(dst), "r"(src), "r"(bytes) : "memory");
}
DEVI void bulk_load(uint32_t dst, const void* src, uint32_t bytes, uint32_t bar) {
  asm volatile("cp.async.bulk.shared::cluster.global.mbarrier::complete_tx::bytes [%0], [%1], %2, [%3];" ::"r"(dst), "l"(src), "r"(bytes), "r"(bar) : "memory");
}
DEVI void bulk_commit() { asm volatile("cp.async.bulk.commit_group;" ::: "memory"); }
DEVI void bulk_wait_all() { asm volatile("cp.async.bulk.wait_group 0;" ::: "memory"); }
DEVI void l2_prefetch(const void* p, uint32_t bytes) { asm volatile("cp.async.bulk.prefetch.L2.global [%0], %1;" ::"l"(p), "r"(bytes) : "memory"); }
DEVI void cluster_arrive() { asm volatile("barrier.cluster.arrive.relaxed.aligned;" ::: "memory"); }
DEVI void cluster_wait() { asm volatile("barrier.cluster.wait.aligned;" ::: "memory"); }
template <int ID> DEVI void named_bar(int n) { asm volatile("bar.sync %0, %1;" ::"n"(ID), "r"(n) : "memory"); }
DEVI void wg_bar(int wg) { if (wg == 0) named_bar<1>(128); else named_bar<2>(128); }
DEVI void wgmma_fence() { asm volatile("wgmma.fence.sync.aligned;" ::: "memory"); }
DEVI void wgmma_commit() { asm volatile("wgmma.commit_group.sync.aligned;" ::: "memory"); }
template <int N> DEVI void wgmma_wait() { asm volatile("wgmma.wait_group.sync.aligned %0;" ::"n"(N) : "memory"); }
template <uint32_t LBO> DEVI uint64_t desc_sw128(uint32_t a16) {
  return ((uint64_t)(0x40000000u | (1024 >> 4)) << 32) | (a16 + ((LBO >> 4) << 16));
}
DEVI uint64_t desc_sw64(uint32_t a16) {
  return ((uint64_t)(0x80000000u | (512 >> 4)) << 32) | (a16 + ((512 >> 4) << 16));
}
DEVI uint32_t pack_bf16(float lo, float hi) { uint32_t r; asm("cvt.rn.bf16x2.f32 %0, %1, %2;" : "=r"(r) : "f"(hi), "f"(lo)); return r; }
DEVI void stsm_x4(uint32_t addr, uint32_t r0, uint32_t r1, uint32_t r2, uint32_t r3) {
  asm volatile("stmatrix.sync.aligned.m8n8.x4.shared.b16 [%0], {%1, %2, %3, %4};" ::"r"(addr), "r"(r0), "r"(r1), "r"(r2), "r"(r3) : "memory");
}
DEVI void sts128(uint32_t addr, uint32_t r0, uint32_t r1, uint32_t r2, uint32_t r3) {
  asm volatile("st.shared.v4.b32 [%0], {%1, %2, %3, %4};" ::"r"(addr), "r"(r0), "r"(r1), "r"(r2), "r"(r3) : "memory");
}
DEVI uint4 lds128(uint32_t addr) {
  uint4 v; asm volatile("ld.shared.v4.b32 {%0, %1, %2, %3}, [%4];" : "=r"(v.x), "=r"(v.y), "=r"(v.z), "=r"(v.w) : "r"(addr) : "memory"); return v;
}
DEVI float ex2(float x) { float y; asm("ex2.approx.ftz.f32 %0, %1;" : "=f"(y) : "f"(x)); return y; }

DEVI void wgmma_ss_n64(float (&d)[32], uint64_t da, uint64_t db) {
  asm volatile("wgmma.mma_async.sync.aligned.m64n64k16.f32.bf16.bf16 {%0, %1, %2, %3, %4, %5, %6, %7, %8, %9, %10, %11, %12, %13, %14, %15, %16, %17, %18, %19, %20, %21, %22, %23, %24, %25, %26, %27, %28, %29, %30, %31}, %32, %33, 1, 1, 1, 0, 1;"
    : "+f"(d[0]), "+f"(d[1]), "+f"(d[2]), "+f"(d[3]), "+f"(d[4]), "+f"(d[5]), "+f"(d[6]), "+f"(d[7]), "+f"(d[8]), "+f"(d[9]), "+f"(d[10]), "+f"(d[11]), "+f"(d[12]), "+f"(d[13]), "+f"(d[14]), "+f"(d[15]), "+f"(d[16]), "+f"(d[17]), "+f"(d[18]), "+f"(d[19]), "+f"(d[20]), "+f"(d[21]), "+f"(d[22]), "+f"(d[23]), "+f"(d[24]), "+f"(d[25]), "+f"(d[26]), "+f"(d[27]), "+f"(d[28]), "+f"(d[29]), "+f"(d[30]), "+f"(d[31])
    : "l"(da), "l"(db));
}
DEVI void wgmma_ss_n128(float (&d)[64], uint64_t da, uint64_t db) {
  asm volatile("wgmma.mma_async.sync.aligned.m64n128k16.f32.bf16.bf16 {%0, %1, %2, %3, %4, %5, %6, %7, %8, %9, %10, %11, %12, %13, %14, %15, %16, %17, %18, %19, %20, %21, %22, %23, %24, %25, %26, %27, %28, %29, %30, %31, %32, %33, %34, %35, %36, %37, %38, %39, %40, %41, %42, %43, %44, %45, %46, %47, %48, %49, %50, %51, %52, %53, %54, %55, %56, %57, %58, %59, %60, %61, %62, %63}, %64, %65, 1, 1, 1, 0, 1;"
    : "+f"(d[0]), "+f"(d[1]), "+f"(d[2]), "+f"(d[3]), "+f"(d[4]), "+f"(d[5]), "+f"(d[6]), "+f"(d[7]), "+f"(d[8]), "+f"(d[9]), "+f"(d[10]), "+f"(d[11]), "+f"(d[12]), "+f"(d[13]), "+f"(d[14]), "+f"(d[15]), "+f"(d[16]), "+f"(d[17]), "+f"(d[18]), "+f"(d[19]), "+f"(d[20]), "+f"(d[21]), "+f"(d[22]), "+f"(d[23]), "+f"(d[24]), "+f"(d[25]), "+f"(d[26]), "+f"(d[27]), "+f"(d[28]), "+f"(d[29]), "+f"(d[30]), "+f"(d[31]), "+f"(d[32]), "+f"(d[33]), "+f"(d[34]), "+f"(d[35]), "+f"(d[36]), "+f"(d[37]), "+f"(d[38]), "+f"(d[39]), "+f"(d[40]), "+f"(d[41]), "+f"(d[42]), "+f"(d[43]), "+f"(d[44]), "+f"(d[45]), "+f"(d[46]), "+f"(d[47]), "+f"(d[48]), "+f"(d[49]), "+f"(d[50]), "+f"(d[51]), "+f"(d[52]), "+f"(d[53]), "+f"(d[54]), "+f"(d[55]), "+f"(d[56]), "+f"(d[57]), "+f"(d[58]), "+f"(d[59]), "+f"(d[60]), "+f"(d[61]), "+f"(d[62]), "+f"(d[63])
    : "l"(da), "l"(db));
}
DEVI void wgmma_qk64(float (&d)[32], uint32_t a0, uint32_t a1, uint32_t a2, uint32_t a3, uint64_t db) {
  asm volatile("wgmma.mma_async.sync.aligned.m64n64k16.f32.bf16.bf16 {%0, %1, %2, %3, %4, %5, %6, %7, %8, %9, %10, %11, %12, %13, %14, %15, %16, %17, %18, %19, %20, %21, %22, %23, %24, %25, %26, %27, %28, %29, %30, %31}, {%32, %33, %34, %35}, %36, 0, 1, 1, 0;"
    : "=f"(d[0]), "=f"(d[1]), "=f"(d[2]), "=f"(d[3]), "=f"(d[4]), "=f"(d[5]), "=f"(d[6]), "=f"(d[7]), "=f"(d[8]), "=f"(d[9]), "=f"(d[10]), "=f"(d[11]), "=f"(d[12]), "=f"(d[13]), "=f"(d[14]), "=f"(d[15]), "=f"(d[16]), "=f"(d[17]), "=f"(d[18]), "=f"(d[19]), "=f"(d[20]), "=f"(d[21]), "=f"(d[22]), "=f"(d[23]), "=f"(d[24]), "=f"(d[25]), "=f"(d[26]), "=f"(d[27]), "=f"(d[28]), "=f"(d[29]), "=f"(d[30]), "=f"(d[31])
    : "r"(a0), "r"(a1), "r"(a2), "r"(a3), "l"(db));
}
DEVI void wgmma_pv(float (&d)[8], uint32_t a0, uint32_t a1, uint32_t a2, uint32_t a3, uint64_t db) {
  asm volatile("wgmma.mma_async.sync.aligned.m64n16k16.f32.bf16.bf16 {%0, %1, %2, %3, %4, %5, %6, %7}, {%8, %9, %10, %11}, %12, 1, 1, 1, 1;"
    : "+f"(d[0]), "+f"(d[1]), "+f"(d[2]), "+f"(d[3]), "+f"(d[4]), "+f"(d[5]), "+f"(d[6]), "+f"(d[7])
    : "r"(a0), "r"(a1), "r"(a2), "r"(a3), "l"(db));
}
DEVI void wgmma_pv0(float (&d)[8], uint32_t a0, uint32_t a1, uint32_t a2, uint32_t a3, uint64_t db) {
  asm volatile("wgmma.mma_async.sync.aligned.m64n16k16.f32.bf16.bf16 {%0, %1, %2, %3, %4, %5, %6, %7}, {%8, %9, %10, %11}, %12, 0, 1, 1, 1;"
    : "=f"(d[0]), "=f"(d[1]), "=f"(d[2]), "=f"(d[3]), "=f"(d[4]), "=f"(d[5]), "=f"(d[6]), "=f"(d[7])
    : "r"(a0), "r"(a1), "r"(a2), "r"(a3), "l"(db));
}


template <int N> struct Acc { float a[64]; float b[(N - 128) / 2]; DEVI float& operator[](int i) { return i < 64 ? a[i] : b[i - 64]; } };
template <> struct Acc<128> { float a[64]; DEVI float& operator[](int i) { return a[i]; } };
template <int N> DEVI void wgmma_ss(Acc<N>& d, uint64_t da, uint64_t db) {
  wgmma_ss_n128(d.a, da, db);
  if constexpr (N == 192) wgmma_ss_n64(d.b, da, db + 256);
  if constexpr (N == 256) wgmma_ss_n128(d.b, da, db + 256);
}

DEVI int oh_chunk(inDEVI int oh_chunk(int j, int i, int& need) {
  if (i >= 3 && i < 5) { const int e = (j & 1) * 2 + i - 3; need = 16 + 2 * e; return 24 + e; }
  if (i >= 5) i -= 2;
  int o, r;
  if (i >= 12) { o = (j + 5) & 7; r = i - 11; }
  else { const int g = i / 3; o = (j + 2 * g) & 7; r = i - 3 * g; }
  need = o;
  return 3 * o + r;
}

 int k = i - 5;
    r = k < 3 ? 0 : k < 5 ? 1 : 2; g = k < 3 ? 1 + k : 1 + ((k - 3) & 1);
  }
  return 3 * ((j + 2 * g) & 7) + r;
}

DEVI int a_slot(int e, int) { return 1 + (e & 3); }

struct Ctx {
  uint32_t sbase, bars, peer, t0, a16, b16;
  int wg, lane;
  int ai, bi; uint32_t aph, bph;
  int brem, ae;
  int pa, pb;
};

DEVI void release_prev(Ctx& c) {
  if (c.pb >= 0) {
    if (c.lane == 0) mbar_arrive(c.bars + 8 * (BAR_EMPTYB + c.pb));
    if (c.lane == 1) mbar_arrive_cluster(c.bars + 8 * (BAR_EMPTYB + c.pb), c.peer);
  }
  if (c.pa >= 0 && c.lane == 2) mbar_arrive(c.bars + 8 * (BAR_EMPTYA + c.pa));
}

DEVI void gemm_wait(Ctx& c) {
  asm volatile("{ .reg .pred p, q; .reg .u32 c;\n"
               "mbarrier.try_wait.parity.shared::cta.b64 p, [%0], %1;\n"
               "mbarrier.try_wait.parity.shared::cta.b64 q, [%2], %3;\n"
               "and.pred p, p, q;\n"
               "@p bra DONE_%=;\n"
               "WAIT_%=:\n"
               "mbarrier.try_wait.parity.shared::cta.b64 p, [%0], %1, %6;\n"
               "mbarrier.try_wait.parity.shared::cta.b64 q, [%2], %3, %6;\n"
               "and.pred p, p, q;\n"
               "@p bra DONE_%=;\n"
               "mov.u32 c, %%clock; sub.u32 c, c, %4; setp.lt.u32 p, c, %5;\n"
               "@p bra WAIT_%=;\n"
               "DONE_%=: }" ::"r"(c.bars + 8 * (BAR_FULLA + c.ai)), "r"((c.aph >> c.ai) & 1), "r"(c.bars + 8 * (BAR_FULLB + c.bi)), "r"(c.bph), "r"(c.t0),
               "n"(TIMEOUT), "r"(WAIT_HINT_NS) : "memory");
}
template <int N, bool SHALLOW>
DEVI void gemm_group(Acc<N>& acc, Ctx& c, int g, int& npa, int& npb) {
  const uint32_t a16 = c.a16 + c.ai * (SLOT >> 4);
  const uint32_t b16 = c.b16 + c.bi * (SLOT >> 4);
  bool adv;
  if constexpr (N >= 192) {
    const uint32_t a2 = a16 + (g & 1) * 4;
    wgmma_ss<N>(acc, desc_sw128<16>(a2), desc_sw128<2048>(b16));
    if (SHALLOW) { wgmma_commit(); wgmma_wait<SHW>(); }
    wgmma_ss<N>(acc, desc_sw128<16>(a2 + 2), desc_sw128<2048>(b16 + 512));
    adv = g & 1;
  } else {
#pragma unroll
    for (int s = 0; s < 4; s++) {
      wgmma_ss<N>(acc, desc_sw128<16>(a16 + s * 2), desc_sw128<4096>(b16 + (s >> 1) * 512 + (s & 1) * 128));
      if (SHALLOW && s < 3 && (SHG == 1 || s == 1)) { wgmma_commit(); wgmma_wait<SHW>(); }
    }
    adv = true;
  }
  wgmma_commit();
  npb = c.brem > 0 ? c.bi : -1;
  c.brem--;
  if (++c.bi == NB) { c.bi = 0; c.bph ^= 1; }
  npa = -1;
  if (adv) { npa = c.ai; c.aph ^= 1u << c.ai; c.ae++; c.ai = 1 + (c.ae & 3); }
}

template <int N, bool SHALLOW = false>
DEVI void bare_groups(Acc<N>& acc, Ctx& c, int g0, int g1) {
  for (int g = g0; g < g1; g++) {
    int npa, npb;
#ifdef TRACE3
    { const uint32_t sbase = c.sbase, t0 = c.t0;
      if (c.brem > 30 && threadIdx.x == 0 && g < 6) { mbar_wait(c.bars + 8 * (BAR_FULLA + c.ai), (c.aph >> c.ai) & 1, c.t0); TR(40 + g); } }
#endif
    gemm_wait(c);
#ifdef TRACE3
    { const uint32_t sbase = c.sbase, t0 = c.t0; if (c.brem > 30 && threadIdx.x == 0 && g < 8) TR(24 + g); }
#endif
    wgmma_fence();
    gemm_group<N, SHALLOW>(acc, c, g, npa, npb);
    wgmma_wait<SHALLOW ? SHW : 1>();
    release_prev(c);
    c.pa = npa; c.pb = npb;
  }
}
DEVI void drain(Ctx& c) {
  wgmma_wait<0>();
  release_prev(c);
  c.pa = c.pb = -1;
}

constexpr float SC = 0.25f * 1.4426950408889634f;

#define ONCE _Pragma("unroll 1") for (unsigned once_ = 0; once_ < gridDim.y; once_++)

struct Gate { float g0, g1; };

DEVI void kill32(float (&S)[32]) {
#pragma unroll
  for (int i = 0; i < 32; i++) S[i] = __int_as_float(0xff800000);
}
DEVI void row_max(const float (&S)[32], float& x0, float& x1) {
  float y0 = S[1], y1 = S[3];
  x0 = fmaxf(x0, S[0]); x1 = fmaxf(x1, S[2]);
#pragma unroll
  for (int n = 1; n < 8; n++) {
    x0 = fmaxf(x0, S[4 * n]); y0 = fmaxf(y0, S[4 * n + 1]); x1 = fmaxf(x1, S[4 * n + 2]); y1 = fmaxf(y1, S[4 * n + 3]);
  }
  x0 = fmaxf(x0, y0); x1 = fmaxf(x1, y1);
}
DEVI void quad_max(float& x0, float& x1) {
  x0 = fmaxf(x0, __shfl_xor_sync(0xffffffffu, x0, 1)); x1 = fmaxf(x1, __shfl_xor_sync(0xffffffffu, x1, 1));
  x0 = fmaxf(x0, __shfl_xor_sync(0xffffffffu, x0, 2)); x1 = fmaxf(x1, __shfl_xor_sync(0xffffffffu, x1, 2));
}
DEVI void exp32(const float (&S)[32], float (&E)[32], float n0, float n1, float (&l)[4]) {
#pragma unroll
  for (int i = 0; i < 32; i++) { E[i] = ex2(fmaf(S[i], SC, (i & 2) ? n1 : n0)); l[i & 3] += E[i]; }
}
DEVI void pack32(const float (&E)[32], uint32_t (&P)[16]) {
#pragma unroll
  for (int i = 0; i < 16; i++) P[i] = pack_bf16(E[2 * i], E[2 * i + 1]);
}
template <bool FIRST> DEVI void pv4(float (&O)[8], const uint32_t (&P)[16], uint32_t v16) {
  if (FIRST) wgmma_pv0(O, P[0], P[1], P[2], P[3], desc_sw64(v16)); else wgmma_pv(O, P[0], P[1], P[2], P[3], desc_sw64(v16));
#pragma unroll
  for (int k = 1; k < 4; k++) wgmma_pv(O, P[4 * k], P[4 * k + 1], P[4 * k + 2], P[4 * k + 3], desc_sw64(v16 + k * 64));
}
DEVI bool wg_any(int wg, bool v) {
  uint32_t r;
  if (wg == 0) asm volatile("{ .reg .pred p, q; setp.ne.u32 p, %1, 0; bar.red.or.pred q, 4, 128, p; selp.u32 %0, 1, 0, q; }" : "=r"(r) : "r"((uint32_t)v) : "memory");
  else asm volatile("{ .reg .pred p, q; setp.ne.u32 p, %1, 0; bar.red.or.pred q, 5, 128, p; selp.u32 %0, 1, 0, q; }" : "=r"(r) : "r"((uint32_t)v) : "memory");
  return r != 0;
}
DEVI void get_gate(Gate& g, uint32_t sbase, int row16, int lane, uint32_t t0) {
  mbar_wait(sbase + OFF_BAR + 8 * BAR_GIN, 0, t0);
  const uint32_t a = sbase + OFF_GIN + (row16 * 16 + (lane >> 2)) * 4;
  asm volatile("ld.shared.f32 %0, [%1];" : "=f"(g.g0) : "r"(a) : "memory");
  asm volatile("ld.shared.f32 %0, [%1];" : "=f"(g.g1) : "r"(a + 32) : "memory");
}

DEVI void attention(uint32_t sbase, int aw, int wi, int lane, int rb, uint32_t t0) {
  const uint32_t bars = sbase + OFF_BAR;
  const uint32_t kvb = ((sbase & 0x3FFFF) + OFF_KV + aw * 4096) >> 4;
  const int cmin = 4 - 2 * rb - aw;
  const int rowc = wi * 16 + (lane >> 2) - (lane & 3) * 2;
  const uint32_t qst = sbase + OFF_A + aw * 8192;
  const float NINF = __int_as_float(0xff800000);
  const int tlo = max(cmin, 1);
#pragma unroll 1
  for (int h = 0; h < 4; h++) {
    const uint32_t kb = kvb + ((h & 1) ^ 1) * (KVBUF >> 4);
    const uint4 q = lds128(qst + h * 2048 + (wi * 32 + lane) * 16);
    float O[8], l0, l1;
    uint32_t nm;
    asm volatile("ld.shared.u32 %0, [%1];" : "=r"(nm) : "r"(sbase + OFF_NM + ((aw * 4 + wi) * 32 + (lane & 28) + h) * 4) : "memory");
    float n0 = __uint_as_float(nm << 16), n1 = __uint_as_float(nm & 0xffff0000u);
    mbar_wait(bars + 8 * (BAR_KVFULL + (h & 1)), h >> 1, t0);
#ifdef SKEW
    if (h == 0 && aw == 1) { const uint32_t ts = clk32(); while (clk32() - ts < SKEW) {} }
#endif
#pragma unroll 1
    for (int attempt = 0; attempt < 2; attempt++) {
      float l[4] = {0.f, 0.f, 0.f, 0.f};
      uint32_t P[16];
      {
        float S[32], F[32];
        wgmma_fence();
        wgmma_qk64(S, q.x, q.y, q.z, q.w, desc_sw64(kb + 4 * 256));
        wgmma_qk64(F, q.x, q.y, q.z, q.w, desc_sw64(kb));
        wgmma_commit();
        wgmma_wait<0>();
        for (int r = 0; r < (cmin > 0 ? 1 : 0); r++) kill32(F);
        float M[32];
#pragma unroll
        for (int i = 0; i < 32; i++) M[i] = ((i >> 2) * 8 + (i & 1) > rowc + (i & 2) * 4) ? F[i] : S[i];
        for (int r = 0; r < attempt; r++) {
          row_max(M, n0, n1);
          quad_max(n0, n1);
          n0 *= -SC; n1 *= -SC;
        }
        exp32(M, M, n0, n1, l);
        pack32(M, P);
        uint32_t PF[16];
#pragma unroll
        for (int i = 0; i < 16; i++) {
          const int col = (i >> 1) * 8, r = rowc + (i & 1) * 8;
          const uint32_t m = (col > r ? 0xFFFFu : 0u) | (col + 1 > r ? 0xFFFF0000u : 0u);
          PF[i] = P[i] & m; P[i] &= ~m;
        }
        wgmma_fence();
        pv4<true>(O, PF, kb + 2);
        wgmma_commit();
#ifndef NOPFW
        wgmma_wait<0>();
#endif
      }
      int t = 3;
#pragma unroll 1
      for (; t >= tlo; t--) {
        float S[32];
        wgmma_fence();
        wgmma_qk64(S, q.x, q.y, q.z, q.w, desc_sw64(kb + t * 256));
        wgmma_commit();
        pv4<false>(O, P, kb + (t + 1) * 256 + 2);
        wgmma_commit();
        wgmma_wait<1>();
        ONCE { exp32(S, S, n0, n1, l); }
        wgmma_wait<0>();
        pack32(S, P);
      }
      wgmma_fence();
      pv4<false>(O, P, kb + (t + 1) * 256 + 2);
      wgmma_commit();
      l0 = l[0] + l[1]; l1 = l[2] + l[3];
      l0 += __shfl_xor_sync(0xffffffffu, l0, 1); l1 += __shfl_xor_sync(0xffffffffu, l1, 1);
      l0 += __shfl_xor_sync(0xffffffffu, l0, 2); l1 += __shfl_xor_sync(0xffffffffu, l1, 2);
      const bool redo = wg_any(aw, attempt == 0 && !(l0 > 1e-6f && l0 < 1e18f && l1 > 1e-6f && l1 < 1e18f));
      wgmma_wait<0>();
      if (!redo) break;
      n0 = NINF; n1 = NINF;
#pragma unroll 1
      for (int u = 3; u >= tlo; u--) {
        float S[32];
        wgmma_fence();
        wgmma_qk64(S, q.x, q.y, q.z, q.w, desc_sw64(kb + u * 256));
        wgmma_commit();
        wgmma_wait<0>();
        row_max(S, n0, n1);
      }
    }
    if (lane == 0) mbar_arrive(bars + 8 * (BAR_KVEMPTY + (h & 1)));
    Gate g;
    get_gate(g, sbase, aw * 4 + wi, lane, t0);
    const float c0 = __fdividef(g.g0, l0), c1 = __fdividef(g.g1, l1);
    const int mi = lane >> 3;
    const int srow = wi * 16 + (lane & 7) + 8 * (mi & 1);
    stsm_x4(qst + h * 2048 + srow * 32 + (mi >> 1) * 16, pack_bf16(O[0] * c0, O[1] * c0), pack_bf16(O[2] * c1, O[3] * c1),
            pack_bf16(O[4] * c0, O[5] * c0), pack_bf16(O[6] * c1, O[7] * c1));
    fence_async_smem();
    __syncwarp();
    if (lane == 0) mbar_arrive(bars + 8 * (BAR_OST + h));
  }
}

template <int CH, int N>
DEVI void store_h_chunk(Acc<N>& acc, uint32_t base  , int lane, float s0, float s1) {
  const int mi = lane >> 3;
#pragma unroll
  for (int tp = 0; tp < 4; tp++) {
    const int t = CH * 8 + tp * 2;
    const uint32_t r0 = pack_bf16(fmaxf(acc[4 * t + 0], 0.f) * s0, fmaxf(acc[4 * t + 1], 0.f) * s0);
    const uint32_t r1 = pack_bf16(fmaxf(acc[4 * t + 2], 0.f) * s1, fmaxf(acc[4 * t + 3], 0.f) * s1);
    const uint32_t r2 = pack_bf16(fmaxf(acc[4 * t + 4], 0.f) * s0, fmaxf(acc[4 * t + 5], 0.f) * s0);
    const uint32_t r3 = pack_bf16(fmaxf(acc[4 * t + 6], 0.f) * s1, fmaxf(acc[4 * t + 7], 0.f) * s1);
    stsm_x4(base + (((tp * 2 + (mi >> 1)) ^ (lane & 7)) << 4), r0, r1, r2, r3);
  }
}

template <int N>
DEVI void phase_q(Ctx& c, int warp) {
  Acc<N> acc;
#pragma unroll
  for (int i = 0; i < N / 2; i++) acc[i] = 0.f;
  bare_groups<N>(acc, c, 0, 16);
  drain(c);
  const int lane = c.lane, mi = lane >> 3;
  const int row = warp * 16 + (lane & 7) + 8 * (mi & 1);
  const int sw = (row >> 1) & 3;
#pragma unroll
  for (int hh = 0; hh < 4; hh++) {
    const uint32_t base = c.sbase + OFF_KV + ((hh + 3) & 3) * 8192 + row * 64;
#pragma unroll
    for (int kv = 0; kv < 2; kv++) {
      const int t = 8 + kv * 8 + 2 * hh;
      stsm_x4(base + (((kv * 2 + (mi >> 1)) ^ sw) << 4),
              pack_bf16(acc[4 * t + 0], acc[4 * t + 1]), pack_bf16(acc[4 * t + 2], acc[4 * t + 3]),
              pack_bf16(acc[4 * t + 4], acc[4 * t + 5]), pack_bf16(acc[4 * t + 6], acc[4 * t + 7]));
    }
    if (hh == 0) {
      fence_async_smem();
      __syncwarp();
      if (lane == 0) mbar_arrive(c.bars + 8 * BAR_KVOK);
    }
  }
  fence_async_smem();
  __syncwarp();
  if (lane == 0) mbar_arrive(c.bars + 8 * BAR_STG);
#pragma unroll
  for (int hh = 0; hh < 4; hh++)
    sts128(c.sbase + OFF_A + c.wg * 8192 + hh * 2048 + ((warp & 3) * 32 + lane) * 16,
           pack_bf16(acc[8 * hh], acc[8 * hh + 1]), pack_bf16(acc[8 * hh + 2], acc[8 * hh + 3]),
           pack_bf16(acc[8 * hh + 4], acc[8 * hh + 5]), pack_bf16(acc[8 * hh + 6], acc[8 * hh + 7]));
#pragma unroll
  for (int hh = 0; hh < 4; hh++) {
    const int q = 8 * hh, k = 32 + 8 * hh;
    float d0 = acc[q] * acc[k] + acc[q + 1] * acc[k + 1] + acc[q + 4] * acc[k + 4] + acc[q + 5] * acc[k + 5];
    float d1 = acc[q + 2] * acc[k + 2] + acc[q + 3] * acc[k + 3] + acc[q + 6] * acc[k + 6] + acc[q + 7] * acc[k + 7];
    d0 += __shfl_xor_sync(0xffffffffu, d0, 1); d1 += __shfl_xor_sync(0xffffffffu, d1, 1);
    d0 += __shfl_xor_sync(0xffffffffu, d0, 2); d1 += __shfl_xor_sync(0xffffffffu, d1, 2);
    if ((lane & 3) == hh)
      asm volatile("st.shared.u32 [%0], %1;" ::"r"(c.sbase + OFF_NM + (warp * 32 + lane) * 4), "r"(pack_bf16(-d0 * SC, -d1 * SC)) : "memory");
  }
  __syncwarp();
  if (lane == 0) mbar_arrive(c.bars + 8 * (BAR_QRDY + c.wg));
  if constexpr (N == 256) {
    Gate g;
    get_gate(g, c.sbase, warp, lane, c.t0);
    mbar_wait(c.bars + 8 * (BAR_FULLA + c.ai), (c.aph >> c.ai) & 1, c.t0);
    store_h_chunk<3>(acc, c.sbase + OFF_A + c.ai * SLOT + row * 128, lane, 1.f - g.g0, 1.f - g.g1);
    fence_async_smem();
    __syncwarp();
    if (lane == 0) { mbar_arrive(c.bars + 8 * BAR_STE); mbar_arrive(c.bars + 8 * (BAR_EMPTYA + c.ai)); }
    c.aph ^= 1u << c.ai; c.ae++; c.ai = a_slot(c.ae, 0);
  }
}

DEVI void first_loads(const Params& P, uint32_t sbase, int e, int j, int rb) {
  const uint32_t bars = sbase + OFF_BAR, fb = bars + 8 * (BAR_FULLB + e), fa = bars + 8 * (BAR_FULLA + 1 + e);
  mbar_expect_tx(fa, 16384);
  mbar_expect_tx(fb, (j & 1) ? 12288 : 16384);
  if (e == 0) tma_load_2d(sbase + OFF_A + SLOT, &P.tmX, 0, rb * 128, fa);
#pragma unroll
  for (int r = 0; r < 2; r++) {
    tma_load_3d(sbase + OFF_B + e * SLOT + r * 8192, &P.tmWqkv, 64 * j, e * 32 + r * 16, 0, fb);
    if (!(j & 1)) tma_load_3d(sbase + OFF_B + e * SLOT + r * 8192 + 6144, &P.tmW1a, 0, e * 32 + r * 16, 24 + (j >> 1), fb);
  }
  if (e == 1) tma_load_2d(sbase + OFF_A + 2 * SLOT, &P.tmX, 64, rb * 128, fa);
}

__global__ void __cluster_dims__(2, 1, 1) __launch_bounds__(640, 1) fused_kernel(const __grid_constant__ Params P) {
  extern __shared__ __align__(1024) uint8_t smem_raw[];
  const uint32_t sbase = smem_u32(smem_raw);
  const uint32_t bars = sbase + OFF_BAR;
  const int tid = threadIdx.x, warp = tid >> 5, lane = tid & 31;
  const uint32_t rank = blockIdx.x & 1, peer = rank ^ 1;
  const int j = (blockIdx.x >> 1) & 7, rb = ((blockIdx.x >> 4) << 1) | rank;
  const uint32_t t0 = clk32();
#ifdef TRACE
  uint32_t gt0; asm volatile("mov.u32 %0, %%globaltimer_lo;" : "=r"(gt0));
#endif

  const int typeB = j & 1;
  if (tid == 544) {
    for (int s = 0; s < NA2; s++) mbar_init(bars + 8 * (BAR_FULLA + s), 1);
    for (int s = 0; s < NB; s++) mbar_init(bars + 8 * (BAR_FULLB + s), 1);
    fence_async_smem();
  } else if (tid < 8) {
    asm volatile("prefetch.tensormap [%0];" ::"l"(&P.tmX + tid) : "memory");
  } else if (tid == 512) {
    for (int s = 0; s < NA2; s++) mbar_init(bars + 8 * (BAR_EMPTYA + s), 9);
    for (int s = 0; s < NB; s++) mbar_init(bars + 8 * (BAR_EMPTYB + s), 16);
  } else if (tid == 576) {
    for (int s = 0; s < 2; s++) { mbar_init(bars + 8 * (BAR_KVFULL + s), 1); mbar_init(bars + 8 * (BAR_KVEMPTY + s), 8); mbar_init(bars + 8 * (BAR_OST + s), 8); mbar_init(bars + 8 * (BAR_OST + 2 + s), 8); mbar_init(bars + 8 * (BAR_QRDY + s), 4); }
    mbar_init(bars + 8 * BAR_STG, 8); mbar_init(bars + 8 * BAR_STE, 8); mbar_init(bars + 8 * BAR_KVOK, 8);
    mbar_init(bars + 8 * BAR_PIN, 1); mbar_init(bars + 8 * BAR_PFREE, 8); mbar_init(bars + 8 * BAR_GIN, 1);
  }
  if (tid >= 512 && lane == 0) asm volatile("fence.mbarrier_init.release.cluster;" ::: "memory");
#ifdef TRACE
  if (tid < 64) asm volatile("st.shared.u32 [%0], %1;" ::"r"(sbase + OFF_BAR + 640 + 4 * tid), "r"(0));
#endif
  const unsigned ep1 = ld_relaxed(&g_epoch) + 1;
  __syncwarp();
  cluster_arrive();
  if (tid == 544) { first_loads(P, sbase, 0, j, rb); first_loads(P, sbase, 1, j, rb); }
#if PF0 == 1
  if (tid == 544) { l2_prefetch(P.x + (size_t)(rb * 128 + j * 16) * DM, 16384); l2_prefetch((const uint8_t*)P.wqkv + blockIdx.x * 12288, 12288); }
#elif PF0 == 2
  if (tid == 320) { l2_prefetch(P.x + (size_t)(rb * 128 + j * 16) * DM, 16384); l2_prefetch((const uint8_t*)P.wqkv + blockIdx.x * 12288, 12288); }
#endif
  __syncwarp();

  const int on = 12 + 4 * typeB;

  if (warp < 8) {
    asm volatile("setmaxnreg.inc.sync.aligned.u32 160;");
    cluster_wait();
    const int wg = __shfl_sync(0xffffffffu, warp >> 2, 0);
    Ctx c{sbase, bars, peer, t0, ((sbase & 0x3FFFF) + OFF_A + wg * 8192) >> 4, ((sbase & 0x3FFFF) + OFF_B) >> 4, wg, lane, 1, 0, 0u, 0u, 32 + on + 4 - NB, 0, -1, -1};
    if (tid == 0) TR(0);
    if (typeB) phase_q<192>(c, warp);
    else phase_q<256>(c, warp);
    asm volatile("setmaxnreg.dec.sync.aligned.u32 128;");
    if (tid == 0) TR(2);
    {
      Acc<192> acc;
#pragma unroll
      for (int i = 0; i < 96; i++) acc[i] = 0.f;
      bare_groups<192>(acc, c, 0, typeB ? SHSB : SHS);
      bare_groups<192, SH>(acc, c, typeB ? SHSB : SHS, 16);
      Gate at;
      get_gate(at, sbase, warp, lane, t0);
      drain(c);
      if (tid == 0) TR(1);
      const uint32_t rowoff = (warp * 16 + (lane & 7) + 8 * ((lane >> 3) & 1)) * 128;
      const float s0 = 1.f - at.g0, s1 = 1.f - at.g1;
      const int e0 = c.ai, e1 = a_slot(c.ae + 1, 0), e2 = a_slot(c.ae + 2, 0);
      mbar_wait(bars + 8 * (BAR_FULLA + e0), (c.aph >> e0) & 1, t0);
      store_h_chunk<0>(acc, sbase + OFF_A + e0 * SLOT + rowoff, lane, s0, s1);
      mbar_wait(bars + 8 * (BAR_FULLA + e1), (c.aph >> e1) & 1, t0);
      store_h_chunk<1>(acc, sbase + OFF_A + e1 * SLOT + rowoff, lane, s0, s1);
      mbar_wait(bars + 8 * (BAR_FULLA + e2), (c.aph >> e2) & 1, t0);
      store_h_chunk<2>(acc, sbase + OFF_A + e2 * SLOT + rowoff, lane, s0, s1);
    }
    fence_async_smem();
    wg_bar(wg);
    if (lane == 0) mbar_arrive(bars + 8 * BAR_STG);
    if (tid == 0) TR(4);
    float own[32];
    {
      Acc<128> acc;
#pragma unroll
      for (int i = 0; i < 64; i++) acc[i] = 0.f;
#if TB == 1
      if (typeB) bare_groups<128, false>(acc, c, 0, on); else bare_groups<128, true>(acc, c, 0, on);
#elif TB == 2
      bare_groups<128, true>(acc, c, 0, typeB ? 8 : on);
      bare_groups<128, false>(acc, c, typeB ? 8 : on, on);
#else
      bare_groups<128, SHO>(acc, c, 0, on);
#endif
      drain(c);
      if (tid == 0) TR(5);
      if (lane == 0) mbar_arrive(bars + 8 * BAR_PFREE);
      named_bar<3>(256);
      const uint32_t pst = sbase + OFF_B + ((30 + on) % NB) * SLOT + wg * 8192 + (tid & 127) * 16;
#pragma unroll
      for (int i = 0; i < 4; i++) {
        uint32_t r[4];
#pragma unroll
        for (int k = 0; k < 4; k++) {
          const int idx = 8 * i + 2 * k;
          const float lo = typeB ? acc[idx] : acc[32 + idx], hi = typeB ? acc[idx + 1] : acc[32 + idx + 1];
          r[k] = pack_bf16(lo, hi);
        }
        sts128(pst + i * 2048, r[0], r[1], r[2], r[3]);
      }
#pragma unroll
      for (int i = 0; i < 32; i++) own[i] = typeB ? acc[32 + i] : acc[i];
      fence_async_smem();
      __syncwarp();
      if (lane == 0) mbar_arrive(bars + 8 * BAR_STG);
    }
#pragma unroll 1
    for (int g = 0; g < 8; g++) {
      const uint32_t a16 = c.a16 + c.ai * (SLOT >> 4);
      const uint32_t b16 = c.b16 + c.bi * (SLOT >> 4) + (g & 1) * 512;
      if (g == 6) {
        mbar_wait(bars + 8 * BAR_PIN, 0, t0);
        const uint32_t pin = sbase + OFF_B + ((31 + on) % NB) * SLOT + wg * 8192 + (tid & 127) * 16;
#pragma unroll
        for (int i = 0; i < 4; i++) {
          const uint4 v = lds128(pin + i * 2048);
          const uint32_t r[4] = {v.x, v.y, v.z, v.w};
#pragma unroll
          for (int k = 0; k < 4; k++) { own[8 * i + 2 * k] += __uint_as_float(r[k] << 16); own[8 * i + 2 * k + 1] += __uint_as_float(r[k] & 0xffff0000u); }
        }
        named_bar<3>(256);
        if (tid == 0) TR(7);
      }
      gemm_wait(c);
      wgmma_fence();
#pragma unroll
      for (int s = 0; s < 4; s++) wgmma_ss_n64(own, desc_sw128<16>(a16 + s * 2), desc_sw128<2048>(b16 + s * 128));
      wgmma_commit();
      wgmma_wait<0>();
      if (lane == 2) mbar_arrive(bars + 8 * (BAR_EMPTYA + c.ai));
      c.aph ^= 1u << c.ai;
      c.ae++; c.ai = a_slot(c.ae, 0);
      if (g & 1) { if (++c.bi == NB) { c.bi = 0; c.bph ^= 1; } }
    }
    if (tid == 0) TR(6);
    {
      const uint32_t ob = sbase + OFF_B + ((31 + on) % NB) * SLOT;
      const uint32_t wb = ob + warp * 2048;
      const uint32_t orow = wb + ((lane & 7) + 8 * ((lane >> 3) & 1)) * 128;
#pragma unroll
      for (int i = 0; i < 4; i++)
        stsm_x4(orow + (((i * 2 + (lane >> 4)) ^ (lane & 7)) << 4), pack_bf16(own[8 * i], own[8 * i + 1]), pack_bf16(own[8 * i + 2], own[8 * i + 3]),
                pack_bf16(own[8 * i + 4], own[8 * i + 5]), pack_bf16(own[8 * i + 6], own[8 * i + 7]));
      __syncwarp();
      uint4* o = (uint4*)(P.out + (size_t)(rb * 128 + warp * 16 + (lane >> 3)) * DM + j * 64) + (lane & 7);
#pragma unroll
      for (int i = 0; i < 4; i++) {
        const int r = i * 4 + (lane >> 3);
        o[i * 4 * (DM / 8)] = lds128(wb + r * 128 + (((lane & 7) ^ (r & 7)) << 4));
      }
    }
    if (tid == 0) TR(8);
#ifdef TRACE
    named_bar<3>(256);
    if (tid < 64) { uint32_t v; asm volatile("ld.shared.u32 %0, [%1];" : "=r"(v) : "r"(sbase + OFF_BAR + 640 + 4 * tid));
      if (tid == 16) v = gt0;
      if (tid == 17) asm volatile("mov.u32 %0, %%globaltimer_lo;" : "=r"(v));
      if (tid == 18) v = clk32() - t0;
      g_trace[blockIdx.x * 64 + tid] = v; }
#endif
  } else if (warp < 16) {
    asm volatile("setmaxnreg.dec.sync.aligned.u32 56;");
    cluster_wait();
    const int aw = __shfl_sync(0xffffffffu, (warp >> 2) & 1, 0);
    {
      const int rowg = rb * 128 + j * 16 + (warp - 8) * 2;
      const uint4* gw = (const uint4*)P.gate_w;
      const uint4* xr = (const uint4*)(P.x + (size_t)rowg * DM);
      mbar_wait(bars + 8 * (BAR_FULLB + 1), 0, t0);
      const uint4 w0 = __ldg(gw + lane), w1 = __ldg(gw + 32 + lane);
      const uint4 xa0 = __ldg(xr + lane), xa1 = __ldg(xr + 32 + lane), xb0 = __ldg(xr + 64 + lane), xb1 = __ldg(xr + 96 + lane);
#pragma unroll
      for (int i = 0; i < 4; i++) sts128(sbase + OFF_KV + 32768 + i * 4096 + (tid - 256) * 16, 0u, 0u, 0u, 0u);
      const uint32_t wa[8] = {w0.x, w0.y, w0.z, w0.w, w1.x, w1.y, w1.z, w1.w};
      const uint32_t xa[8] = {xa0.x, xa0.y, xa0.z, xa0.w, xa1.x, xa1.y, xa1.z, xa1.w};
      const uint32_t xb[8] = {xb0.x, xb0.y, xb0.z, xb0.w, xb1.x, xb1.y, xb1.z, xb1.w};
      float za = 0.f, zb = 0.f;
#pragma unroll
      for (int e = 0; e < 8; e++) {
        const float wl = __uint_as_float(wa[e] << 16), wh = __uint_as_float(wa[e] & 0xffff0000u);
        za = fmaf(__uint_as_float(xa[e] << 16), wl, za); za = fmaf(__uint_as_float(xa[e] & 0xffff0000u), wh, za);
        zb = fmaf(__uint_as_float(xb[e] << 16), wl, zb); zb = fmaf(__uint_as_float(xb[e] & 0xffff0000u), wh, zb);
      }
#pragma unroll
      for (int o = 16; o > 0; o >>= 1) { za += __shfl_xor_sync(0xffffffffu, za, o); zb += __shfl_xor_sync(0xffffffffu, zb, o); }
      if (lane < 2) asm volatile("st.shared.f32 [%0], %1;" ::"r"(sbase + OFF_GST + (warp - 8) * 8 + lane * 4), "f"(1.f / (1.f + __expf(-(lane ? zb : za)))) : "memory");
      fence_async_smem();
      named_bar<6>(256);
      if (tid == 256) {
        bulk_store(&g_gate[rb * 128 + j * 16], sbase + OFF_GST, 64);
        bulk_commit(); bulk_wait_all();
        flag_add(&g_flag_g[rb * FS]);
        flag_wait(&g_flag_g[rb * FS], ep1 * 8, t0);
        fence_async_global();
        mbar_expect_tx(bars + 8 * BAR_GIN, 512);
        bulk_load(sbase + OFF_GIN, &g_gate[rb * 128], 512, bars + 8 * BAR_GIN);
        TR(10);
      }
      __syncwarp();
    }
    mbar_wait(bars + 8 * (BAR_QRDY + aw), 0, t0);
    asm volatile("setmaxnreg.inc.sync.aligned.u32 96;");
    attention(sbase, aw, warp & 3, lane, rb, t0);
    if (tid == 256) TR(3);
  } else {
    asm volatile("setmaxnreg.dec.sync.aligned.u32 32;");
    if (warp == 16) {
      __syncwarp();
      cluster_wait();
#ifdef TRACE3
      if (lane == 0) TR(51);
#endif
      if (lane == 0) {
        int bi = 2; uint32_t bph = 1;
        const int nb = 32 + on + 4;
        for (int eb = 2; eb < nb; eb++) {
          if (eb == 4 || eb == 6) {
            const int ea = eb >> 1;
            mbar_expect_tx(bars + 8 * (BAR_FULLA + 1 + ea), 16384);
            tma_load_2d(sbase + OFF_A + (1 + ea) * SLOT, &P.tmX, ea * 64, rb * 128, bars + 8 * (BAR_FULLA + 1 + ea));
          }
          const uint32_t fb = bars + 8 * (BAR_FULLB + bi), dst = sbase + OFF_B + bi * SLOT + rank * 8192;
          mbar_wait(bars + 8 * (BAR_EMPTYB + bi), bph, t0);
          if (eb < 16) {
            mbar_expect_tx(fb, typeB ? 12288 : 16384);
            tma_load_3d_mc(dst, &P.tmWqkv, 64 * j, eb * 32 + rank * 16, 0, fb);
            if (!typeB) tma_load_3d_mc(dst + 6144, &P.tmW1a, 0, eb * 32 + rank * 16, 24 + (j >> 1), fb);
          }
          else if (eb < 32) { mbar_expect_tx(fb, 12288); tma_load_3d_mc(dst, &P.tmW1b, 0, (eb - 16) * 32 + rank * 16, 3 * j, fb); }
          else if (eb < 32 + on) { int ow; const int ch = oh_chunk(j, eb - 32, ow); mbar_expect_tx(fb, 16384); tma_load_3d_mc(dst, &P.tmW2, 0, ch * 64 + rank * 32, (j >> 1) * 2, fb); }
          else { mbar_expect_tx(fb, 16384); tma_load_4d_mc(dst, &P.tmWo, 64 * j, 0, eb - 32 - on, rank * 4, fb); }
#ifdef TRACE3
          if (eb < 6) TR(32 + eb);
#endif
          if (++bi == NB) { bi = 0; bph ^= 1; }
#ifndef NOPF
          if (eb == PFAT) {
            const int b = blockIdx.x;
             int ch = ea & 7, need = -1;
          if (ea >= 16 + on) { need = 8 + ea - 16 - on; ch = 20 + need; }
          else if (ea >= 19) ch = oh_chunk(j, ea - 16, need);
          if (need >= 0 && !((ready >> need) & 1)) {
            const unsigned* fp = need < 8 ? &g_flag_h[rb * 8 * FS] : need < 16 ? &g_flag_o[rb * 8 * FS] : &g_flag_kv[rb * 8 * FS];
            const unsigned tgt = (need & 8) ? ep1 * 4 : (need & 16) ? ep1 * 2 : ep1;
            do {
              unsigned v[8];
#pragma unroll
              for (int i = 0; i < 8; i++) v[i] = ld_relaxed(fp + i * FS);
#pragma unroll
              for (int i = 0; i < 8; i++) if ((int)(v[i] - tgt) >= 0) ready |= 1u << (i + (need & 24));
            } while (!((ready >> need) & 1) && clk32() - t0 < TIMEOUT);
            fence_async_global();
          }
 1; ea < 5; ea++) mbar_arrive(bars + 8 * (BAR_EMPTYA + ea));
        uint32_t aph = 0xE1;
        const int na = 16 + on + 8;
        unsigned ready = 0;
        for (int er = 4; er < na + 1 - typeB; er++) {
          const int ai = a_slot(er, 0);
          const int ea = (typeB || er < 8) ? er : er == 8 ? 16 : er - 1;
          const uint32_t fb = bars + 8 * (BAR_FULLA + ai), dst = sbase + OFF_A + ai * SLOT;
          int ch = ea & 7;
          if (ea >= 19) {
            ch = ea >= 16 + on ? 12 - on + ea : oh_chunk(j, ea - 16);
            while (!((ready >> ch) & 1) && clk32() - t0 < TIMEOUT) {
              const unsigned* fp = ch < 24 ? &g_flag_h[rb * 8 * FS] : ch < 28 ? &g_flag_e[rb * 8 * FS] : &g_flag_o[rb * 8 * FS];
              unsigned v[8];
#pragma unroll
              for (int i = 0; i < 8; i++) v[i] = ld_relaxed(fp + i * FS);
#pragma unroll
              for (int i = 0; i < 8; i++) {
                if (ch < 24) ready |= (uint64_t)((1u << min(max((int)(v[i] - (ep1 - 1) * 3), 0), 3)) - 1) << (3 * i);
                else if (ch < 28) { if (!(i & 1) && (int)(v[i] - ep1) >= 0) ready |= 1ull << (24 + (i >> 1)); }
                else if ((int)(v[i] - ep1 * 4) >= 0) ready |= 1ull << (28 + i);
              }
              fence_async_global();
            }
          }
          mbar_wait(bars + 8 * (BAR_EMPTYA + ai), (aph >> ai) & 1, t0);
          if (ea >= 16 && ea < 19) mbar_arrive(fb);
          else {
            mbar_arrive(bars + 8 * (BAR_EMPTYA + ai));
            mbar_expect_tx(fb, 16384);
            tma_load_2d(dst, ea < 16 ? &P.tmX : &P.tmHO, ch * 64, rb * 128, fb);
          }
#if !defined(TRACE2) && !defined(TRACE3)
          TR(24 + ea);
#endif
          aph ^= 1u << ai;
        }
      }
    } else {
      const int wg = warp - 18;
      cluster_wait();
      if (lane == 0 && wg == 0) {
        const uint32_t stg = bars + 8 * BAR_STG;
        mbar_wait(bars + 8 * BAR_KVOK, 0, t0);
        bulk_store(g_kv + ((size_t)(4 * j) * SEQ + rb * 128) * 64, sbase + OFF_KV + 3 * 8192, 8192);
        bulk_commit(); bulk_wait_all();
        flag_add(&g_flag_kv[(rb * 8 + j) * FS]);
        TR(21);
        mbar_wait(stg, 0, t0);
        for (int hh = 1; hh < 4; hh++) bulk_store(g_kv + ((size_t)(4 * j + hh) * SEQ + rb * 128) * 64, sbase + OFF_KV + (hh - 1) * 8192, 8192);
        if (!typeB) {
          mbar_wait(bars + 8 * BAR_STE, 0, t0);
          tma_store_2d(&P.tmHO, (24 + (j >> 1)) * 64, rb * 128, sbase + OFF_A + a_slot(8, 0) * SLOT);
        }
        bulk_commit(); bulk_wait_all();
        if (!typeB) mbar_arrive(bars + 8 * (BAR_EMPTYA + a_slot(8, 0)));
        flag_add(&g_flag_kv[(rb * 8 + j) * FS]);
        const int hg = 17 - typeB;
        mbar_wait(stg, 1, t0);
        for (int i = 0; i < 3; i++) { tma_store_2d(&P.tmHO, (3 * j + i) * 64, rb * 128, sbase + OFF_A + a_slot(hg + i, 0) * SLOT); bulk_commit(); }
        asm volatile("cp.async.bulk.wait_group.read 2;" ::: "memory");
        mbar_arrive(bars + 8 * (BAR_EMPTYA + a_slot(hg, 0)));
        asm volatile("cp.async.bulk.wait_group.read 1;" ::: "memory");
        mbar_arrive(bars + 8 * (BAR_EMPTYA + a_slot(hg + 1, 0)));
        bulk_wait_all();
        mbar_arrive(bars + 8 * (BAR_EMPTYA + a_slot(hg + 2, 0)));
        flag_add(&g_flag_h[(rb * 8 + j) * FS]);
        TR(22);
        {
          const unsigned old = atomicAdd(&g_done, 1u);
          if (old == gridDim.x - 1) { g_done = 0; *(volatile unsigned*)&g_epoch = ep1; }
        }
        mbar_wait(stg, 0, t0);
        bulk_store(g_part + (size_t)(rb * 8 + (j ^ 1)) * 16384, sbase + OFF_B + ((30 + on) % NB) * SLOT, 16384);
        bulk_commit(); bulk_wait_all();
        flag_add(&g_flag_p[(rb * 8 + (j ^ 1)) * FS]);
        TR(23);
      } else if (lane == 0) {
        const int nblk = rb >= 2 ? 3 : rb + 1;
        const uint32_t kvbytes = nblk * 8192;
        const uint8_t* kvsrc = g_kv + ((size_t)(4 * j) * SEQ + (rb + 1 - nblk) * 128) * 64;
        const uint32_t kvdst = sbase + OFF_KV + (3 - nblk) * 8192;
        mbar_wait(bars + 8 * BAR_GIN, 0, t0);
        for (int hh = 0; hh < 2; hh++) {
          const unsigned* f0 = &g_flag_kv[(rb * 8 + j) * FS];
          const unsigned* f1 = rb >= 1 ? f0 - 8 * FS : f0;
          const unsigned* f2 = rb >= 2 ? f0 - 16 * FS : f0;
          const unsigned tgt = ep1 * 2 - 1 + hh;
          unsigned v0, v1, v2;
          do { v0 = ld_relaxed(f0); v1 = ld_relaxed(f1); v2 = ld_relaxed(f2); }
          while (((int)(v0 - tgt) < 0 || (int)(v1 - tgt) < 0 || (int)(v2 - tgt) < 0) && clk32() - t0 < TIMEOUT);
          if (hh == 0) TR(11);
          fence_async_global();
          mbar_expect_tx(bars + 8 * (BAR_KVFULL + hh), kvbytes);
          bulk_load(kvdst + (hh ^ 1) * KVBUF, kvsrc + (size_t)hh * SEQ * 64, kvbytes, bars + 8 * (BAR_KVFULL + hh));
        }
        for (int hh = 0; hh < 4; hh++) {
          mbar_wait(bars + 8 * (BAR_OST + hh), 0, t0);
          for (int aw = 0; aw < 2; aw++) {
            tma_store_2d(&P.tmOs, DFF + hh * 128 + j * 16, rb * 128 + aw * 64, sbase + OFF_A + aw * 8192 + hh * 2048);
          }
          bulk_commit();
          if (hh < 2) {
            mbar_wait(bars + 8 * (BAR_KVEMPTY + hh), 0, t0);
            mbar_expect_tx(bars + 8 * (BAR_KVFULL + hh), kvbytes);
            bulk_load(kvdst + (hh ^ 1) * KVBUF, kvsrc + (size_t)(hh + 2) * SEQ * 64, kvbytes, bars + 8 * (BAR_KVFULL + hh));
          }
          bulk_wait_all();
          flag_add(&g_flag_o[(rb * 8 + hh * 2 + (j >> 2)) * FS]);
          TR(12 + hh);
        }
      }
    }
  }
}

typedef CUresult (*EncodeFn)(CUtensorMap*, CUtensorMapDataType, cuuint32_t, void*, const cuuint64_t*, const cuuint64_t*, const cuuint32_t*,
                             const cuuint32_t*, CUtensorMapInterleave, CUtensorMapSwizzle, CUtensorMapL2promotion, CUtensorMapFloatOOBfill);

void make_map(EncodeFn enc, CUtensorMap* m, const void* ptr, int rank, const cuuint64_t* dims, const cuuint64_t* strides, const cuuint32_t* box,
              CUtensorMapSwizzle sw = CU_TENSOR_MAP_SWIZZLE_128B) {
  cuuint32_t es[4] = {1, 1, 1, 1};
  enc(m, CU_TENSOR_MAP_DATA_TYPE_BFLOAT16, rank, const_cast<void*>(ptr), dims, strides, box, es, CU_TENSOR_MAP_INTERLEAVE_NONE, sw,
      CU_TENSOR_MAP_L2_PROMOTION_L2_256B, CU_TENSOR_MAP_FLOAT_OOB_FILL_NONE);
}

}

extern "C" void kernel_launch(void* const* d_in, const int* in_sizes, int n_in, void* d_out, int out_size) {
  (void)in_sizes; (void)n_in; (void)out_size;
  static EncodeFn enc = nullptr;
  static void* ho_ptr = nullptr;
  if (!enc) {
    void* fn = nullptr; cudaDriverEntryPointQueryResult st;
    cudaGetDriverEntryPoint("cuTensorMapEncodeTiled", &fn, cudaEnableDefault, &st);
    enc = (EncodeFn)fn;
    cudaGetSymbolAddress(&ho_ptr, g_ho);
    cudaFuncSetAttribute(fused_kernel, cudaFuncAttributeMaxDynamicSharedMemorySize, SMEM_BYTES);
  }
  const __nv_bfloat16* x = (const __nv_bfloat16*)d_in[0];
  const __nv_bfloat16* wqkv = (const __nv_bfloat16*)d_in[1];
  const __nv_bfloat16* wo = (const __nv_bfloat16*)d_in[2];
  const __nv_bfloat16* w1 = (const __nv_bfloat16*)d_in[4];
  const __nv_bfloat16* w2 = (const __nv_bfloat16*)d_in[5];
  const __nv_bfloat16* gate_w = (const __nv_bfloat16*)d_in[6];
  Params P;
  { cuuint64_t d[2] = {DM, SEQ}, s[1] = {DM * 2}; cuuint32_t b[2] = {64, 128}; make_map(enc, &P.tmX, x, 2, d, s, b); }
  { cuuint64_t d[3] = {512, 512, 3}, s[2] = {1536 * 2, 512 * 2}; cuuint32_t b[3] = {64, 16, 3}; make_map(enc, &P.tmWqkv, wqkv, 3, d, s, b); }
  { cuuint64_t d[3] = {64, 512, 28}, s[2] = {DFF * 2, 128}; cuuint32_t b[3] = {64, 16, 1}; make_map(enc, &P.tmW1a, w1, 3, d, s, b);
    b[2] = 3; make_map(enc, &P.tmW1b, w1, 3, d, s, b); }
  { cuuint64_t d[3] = {64, DFF, 8}, s[2] = {DM * 2, 128}; cuuint32_t b[3] = {64, 32, 2}; make_map(enc, &P.tmW2, w2, 3, d, s, b); }
  { cuuint64_t d[4] = {DM, 16, 4, 8}, s[3] = {DM * 2, 16 * DM * 2, 64 * DM * 2}; cuuint32_t b[4] = {64, 16, 1, 4}; make_map(enc, &P.tmWo, wo, 4, d, s, b); }
  { cuuint64_t d[2] = {KHO, SEQ}, s[1] = {KHO * 2}; cuuint32_t b[2] = {64, 128}; make_map(enc, &P.tmHO, ho_ptr, 2, d, s, b);
    b[1] = 64; b[0] = 16; make_map(enc, &P.tmOs, ho_ptr, 2, d, s, b, CU_TENSOR_MAP_SWIZZLE_NONE); }
  P.x = x; P.gate_w = gate_w; P.w1 = w1; P.w2 = w2; P.wo = wo; P.wqkv = wqkv; P.out = (__nv_bfloat16*)d_out;
  fused_kernel<<<128, 640, SMEM_BYTES>>>(P);
}

#ifdef TRACE
extern "C" void dbg_trace(unsigned* host) { cudaDeviceSynchronize(); cudaMemcpyFromSymbol(host, g_trace, sizeof(g_trace)); }
#endif
#ifdef DEBUG_EXPORTS
extern "C" void dbg_copy(int which, void* dst) {
  cudaDeviceSynchronize();
  if (which == 0) cudaMemcpyFromSymbol(dst, g_kv, sizeof(g_kv), 0, cudaMemcpyDeviceToDevice);
  if (which == 2) cudaMemcpyFromSymbol(dst, g_ho, sizeof(g_ho), 0, cudaMemcpyDeviceToDevice);
  if (which == 3) cudaMemcpyFromSymbol(dst, g_gate, sizeof(g_gate), 0, cudaMemcpyDeviceToDevice);
  cudaDeviceSynchronize();
}
#endif
```

```cpp
#include <cuda_runtime.h>
#include <cuda_bf16.h>
#include <cuda.h>
#include <stdint.h>

#define DEVI __device__ __forceinline__

namespace {

constexpr int SEQ = 2048, DM = 512, DFF = 1792, KHO = 2304;
constexpr int NA = 5, NB = 6, SLOT = 16384, KVBUF = 24576;
constexpr int OFF_B = 0, OFF_A = NB * SLOT, OFF_KV = OFF_A + NA * SLOT, OFF_BAR = OFF_KV + 2 * KVBUF;
constexpr int OFF_GST = OFF_BAR + 512;
constexpr int OFF_GIN = OFF_BAR + 1024;
constexpr int OFF_NM = OFF_BAR + 1536;
constexpr int SMEM_BYTES = OFF_BAR + 2560;
constexpr uint32_t TIMEOUT = 1u << 28;
constexpr uint32_t WAIT_HINT_NS = 20000u;
constexpr int PFAT = 8;
#ifndef SHSV
#define SHSV 6
#endif
constexpr int SHS = SHSV;
constexpr int FS = 8;

constexpr int BAR_FULLA = 0, BAR_EMPTYA = BAR_FULLA + NA, BAR_FULLB = BAR_EMPTYA + NA, BAR_EMPTYB = BAR_FULLB + NB,
              BAR_KVFULL = BAR_EMPTYB + NB, BAR_KVEMPTY = BAR_KVFULL + 2, BAR_STG = BAR_KVEMPTY + 2, BAR_PIN = BAR_STG + 1, BAR_STE = BAR_PIN + 1,
              BAR_PFREE = BAR_STE + 1, BAR_GIN = BAR_PFREE + 1, BAR_OST = BAR_GIN + 1, BAR_QRDY = BAR_OST + 4, BAR_KVOK = BAR_QRDY + 2;

__device__ __align__(1024) uint8_t g_kv[32 * SEQ * 64];
__device__ __align__(1024) __nv_bfloat16 g_ho[SEQ * KHO];
__device__ __align__(1024) uint8_t g_part[128 * 16384];
__device__ __align__(128) float g_gate[SEQ];
__device__ unsigned g_flag_kv[128 * FS], g_flag_h[128 * FS], g_flag_o[128 * FS], g_flag_g[16 * FS], g_flag_p[128 * FS], g_flag_e[128 * FS];
__device__ unsigned g_epoch, g_done;
#ifdef TRACE
__device__ unsigned g_trace[128 * 64];
#define TR(i) do { asm volatile("st.shared.u32 [%0], %1;" ::"r"(sbase + OFF_BAR + 640 + 4 * (i)), "r"(clk32() - t0)); } while (0)
#else
#define TR(i) do {} while (0)
#endif

struct Params {
  CUtensorMap tmX, tmWqkv, tmW1a, tmW1b, tmW1c, tmW2, tmWo, tmHO, tmOs;
  const __nv_bfloat16* x;
  const __nv_bfloat16* gate_w;
  const __nv_bfloat16* w1;
  const __nv_bfloat16* w2;
  const __nv_bfloat16* wo;
  __nv_bfloat16* out;
};

DEVI uint32_t smem_u32(const void* p) { return (uint32_t)__cvta_generic_to_shared(p); }
DEVI uint32_t clk32() { uint32_t c; asm volatile("mov.u32 %0, %%clock;" : "=r"(c)); return c; }
DEVI void mbar_init(uint32_t bar, uint32_t cnt) { asm volatile("mbarrier.init.shared::cta.b64 [%0], %1;" ::"r"(bar), "r"(cnt)); }
DEVI void mbar_expect_tx(uint32_t bar, uint32_t bytes) { asm volatile("mbarrier.arrive.expect_tx.shared::cta.b64 _, [%0], %1;" ::"r"(bar), "r"(bytes) : "memory"); }
DEVI void mbar_arrive(uint32_t bar) { asm volatile("mbarrier.arrive.shared::cta.b64 _, [%0];" ::"r"(bar) : "memory"); }
DEVI void mbar_arrive_cluster(uint32_t bar, uint32_t cta) {
  asm volatile("{ .reg .b32 ra; mapa.shared::cluster.u32 ra, %0, %1; mbarrier.arrive.shared::cluster.b64 _, [ra]; }" ::"r"(bar), "r"(cta) : "memory");
}
DEVI void mbar_wait(uint32_t bar, uint32_t parity, uint32_t t0) {
  asm volatile("{ .reg .pred p; .reg .u32 c;\n"
               "mbarrier.try_wait.parity.shared::cta.b64 p, [%0], %1;\n"
               "@p bra DONE_%=;\n"
               "WAIT_%=:\n"
               "mbarrier.try_wait.parity.shared::cta.b64 p, [%0], %1, %4;\n"
               "@p bra DONE_%=;\n"
               "mov.u32 c, %%clock; sub.u32 c, c, %2; setp.lt.u32 p, c, %3;\n"
               "@p bra WAIT_%=;\n"
               "DONE_%=: }" ::"r"(bar), "r"(parity), "r"(t0), "n"(TIMEOUT), "r"(WAIT_HINT_NS) : "memory");
}
DEVI unsigned ld_relaxed(const unsigned* p) { unsigned v; asm volatile("ld.relaxed.gpu.global.u32 %0, [%1];" : "=r"(v) : "l"(p) : "memory"); return v; }
DEVI void flag_wait(const unsigned* p, unsigned target, uint32_t t0) {
  while ((int)(ld_relaxed(p) - target) < 0) { if (clk32() - t0 > TIMEOUT) break; }
}
DEVI void flag_add(unsigned* p) {
  asm volatile("fence.proxy.async.global;\n red.release.gpu.global.add.u32 [%0], 1;" ::"l"(p) : "memory");
}
DEVI void fence_async_smem() { asm volatile("fence.proxy.async.shared::cta;" ::: "memory"); }
DEVI void fence_async_global() {
  asm volatile("fence.acquire.gpu;" ::: "memory");
  asm volatile("fence.proxy.async.global;" ::: "memory");
}
DEVI void tma_load_2d(uint32_t dst, const CUtensorMap* m, int c0, int c1, uint32_t bar) {
  asm volatile("cp.async.bulk.tensor.2d.shared::cluster.global.mbarrier::complete_tx::bytes [%0], [%1, {%3, %4}], [%2];" ::"r"(dst), "l"(m), "r"(bar), "r"(c0), "r"(c1) : "memory");
}
DEVI void tma_load_3d(uint32_t dst, const CUtensorMap* m, int c0, int c1, int c2, uint32_t bar) {
  asm volatile("cp.async.bulk.tensor.3d.shared::cluster.global.mbarrier::complete_tx::bytes [%0], [%1, {%3, %4, %5}], [%2];"
               ::"r"(dst), "l"(m), "r"(bar), "r"(c0), "r"(c1), "r"(c2) : "memory");
}
DEVI void tma_load_3d_mc(uint32_t dst, const CUtensorMap* m, int c0, int c1, int c2, uint32_t bar) {
  asm volatile("cp.async.bulk.tensor.3d.shared::cluster.global.mbarrier::complete_tx::bytes.multicast::cluster [%0], [%1, {%3, %4, %5}], [%2], %6;"
               ::"r"(dst), "l"(m), "r"(bar), "r"(c0), "r"(c1), "r"(c2), "h"((uint16_t)3) : "memory");
}
DEVI void tma_load_4d_mc(uint32_t dst, const CUtensorMap* m, int c0, int c1, int c2, int c3, uint32_t bar) {
  asm volatile("cp.async.bulk.tensor.4d.shared::cluster.global.mbarrier::complete_tx::bytes.multicast::cluster [%0], [%1, {%3, %4, %5, %6}], [%2], %7;"
               ::"r"(dst), "l"(m), "r"(bar), "r"(c0), "r"(c1), "r"(c2), "r"(c3), "h"((uint16_t)3) : "memory");
}
DEVI void tma_store_2d(const CUtensorMap* m, int c0, int c1, uint32_t src) {
  asm volatile("cp.async.bulk.tensor.2d.global.shared::cta.bulk_group [%0, {%1, %2}], [%3];" ::"l"(m), "r"(c0), "r"(c1), "r"(src) : "memory");
}
DEVI void bulk_store(void* dst, uint32_t src, uint32_t bytes) {
  asm volatile("cp.async.bulk.global.shared::cta.bulk_group [%0], [%1], %2;" ::"l"(dst), "r"(src), "r"(bytes) : "memory");
}
DEVI void bulk_load(uint32_t dst, const void* src, uint32_t bytes, uint32_t bar) {
  asm volatile("cp.async.bulk.shared::cluster.global.mbarrier::complete_tx::bytes [%0], [%1], %2, [%3];" ::"r"(dst), "l"(src), "r"(bytes), "r"(bar) : "memory");
}
DEVI void bulk_commit() { asm volatile("cp.async.bulk.commit_group;" ::: "memory"); }
DEVI void bulk_wait_all() { asm volatile("cp.async.bulk.wait_group 0;" ::: "memory"); }
DEVI void l2_prefetch(const void* p, uint32_t bytes) { asm volatile("cp.async.bulk.prefetch.L2.global [%0], %1;" ::"l"(p), "r"(bytes) : "memory"); }
DEVI void cluster_arrive() { asm volatile("barrier.cluster.arrive.relaxed.aligned;" ::: "memory"); }
DEVI void cluster_wait() { asm volatile("barrier.cluster.wait.aligned;" ::: "memory"); }
template <int ID> DEVI void named_bar(int n) { asm volatile("bar.sync %0, %1;" ::"n"(ID), "r"(n) : "memory"); }
DEVI void wg_bar(int wg) { if (wg == 0) named_bar<1>(128); else named_bar<2>(128); }
DEVI void wgmma_fence() { asm volatile("wgmma.fence.sync.aligned;" ::: "memory"); }
DEVI void wgmma_commit() { asm volatile("wgmma.commit_group.sync.aligned;" ::: "memory"); }
template <int N> DEVI void wgmma_wait() { asm volatile("wgmma.wait_group.sync.aligned %0;" ::"n"(N) : "memory"); }
template <uint32_t LBO> DEVI uint64_t desc_sw128(uint32_t a16) {
  return ((uint64_t)(0x40000000u | (1024 >> 4)) << 32) | (a16 + ((LBO >> 4) << 16));
}
DEVI uint64_t desc_sw64(uint32_t a16) {
  return ((uint64_t)(0x80000000u | (512 >> 4)) << 32) | (a16 + ((512 >> 4) << 16));
}
DEVI uint32_t pack_bf16(float lo, float hi) { uint32_t r; asm("cvt.rn.bf16x2.f32 %0, %1, %2;" : "=r"(r) : "f"(hi), "f"(lo)); return r; }
DEVI void stsm_x4(uint32_t addr, uint32_t r0, uint32_t r1, uint32_t r2, uint32_t r3) {
  asm volatile("stmatrix.sync.aligned.m8n8.x4.shared.b16 [%0], {%1, %2, %3, %4};" ::"r"(addr), "r"(r0), "r"(r1), "r"(r2), "r"(r3) : "memory");
}
DEVI void sts128(uint32_t addr, uint32_t r0, uint32_t r1, uint32_t r2, uint32_t r3) {
  asm volatile("st.shared.v4.b32 [%0], {%1, %2, %3, %4};" ::"r"(addr), "r"(r0), "r"(r1), "r"(r2), "r"(r3) : "memory");
}
DEVI uint4 lds128(uint32_t addr) {
  uint4 v; asm volatile("ld.shared.v4.b32 {%0, %1, %2, %3}, [%4];" : "=r"(v.x), "=r"(v.y), "=r"(v.z), "=r"(v.w) : "r"(addr) : "memory"); return v;
}
DEVI float ex2(float x) { float y; asm("ex2.approx.ftz.f32 %0, %1;" : "=f"(y) : "f"(x)); return y; }

DEVI void wgmma_ss_n64(float (&d)[32], uint64_t da, uint64_t db) {
  asm volatile("wgmma.mma_async.sync.aligned.m64n64k16.f32.bf16.bf16 {%0, %1, %2, %3, %4, %5, %6, %7, %8, %9, %10, %11, %12, %13, %14, %15, %16, %17, %18, %19, %20, %21, %22, %23, %24, %25, %26, %27, %28, %29, %30, %31}, %32, %33, 1, 1, 1, 0, 1;"
    : "+f"(d[0]), "+f"(d[1]), "+f"(d[2]), "+f"(d[3]), "+f"(d[4]), "+f"(d[5]), "+f"(d[6]), "+f"(d[7]), "+f"(d[8]), "+f"(d[9]), "+f"(d[10]), "+f"(d[11]), "+f"(d[12]), "+f"(d[13]), "+f"(d[14]), "+f"(d[15]), "+f"(d[16]), "+f"(d[17]), "+f"(d[18]), "+f"(d[19]), "+f"(d[20]), "+f"(d[21]), "+f"(d[22]), "+f"(d[23]), "+f"(d[24]), "+f"(d[25]), "+f"(d[26]), "+f"(d[27]), "+f"(d[28]), "+f"(d[29]), "+f"(d[30]), "+f"(d[31])
    : "l"(da), "l"(db));
}
DEVI void wgmma_ss_n128(float (&d)[64], uint64_t da, uint64_t db) {
  asm volatile("wgmma.mma_async.sync.aligned.m64n128k16.f32.bf16.bf16 {%0, %1, %2, %3, %4, %5, %6, %7, %8, %9, %10, %11, %12, %13, %14, %15, %16, %17, %18, %19, %20, %21, %22, %23, %24, %25, %26, %27, %28, %29, %30, %31, %32, %33, %34, %35, %36, %37, %38, %39, %40, %41, %42, %43, %44, %45, %46, %47, %48, %49, %50, %51, %52, %53, %54, %55, %56, %57, %58, %59, %60, %61, %62, %63}, %64, %65, 1, 1, 1, 0, 1;"
    : "+f"(d[0]), "+f"(d[1]), "+f"(d[2]), "+f"(d[3]), "+f"(d[4]), "+f"(d[5]), "+f"(d[6]), "+f"(d[7]), "+f"(d[8]), "+f"(d[9]), "+f"(d[10]), "+f"(d[11]), "+f"(d[12]), "+f"(d[13]), "+f"(d[14]), "+f"(d[15]), "+f"(d[16]), "+f"(d[17]), "+f"(d[18]), "+f"(d[19]), "+f"(d[20]), "+f"(d[21]), "+f"(d[22]), "+f"(d[23]), "+f"(d[24]), "+f"(d[25]), "+f"(d[26]), "+f"(d[27]), "+f"(d[28]), "+f"(d[29]), "+f"(d[30]), "+f"(d[31]), "+f"(d[32]), "+f"(d[33]), "+f"(d[34]), "+f"(d[35]), "+f"(d[36]), "+f"(d[37]), "+f"(d[38]), "+f"(d[39]), "+f"(d[40]), "+f"(d[41]), "+f"(d[42]), "+f"(d[43]), "+f"(d[44]), "+f"(d[45]), "+f"(d[46]), "+f"(d[47]), "+f"(d[48]), "+f"(d[49]), "+f"(d[50]), "+f"(d[51]), "+f"(d[52]), "+f"(d[53]), "+f"(d[54]), "+f"(d[55]), "+f"(d[56]), "+f"(d[57]), "+f"(d[58]), "+f"(d[59]), "+f"(d[60]), "+f"(d[61]), "+f"(d[62]), "+f"(d[63])
    : "l"(da), "l"(db));
}
DEVI void wgmma_qk64(float (&d)[32], uint32_t a0, uint32_t a1, uint32_t a2, uint32_t a3, uint64_t db) {
  asm volatile("wgmma.mma_async.sync.aligned.m64n64k16.f32.bf16.bf16 {%0, %1, %2, %3, %4, %5, %6, %7, %8, %9, %10, %11, %12, %13, %14, %15, %16, %17, %18, %19, %20, %21, %22, %23, %24, %25, %26, %27, %28, %29, %30, %31}, {%32, %33, %34, %35}, %36, 0, 1, 1, 0;"
    : "=f"(d[0]), "=f"(d[1]), "=f"(d[2]), "=f"(d[3]), "=f"(d[4]), "=f"(d[5]), "=f"(d[6]), "=f"(d[7]), "=f"(d[8]), "=f"(d[9]), "=f"(d[10]), "=f"(d[11]), "=f"(d[12]), "=f"(d[13]), "=f"(d[14]), "=f"(d[15]), "=f"(d[16]), "=f"(d[17]), "=f"(d[18]), "=f"(d[19]), "=f"(d[20]), "=f"(d[21]), "=f"(d[22]), "=f"(d[23]), "=f"(d[24]), "=f"(d[25]), "=f"(d[26]), "=f"(d[27]), "=f"(d[28]), "=f"(d[29]), "=f"(d[30]), "=f"(d[31])
    : "r"(a0), "r"(a1), "r"(a2), "r"(a3), "l"(db));
}
DEVI void wgmma_pv(float (&d)[8], uint32_t a0, uint32_t a1, uint32_t a2, uint32_t a3, uint64_t db) {
  asm volatile("wgmma.mma_async.sync.aligned.m64n16k16.f32.bf16.bf16 {%0, %1, %2, %3, %4, %5, %6, %7}, {%8, %9, %10, %11}, %12, 1, 1, 1, 1;"
    : "+f"(d[0]), "+f"(d[1]), "+f"(d[2]), "+f"(d[3]), "+f"(d[4]), "+f"(d[5]), "+f"(d[6]), "+f"(d[7])
    : "r"(a0), "r"(a1), "r"(a2), "r"(a3), "l"(db));
}
DEVI void wgmma_pv0(float (&d)[8], uint32_t a0, uint32_t a1, uint32_t a2, uint32_t a3, uint64_t db) {
  asm volatile("wgmma.mma_async.sync.aligned.m64n16k16.f32.bf16.bf16 {%0, %1, %2, %3, %4, %5, %6, %7}, {%8, %9, %10, %11}, %12, 0, 1, 1, 1;"
    : "=f"(d[0]), "=f"(d[1]), "=f"(d[2]), "=f"(d[3]), "=f"(d[4]), "=f"(d[5]), "=f"(d[6]), "=f"(d[7])
    : "r"(a0), "r"(a1), "r"(a2), "r"(a3), "l"(db));
}


template <int N> struct Acc { float a[64]; float b[(N - 128) / 2]; DEVI float& operator[](int i) { return i < 64 ? a[i] : b[i - 64]; } };
template <> struct Acc<128> { float a[64]; DEVI float& operator[](int i) { return a[i]; } };
template <int N> DEVI void wgmma_ss(Acc<N>& d, uint64_t da, uint64_t db) {
  wgmma_ss_n128(d.a, da, db);
  if constexpr (N == 192) wgmma_ss_n64(d.b, da, db + 256);
  if constexpr (N == 256) wgmma_ss_n128(d.b, da, db + 256);
}

DEVI int h_first(int j) { return (j & 1) ? 12 + (j & 6) : 3 * (j >> 1); }
DEVI int oh_chunk(int j, int i, int& need) {
  const int tb = j & 1, hn = 3 - tb;
  need = j;
  if (i < hn) return h_first(j) + i;
  i -= hn;
  if (i < 4) { const int o = (j + 2 * i) & 7; need = 16 + o; return 20 + o; }
  i -= 4;
  if (tb) {
    if (i < 6) { need = (j + 2 + (i & 6)) & 7; return h_first(need) + (i & 1); }
    i -= 1;
  }
  const int g = i / 3;
  need = ((j & 6) + 2 + 2 * g) & 7;
  return h_first(need) + i - 3 * g;
}

DEVI int a_slot(int e) { return 1 + (e & 3); }

struct Ctx {
  uint32_t sbase, bars, peer, t0, a16, b16;
  int wg, lane;
  int ai, bi; uint32_t aph, bph;
  int brem, ae;
  int pa, pb;
};

DEVI void release_prev(Ctx& c) {
  if (c.pb >= 0) {
    if (c.lane == 0) mbar_arrive(c.bars + 8 * (BAR_EMPTYB + c.pb));
    if (c.lane == 1) mbar_arrive_cluster(c.bars + 8 * (BAR_EMPTYB + c.pb), c.peer);
  }
  if (c.pa >= 0 && c.lane == 2) mbar_arrive(c.bars + 8 * (BAR_EMPTYA + c.pa));
}

DEVI void gemm_wait(Ctx& c) {
  asm volatile("{ .reg .pred p, q; .reg .u32 c;\n"
               "mbarrier.try_wait.parity.shared::cta.b64 p, [%0], %1;\n"
               "mbarrier.try_wait.parity.shared::cta.b64 q, [%2], %3;\n"
               "and.pred p, p, q;\n"
               "@p bra DONE_%=;\n"
               "WAIT_%=:\n"
               "mbarrier.try_wait.parity.shared::cta.b64 p, [%0], %1, %6;\n"
               "mbarrier.try_wait.parity.shared::cta.b64 q, [%2], %3, %6;\n"
               "and.pred p, p, q;\n"
               "@p bra DONE_%=;\n"
               "mov.u32 c, %%clock; sub.u32 c, c, %4; setp.lt.u32 p, c, %5;\n"
               "@p bra WAIT_%=;\n"
               "DONE_%=: }" ::"r"(c.bars + 8 * (BAR_FULLA + c.ai)), "r"((c.aph >> c.ai) & 1), "r"(c.bars + 8 * (BAR_FULLB + c.bi)), "r"(c.bph), "r"(c.t0),
               "n"(TIMEOUT), "r"(WAIT_HINT_NS) : "memory");
}
template <int N, bool SHALLOW>
DEVI void gemm_group(Acc<N>& acc, Ctx& c, int g, int& npa, int& npb) {
  const uint32_t a16 = c.a16 + c.ai * (SLOT >> 4);
  const uint32_t b16 = c.b16 + c.bi * (SLOT >> 4);
  bool adv;
  if constexpr (N >= 192) {
    const uint32_t a2 = a16 + (g & 1) * 4;
    wgmma_ss<N>(acc, desc_sw128<16>(a2), desc_sw128<2048>(b16));
    if (SHALLOW) { wgmma_commit(); wgmma_wait<0>(); }
    wgmma_ss<N>(acc, desc_sw128<16>(a2 + 2), desc_sw128<2048>(b16 + 512));
    adv = g & 1;
  } else {
#pragma unroll
    for (int s = 0; s < 4; s++) {
      wgmma_ss<N>(acc, desc_sw128<16>(a16 + s * 2), desc_sw128<4096>(b16 + (s >> 1) * 512 + (s & 1) * 128));
      if (SHALLOW && s < 3) { wgmma_commit(); wgmma_wait<0>(); }
    }
    adv = true;
  }
  wgmma_commit();
  npb = c.brem > 0 ? c.bi : -1;
  c.brem--;
  if (++c.bi == NB) { c.bi = 0; c.bph ^= 1; }
  npa = -1;
  if (adv) { npa = c.ai; c.aph ^= 1u << c.ai; c.ae++; c.ai = 1 + (c.ae & 3); }
}

template <int N, bool SHALLOW = false>
DEVI void bare_groups(Acc<N>& acc, Ctx& c, int g0, int g1) {
  for (int g = g0; g < g1; g++) {
    int npa, npb;
#ifdef TRACE3
    { const uint32_t sbase = c.sbase, t0 = c.t0;
      if (c.brem > 30 && threadIdx.x == 0 && g < 6) { mbar_wait(c.bars + 8 * (BAR_FULLA + c.ai), (c.aph >> c.ai) & 1, c.t0); TR(40 + g); } }
#endif
    gemm_wait(c);
#ifdef TRACE3
    { const uint32_t sbase = c.sbase, t0 = c.t0; if (c.brem > 30 && threadIdx.x == 0 && g < 8) TR(24 + g); }
#endif
    wgmma_fence();
    gemm_group<N, SHALLOW>(acc, c, g, npa, npb);
    wgmma_wait<SHALLOW ? 0 : 1>();
    if (SHALLOW) { c.pa = npa; c.pb = npb; }
    release_prev(c);
    c.pa = SHALLOW ? -1 : npa; c.pb = SHALLOW ? -1 : npb;
  }
}
DEVI void drain(Ctx& c) {
  wgmma_wait<0>();
  release_prev(c);
  c.pa = c.pb = -1;
}

constexpr float SC = 0.25f * 1.4426950408889634f;

#define ONCE _Pragma("unroll 1") for (unsigned once_ = 0; once_ < gridDim.y; once_++)

struct Gate { float g0, g1; };

DEVI void kill32(float (&S)[32]) {
#pragma unroll
  for (int i = 0; i < 32; i++) S[i] = __int_as_float(0xff800000);
}
DEVI void row_max(const float (&S)[32], float& x0, float& x1) {
  float y0 = S[1], y1 = S[3];
  x0 = fmaxf(x0, S[0]); x1 = fmaxf(x1, S[2]);
#pragma unroll
  for (int n = 1; n < 8; n++) {
    x0 = fmaxf(x0, S[4 * n]); y0 = fmaxf(y0, S[4 * n + 1]); x1 = fmaxf(x1, S[4 * n + 2]); y1 = fmaxf(y1, S[4 * n + 3]);
  }
  x0 = fmaxf(x0, y0); x1 = fmaxf(x1, y1);
}
DEVI void quad_max(float& x0, float& x1) {
  x0 = fmaxf(x0, __shfl_xor_sync(0xffffffffu, x0, 1)); x1 = fmaxf(x1, __shfl_xor_sync(0xffffffffu, x1, 1));
  x0 = fmaxf(x0, __shfl_xor_sync(0xffffffffu, x0, 2)); x1 = fmaxf(x1, __shfl_xor_sync(0xffffffffu, x1, 2));
}
DEVI void exp32(const float (&S)[32], float (&E)[32], float n0, float n1, float (&l)[4]) {
#pragma unroll
  for (int i = 0; i < 32; i++) { E[i] = ex2(fmaf(S[i], SC, (i & 2) ? n1 : n0)); l[i & 3] += E[i]; }
}
DEVI void pack32(const float (&E)[32], uint32_t (&P)[16]) {
#pragma unroll
  for (int i = 0; i < 16; i++) P[i] = pack_bf16(E[2 * i], E[2 * i + 1]);
}
template <bool FIRST> DEVI void pv4(float (&O)[8], const uint32_t (&P)[16], uint32_t v16) {
  if (FIRST) wgmma_pv0(O, P[0], P[1], P[2], P[3], desc_sw64(v16)); else wgmma_pv(O, P[0], P[1], P[2], P[3], desc_sw64(v16));
#pragma unroll
  for (int k = 1; k < 4; k++) wgmma_pv(O, P[4 * k], P[4 * k + 1], P[4 * k + 2], P[4 * k + 3], desc_sw64(v16 + k * 64));
}
DEVI bool wg_any(int wg, bool v) {
  uint32_t r;
  if (wg == 0) asm volatile("{ .reg .pred p, q; setp.ne.u32 p, %1, 0; bar.red.or.pred q, 4, 128, p; selp.u32 %0, 1, 0, q; }" : "=r"(r) : "r"((uint32_t)v) : "memory");
  else asm volatile("{ .reg .pred p, q; setp.ne.u32 p, %1, 0; bar.red.or.pred q, 5, 128, p; selp.u32 %0, 1, 0, q; }" : "=r"(r) : "r"((uint32_t)v) : "memory");
  return r != 0;
}
DEVI void get_gate(Gate& g, uint32_t sbase, int row16, int lane, uint32_t t0) {
  mbar_wait(sbase + OFF_BAR + 8 * BAR_GIN, 0, t0);
  const uint32_t a = sbase + OFF_GIN + (row16 * 16 + (lane >> 2)) * 4;
  asm volatile("ld.shared.f32 %0, [%1];" : "=f"(g.g0) : "r"(a) : "memory");
  asm volatile("ld.shared.f32 %0, [%1];" : "=f"(g.g1) : "r"(a + 32) : "memory");
}

DEVI void attention(uint32_t sbase, int aw, int wi, int lane, int rb, uint32_t t0) {
  const uint32_t bars = sbase + OFF_BAR;
  const uint32_t kvb = ((sbase & 0x3FFFF) + OFF_KV + aw * 4096) >> 4;
  const int cmin = 4 - 2 * rb - aw;
  const int rowc = wi * 16 + (lane >> 2) - (lane & 3) * 2;
  const uint32_t qst = sbase + OFF_A + aw * 8192;
  const float NINF = __int_as_float(0xff800000);
  const int tlo = max(cmin, 1);
#pragma unroll 1
  for (int h = 0; h < 4; h++) {
    const uint32_t kb = kvb + (h & 1) * (KVBUF >> 4);
    const uint4 q = lds128(qst + h * 2048 + (wi * 32 + lane) * 16);
    float O[8], l0, l1;
    uint32_t nm;
    asm volatile("ld.shared.u32 %0, [%1];" : "=r"(nm) : "r"(sbase + OFF_NM + ((aw * 4 + wi) * 32 + (lane & 28) + h) * 4) : "memory");
    float n0 = __uint_as_float(nm << 16), n1 = __uint_as_float(nm & 0xffff0000u);
    mbar_wait(bars + 8 * (BAR_KVFULL + (h & 1)), h >> 1, t0);
#ifdef SKEW
    if (h == 0 && aw == 1) { const uint32_t ts = clk32(); while (clk32() - ts < SKEW) {} }
#endif
#pragma unroll 1
    for (int attempt = 0; attempt < 2; attempt++) {
      float l[4] = {0.f, 0.f, 0.f, 0.f};
      uint32_t P[16];
      {
        float S[32], F[32];
        wgmma_fence();
        wgmma_qk64(S, q.x, q.y, q.z, q.w, desc_sw64(kb + 4 * 256));
        wgmma_qk64(F, q.x, q.y, q.z, q.w, desc_sw64(kb));
        wgmma_commit();
        wgmma_wait<0>();
        for (int r = 0; r < (cmin > 0 ? 1 : 0); r++) kill32(F);
        float M[32];
#pragma unroll
        for (int i = 0; i < 32; i++) M[i] = ((i >> 2) * 8 + (i & 1) > rowc + (i & 2) * 4) ? F[i] : S[i];
        for (int r = 0; r < attempt; r++) {
          row_max(M, n0, n1);
          quad_max(n0, n1);
          n0 *= -SC; n1 *= -SC;
        }
        exp32(M, M, n0, n1, l);
        pack32(M, P);
        uint32_t PF[16];
#pragma unroll
        for (int i = 0; i < 16; i++) {
          const int col = (i >> 1) * 8, r = rowc + (i & 1) * 8;
          const uint32_t m = (col > r ? 0xFFFFu : 0u) | (col + 1 > r ? 0xFFFF0000u : 0u);
          PF[i] = P[i] & m; P[i] &= ~m;
        }
        wgmma_fence();
        pv4<true>(O, PF, kb + 2);
        wgmma_commit();
#ifndef NOPFW
        wgmma_wait<0>();
#endif
      }
      int t = 3;
#pragma unroll 1
      for (; t >= tlo; t--) {
        float S[32];
        wgmma_fence();
        wgmma_qk64(S, q.x, q.y, q.z, q.w, desc_sw64(kb + t * 256));
        wgmma_commit();
        pv4<false>(O, P, kb + (t + 1) * 256 + 2);
        wgmma_commit();
        wgmma_wait<1>();
        ONCE { exp32(S, S, n0, n1, l); }
        wgmma_wait<0>();
        pack32(S, P);
      }
      wgmma_fence();
      pv4<false>(O, P, kb + (t + 1) * 256 + 2);
      wgmma_commit();
      l0 = l[0] + l[1]; l1 = l[2] + l[3];
      l0 += __shfl_xor_sync(0xffffffffu, l0, 1); l1 += __shfl_xor_sync(0xffffffffu, l1, 1);
      l0 += __shfl_xor_sync(0xffffffffu, l0, 2); l1 += __shfl_xor_sync(0xffffffffu, l1, 2);
      const bool redo = wg_any(aw, attempt == 0 && !(l0 > 1e-6f && l0 < 1e18f && l1 > 1e-6f && l1 < 1e18f));
      wgmma_wait<0>();
      if (!redo) break;
      n0 = NINF; n1 = NINF;
#pragma unroll 1
      for (int u = 3; u >= tlo; u--) {
        float S[32];
        wgmma_fence();
        wgmma_qk64(S, q.x, q.y, q.z, q.w, desc_sw64(kb + u * 256));
        wgmma_commit();
        wgmma_wait<0>();
        row_max(S, n0, n1);
      }
    }
    if (lane == 0) mbar_arrive(bars + 8 * (BAR_KVEMPTY + (h & 1)));
    Gate g;
    get_gate(g, sbase, aw * 4 + wi, lane, t0);
    const float c0 = __fdividef(g.g0, l0), c1 = __fdividef(g.g1, l1);
    const int mi = lane >> 3;
    const int srow = wi * 16 + (lane & 7) + 8 * (mi & 1);
    stsm_x4(qst + h * 2048 + srow * 32 + (mi >> 1) * 16, pack_bf16(O[0] * c0, O[1] * c0), pack_bf16(O[2] * c1, O[3] * c1),
            pack_bf16(O[4] * c0, O[5] * c0), pack_bf16(O[6] * c1, O[7] * c1));
    fence_async_smem();
    __syncwarp();
    if (lane == 0) mbar_arrive(bars + 8 * (BAR_OST + h));
  }
}

template <int CH, int N>
DEVI void store_h_chunk(Acc<N>& acc, uint32_t base  , int lane, float s0, float s1) {
  const int mi = lane >> 3;
#pragma unroll
  for (int tp = 0; tp < 4; tp++) {
    const int t = CH * 8 + tp * 2;
    const uint32_t r0 = pack_bf16(fmaxf(acc[4 * t + 0], 0.f) * s0, fmaxf(acc[4 * t + 1], 0.f) * s0);
    const uint32_t r1 = pack_bf16(fmaxf(acc[4 * t + 2], 0.f) * s1, fmaxf(acc[4 * t + 3], 0.f) * s1);
    const uint32_t r2 = pack_bf16(fmaxf(acc[4 * t + 4], 0.f) * s0, fmaxf(acc[4 * t + 5], 0.f) * s0);
    const uint32_t r3 = pack_bf16(fmaxf(acc[4 * t + 6], 0.f) * s1, fmaxf(acc[4 * t + 7], 0.f) * s1);
    stsm_x4(base + (((tp * 2 + (mi >> 1)) ^ (lane & 7)) << 4), r0, r1, r2, r3);
  }
}

template <int N>
DEVI void phase_q(Ctx& c, int warp) {
  Acc<N> acc;
#pragma unroll
  for (int i = 0; i < N / 2; i++) acc[i] = 0.f;
  bare_groups<N>(acc, c, 0, 16);
  drain(c);
  const int lane = c.lane, mi = lane >> 3;
  const int row = warp * 16 + (lane & 7) + 8 * (mi & 1);
  const int sw = (row >> 1) & 3;
#pragma unroll
  for (int hh = 0; hh < 4; hh++) {
    const uint32_t base = c.sbase + OFF_KV + hh * 8192 + row * 64;
#pragma unroll
    for (int kv = 0; kv < 2; kv++) {
      const int t = 8 + kv * 8 + 2 * hh;
      stsm_x4(base + (((kv * 2 + (mi >> 1)) ^ sw) << 4),
              pack_bf16(acc[4 * t + 0], acc[4 * t + 1]), pack_bf16(acc[4 * t + 2], acc[4 * t + 3]),
              pack_bf16(acc[4 * t + 4], acc[4 * t + 5]), pack_bf16(acc[4 * t + 6], acc[4 * t + 7]));
    }
  }
  fence_async_smem();
  __syncwarp();
  if (lane == 0) mbar_arrive(c.bars + 8 * BAR_STG);
#pragma unroll
  for (int hh = 0; hh < 4; hh++)
    sts128(c.sbase + OFF_A + c.wg * 8192 + hh * 2048 + ((warp & 3) * 32 + lane) * 16,
           pack_bf16(acc[8 * hh], acc[8 * hh + 1]), pack_bf16(acc[8 * hh + 2], acc[8 * hh + 3]),
           pack_bf16(acc[8 * hh + 4], acc[8 * hh + 5]), pack_bf16(acc[8 * hh + 6], acc[8 * hh + 7]));
#pragma unroll
  for (int hh = 0; hh < 4; hh++) {
    const int q = 8 * hh, k = 32 + 8 * hh;
    float d0 = acc[q] * acc[k] + acc[q + 1] * acc[k + 1] + acc[q + 4] * acc[k + 4] + acc[q + 5] * acc[k + 5];
    float d1 = acc[q + 2] * acc[k + 2] + acc[q + 3] * acc[k + 3] + acc[q + 6] * acc[k + 6] + acc[q + 7] * acc[k + 7];
    d0 += __shfl_xor_sync(0xffffffffu, d0, 1); d1 += __shfl_xor_sync(0xffffffffu, d1, 1);
    d0 += __shfl_xor_sync(0xffffffffu, d0, 2); d1 += __shfl_xor_sync(0xffffffffu, d1, 2);
    if ((lane & 3) == hh)
      asm volatile("st.shared.u32 [%0], %1;" ::"r"(c.sbase + OFF_NM + (warp * 32 + lane) * 4), "r"(pack_bf16(-d0 * SC, -d1 * SC)) : "memory");
  }
  __syncwarp();
  if (lane == 0) mbar_arrive(c.bars + 8 * (BAR_QRDY + c.wg));
  if constexpr (N == 256) {
    Gate g;
    get_gate(g, c.sbase, warp, lane, c.t0);
    store_h_chunk<3>(acc, c.sbase + OFF_KV + 32768 + row * 128, lane, 1.f - g.g0, 1.f - g.g1);
    fence_async_smem();
    __syncwarp();
    if (lane == 0) mbar_arrive(c.bars + 8 * BAR_STE);
  }
}

DEVI void first_loads(const Params& P, uint32_t sbase, int e, int j, int rb) {
  const uint32_t bars = sbase + OFF_BAR, fb = bars + 8 * (BAR_FULLB + e), fa = bars + 8 * (BAR_FULLA + 1 + e);
  mbar_expect_tx(fa, 16384);
  mbar_expect_tx(fb, 16384);
  if (e == 0) tma_load_2d(sbase + OFF_A + SLOT, &P.tmX, 0, rb * 128, fa);
#pragma unroll
  for (int r = 0; r < 2; r++) {
    tma_load_3d(sbase + OFF_B + e * SLOT + r * 8192, &P.tmWqkv, 64 * j, e * 32 + r * 16, 0, fb);
    tma_load_3d(sbase + OFF_B + e * SLOT + r * 8192 + 6144, &P.tmW1a, 0, e * 32 + r * 16, 20 + j, fb);
  }
  if (e == 1) tma_load_2d(sbase + OFF_A + 2 * SLOT, &P.tmX, 64, rb * 128, fa);
}

__global__ void __cluster_dims__(2, 1, 1) __launch_bounds__(640, 1) fused_kernel(const __grid_constant__ Params P) {
  extern __shared__ __align__(1024) uint8_t smem_raw[];
  const uint32_t sbase = smem_u32(smem_raw);
  const uint32_t bars = sbase + OFF_BAR;
  const int tid = threadIdx.x, warp = tid >> 5, lane = tid & 31;
  const uint32_t rank = blockIdx.x & 1, peer = rank ^ 1;
  const int j = (blockIdx.x >> 1) & 7, rb = ((blockIdx.x >> 4) << 1) | rank;
  const uint32_t t0 = clk32();
#ifdef TRACE
  uint32_t gt0; asm volatile("mov.u32 %0, %%globaltimer_lo;" : "=r"(gt0));
#endif

  const int typeB = j & 1;
  if (tid == 544) {
    for (int s = 0; s < NA; s++) mbar_init(bars + 8 * (BAR_FULLA + s), 1);
    for (int s = 0; s < NB; s++) mbar_init(bars + 8 * (BAR_FULLB + s), 1);
    fence_async_smem();
  } else if (tid < 9) {
    asm volatile("prefetch.tensormap [%0];" ::"l"(&P.tmX + tid) : "memory");
  } else if (tid == 512) {
    for (int s = 0; s < NA; s++) mbar_init(bars + 8 * (BAR_EMPTYA + s), 9);
    for (int s = 0; s < NB; s++) mbar_init(bars + 8 * (BAR_EMPTYB + s), 16);
  } else if (tid == 576) {
    for (int s = 0; s < 2; s++) { mbar_init(bars + 8 * (BAR_KVFULL + s), 1); mbar_init(bars + 8 * (BAR_KVEMPTY + s), 8); mbar_init(bars + 8 * (BAR_OST + s), 8); mbar_init(bars + 8 * (BAR_OST + 2 + s), 8); mbar_init(bars + 8 * (BAR_QRDY + s), 4); }
    mbar_init(bars + 8 * BAR_STG, 8); mbar_init(bars + 8 * BAR_STE, 8); mbar_init(bars + 8 * BAR_KVOK, 1);
    mbar_init(bars + 8 * BAR_PIN, 1); mbar_init(bars + 8 * BAR_PFREE, 8); mbar_init(bars + 8 * BAR_GIN, 1);
  }
  if (tid >= 512 && lane == 0) asm volatile("fence.mbarrier_init.release.cluster;" ::: "memory");
#ifdef TRACE
  if (tid < 64) asm volatile("st.shared.u32 [%0], %1;" ::"r"(sbase + OFF_BAR + 640 + 4 * tid), "r"(0));
#endif
  const unsigned ep1 = ld_relaxed(&g_epoch) + 1;
  __syncwarp();
  cluster_arrive();
  if (tid == 544) { first_loads(P, sbase, 0, j, rb); first_loads(P, sbase, 1, j, rb); }
#if PF0 == 1
  if (tid == 544) { l2_prefetch(P.x + (size_t)(rb * 128 + j * 16) * DM, 16384); l2_prefetch((const uint8_t*)P.wqkv + blockIdx.x * 12288, 12288); }
#elif PF0 == 2
  if (tid == 320) { l2_prefetch(P.x + (size_t)(rb * 128 + j * 16) * DM, 16384); l2_prefetch((const uint8_t*)P.wqkv + blockIdx.x * 12288, 12288); }
#endif
  __syncwarp();

  const int on = 12 + 4 * typeB, hn = 3 - typeB;
  const int bo = typeB ? 24 : 32;
  const int nb = bo + on + 4;

  if (warp < 8) {
    asm volatile("setmaxnreg.inc.sync.aligned.u32 160;");
    cluster_wait();
    const int wg = __shfl_sync(0xffffffffu, warp >> 2, 0);
    Ctx c{sbase, bars, peer, t0, ((sbase & 0x3FFFF) + OFF_A + wg * 8192) >> 4, ((sbase & 0x3FFFF) + OFF_B) >> 4, wg, lane, 1, 0, 0u, 0u, nb - NB, 0, -1, -1};
    if (tid == 0) TR(0);
    phase_q<256>(c, warp);
    asm volatile("setmaxnreg.dec.sync.aligned.u32 128;");
    if (tid == 0) TR(2);
    {
      const uint32_t rowoff = (warp * 16 + (lane & 7) + 8 * ((lane >> 3) & 1)) * 128;
      Gate at;
      get_gate(at, sbase, warp, lane, t0);
      const float s0 = 1.f - at.g0, s1 = 1.f - at.g1;
      if (typeB) {
        Acc<128> acc;
#pragma unroll
        for (int i = 0; i < 64; i++) acc[i] = 0.f;
        bare_groups<128>(acc, c, 0, SHS / 2 + 1);
        drain(c);
        bare_groups<128, true>(acc, c, SHS / 2 + 1, 8);
        mbar_wait(bars + 8 * (BAR_FULLA + 1), 0, t0);
        store_h_chunk<0>(acc, sbase + OFF_A + 1 * SLOT + rowoff, lane, s0, s1);
        mbar_wait(bars + 8 * (BAR_FULLA + 2), 0, t0);
        store_h_chunk<1>(acc, sbase + OFF_A + 2 * SLOT + rowoff, lane, s0, s1);
      } else {
        Acc<192> acc;
#pragma unroll
        for (int i = 0; i < 96; i++) acc[i] = 0.f;
        bare_groups<192>(acc, c, 0, SHS);
        drain(c);
        bare_groups<192, true>(acc, c, SHS, 16);
        mbar_wait(bars + 8 * (BAR_FULLA + 1), 0, t0);
        store_h_chunk<0>(acc, sbase + OFF_A + 1 * SLOT + rowoff, lane, s0, s1);
        mbar_wait(bars + 8 * (BAR_FULLA + 2), 0, t0);
        store_h_chunk<1>(acc, sbase + OFF_A + 2 * SLOT + rowoff, lane, s0, s1);
        mbar_wait(bars + 8 * (BAR_FULLA + 3), 0, t0);
        store_h_chunk<2>(acc, sbase + OFF_A + 3 * SLOT + rowoff, lane, s0, s1);
      }
    }
    fence_async_smem();
    wg_bar(wg);
    if (lane == 0) mbar_arrive(bars + 8 * BAR_STG);
    if (tid == 0) TR(4);
    float own[32];
    {
      Acc<128> acc;
#pragma unroll
      for (int i = 0; i < 64; i++) acc[i] = 0.f;
#if TB == 1
      if (typeB) bare_groups<128, false>(acc, c, 0, on); else bare_groups<128, true>(acc, c, 0, on);
#elif TB == 2
      bare_groups<128, true>(acc, c, 0, typeB ? 8 : on);
      bare_groups<128, false>(acc, c, typeB ? 8 : on, on);
#else
      bare_groups<128, true>(acc, c, 0, on);
#endif
      drain(c);
      if (tid == 0) TR(5);
      if (lane == 0) mbar_arrive(bars + 8 * BAR_PFREE);
      named_bar<3>(256);
      const uint32_t pst = sbase + OFF_B + ((nb - 6) % NB) * SLOT + wg * 8192 + (tid & 127) * 16;
#pragma unroll
      for (int i = 0; i < 4; i++) {
        uint32_t r[4];
#pragma unroll
        for (int k = 0; k < 4; k++) {
          const int idx = 8 * i + 2 * k;
          const float lo = typeB ? acc[idx] : acc[32 + idx], hi = typeB ? acc[idx + 1] : acc[32 + idx + 1];
          r[k] = pack_bf16(lo, hi);
        }
        sts128(pst + i * 2048, r[0], r[1], r[2], r[3]);
      }
#pragma unroll
      for (int i = 0; i < 32; i++) own[i] = typeB ? acc[32 + i] : acc[i];
      fence_async_smem();
      __syncwarp();
      if (lane == 0) mbar_arrive(bars + 8 * BAR_STG);
    }
#pragma unroll 1
    for (int g = 0; g < 8; g++) {
      const uint32_t a16 = c.a16 + c.ai * (SLOT >> 4);
      const uint32_t b16 = c.b16 + c.bi * (SLOT >> 4) + (g & 1) * 512;
      if (g == 6) {
        mbar_wait(bars + 8 * BAR_PIN, 0, t0);
        const uint32_t pin = sbase + OFF_B + ((nb - 5) % NB) * SLOT + wg * 8192 + (tid & 127) * 16;
#pragma unroll
        for (int i = 0; i < 4; i++) {
          const uint4 v = lds128(pin + i * 2048);
          const uint32_t r[4] = {v.x, v.y, v.z, v.w};
#pragma unroll
          for (int k = 0; k < 4; k++) { own[8 * i + 2 * k] += __uint_as_float(r[k] << 16); own[8 * i + 2 * k + 1] += __uint_as_float(r[k] & 0xffff0000u); }
        }
        named_bar<3>(256);
        if (tid == 0) TR(7);
      }
      gemm_wait(c);
      wgmma_fence();
#pragma unroll
      for (int s = 0; s < 4; s++) wgmma_ss_n64(own, desc_sw128<16>(a16 + s * 2), desc_sw128<2048>(b16 + s * 128));
      wgmma_commit();
      wgmma_wait<0>();
      if (lane == 2) mbar_arrive(bars + 8 * (BAR_EMPTYA + c.ai));
      c.aph ^= 1u << c.ai;
      c.ae++; c.ai = a_slot(c.ae);
      if (g & 1) { if (++c.bi == NB) { c.bi = 0; c.bph ^= 1; } }
    }
    if (tid == 0) TR(6);
    {
      const uint32_t ob = sbase + OFF_B + ((nb - 5) % NB) * SLOT;
      const uint32_t wb = ob + warp * 2048;
      const uint32_t orow = wb + ((lane & 7) + 8 * ((lane >> 3) & 1)) * 128;
#pragma unroll
      for (int i = 0; i < 4; i++)
        stsm_x4(orow + (((i * 2 + (lane >> 4)) ^ (lane & 7)) << 4), pack_bf16(own[8 * i], own[8 * i + 1]), pack_bf16(own[8 * i + 2], own[8 * i + 3]),
                pack_bf16(own[8 * i + 4], own[8 * i + 5]), pack_bf16(own[8 * i + 6], own[8 * i + 7]));
      __syncwarp();
      uint4* o = (uint4*)(P.out + (size_t)(rb * 128 + warp * 16 + (lane >> 3)) * DM + j * 64) + (lane & 7);
#pragma unroll
      for (int i = 0; i < 4; i++) {
        const int r = i * 4 + (lane >> 3);
        o[i * 4 * (DM / 8)] = lds128(wb + r * 128 + (((lane & 7) ^ (r & 7)) << 4));
      }
    }
    if (tid == 0) TR(8);
#ifdef TRACE
    named_bar<3>(256);
    if (tid < 64) { uint32_t v; asm volatile("ld.shared.u32 %0, [%1];" : "=r"(v) : "r"(sbase + OFF_BAR + 640 + 4 * tid));
      if (tid == 16) v = gt0;
      if (tid == 17) asm volatile("mov.u32 %0, %%globaltimer_lo;" : "=r"(v));
      if (tid == 18) v = clk32() - t0;
      g_trace[blockIdx.x * 64 + tid] = v; }
#endif
  } else if (warp < 16) {
    asm volatile("setmaxnreg.dec.sync.aligned.u32 56;");
    cluster_wait();
    const int aw = __shfl_sync(0xffffffffu, (warp >> 2) & 1, 0);
    {
      const int rowg = rb * 128 + j * 16 + (warp - 8) * 2;
      const uint4* gw = (const uint4*)P.gate_w;
      const uint4* xr = (const uint4*)(P.x + (size_t)rowg * DM);
      mbar_wait(bars + 8 * (BAR_FULLB + 1), 0, t0);
      const uint4 w0 = __ldg(gw + lane), w1 = __ldg(gw + 32 + lane);
      const uint4 xa0 = __ldg(xr + lane), xa1 = __ldg(xr + 32 + lane), xb0 = __ldg(xr + 64 + lane), xb1 = __ldg(xr + 96 + lane);
#pragma unroll
      for (int i = 0; i < 4; i++) sts128(sbase + OFF_KV + 32768 + i * 4096 + (tid - 256) * 16, 0u, 0u, 0u, 0u);
      const uint32_t wa[8] = {w0.x, w0.y, w0.z, w0.w, w1.x, w1.y, w1.z, w1.w};
      const uint32_t xa[8] = {xa0.x, xa0.y, xa0.z, xa0.w, xa1.x, xa1.y, xa1.z, xa1.w};
      const uint32_t xb[8] = {xb0.x, xb0.y, xb0.z, xb0.w, xb1.x, xb1.y, xb1.z, xb1.w};
      float za = 0.f, zb = 0.f;
#pragma unroll
      for (int e = 0; e < 8; e++) {
        const float wl = __uint_as_float(wa[e] << 16), wh = __uint_as_float(wa[e] & 0xffff0000u);
        za = fmaf(__uint_as_float(xa[e] << 16), wl, za); za = fmaf(__uint_as_float(xa[e] & 0xffff0000u), wh, za);
        zb = fmaf(__uint_as_float(xb[e] << 16), wl, zb); zb = fmaf(__uint_as_float(xb[e] & 0xffff0000u), wh, zb);
      }
#pragma unroll
      for (int o = 16; o > 0; o >>= 1) { za += __shfl_xor_sync(0xffffffffu, za, o); zb += __shfl_xor_sync(0xffffffffu, zb, o); }
      if (lane < 2) asm volatile("st.shared.f32 [%0], %1;" ::"r"(sbase + OFF_GST + (warp - 8) * 8 + lane * 4), "f"(1.f / (1.f + __expf(-(lane ? zb : za)))) : "memory");
      fence_async_smem();
      named_bar<6>(256);
      if (tid == 256) {
        bulk_store(&g_gate[rb * 128 + j * 16], sbase + OFF_GST, 64);
        bulk_commit(); bulk_wait_all();
        flag_add(&g_flag_g[rb * FS]);
        flag_wait(&g_flag_g[rb * FS], ep1 * 8, t0);
        fence_async_global();
        mbar_expect_tx(bars + 8 * BAR_GIN, 512);
        bulk_load(sbase + OFF_GIN, &g_gate[rb * 128], 512, bars + 8 * BAR_GIN);
        TR(10);
      }
      __syncwarp();
    }
    mbar_wait(bars + 8 * (BAR_QRDY + aw), 0, t0);
    asm volatile("setmaxnreg.inc.sync.aligned.u32 96;");
    attention(sbase, aw, warp & 3, lane, rb, t0);
    if (tid == 256) TR(3);
  } else {
    asm volatile("setmaxnreg.dec.sync.aligned.u32 32;");
    if (warp == 16) {
      __syncwarp();
      cluster_wait();
#ifdef TRACE3
      if (lane == 0) TR(51);
#endif
      if (lane == 0) {
        int bi = 2; uint32_t bph = 1;
        for (int eb = 2; eb < nb; eb++) {
          if (eb == 4 || eb == 6) {
            const int ea = eb >> 1;
            mbar_expect_tx(bars + 8 * (BAR_FULLA + 1 + ea), 16384);
            tma_load_2d(sbase + OFF_A + (1 + ea) * SLOT, &P.tmX, ea * 64, rb * 128, bars + 8 * (BAR_FULLA + 1 + ea));
          }
          const uint32_t fb = bars + 8 * (BAR_FULLB + bi), dst = sbase + OFF_B + bi * SLOT + rank * 8192;
          mbar_wait(bars + 8 * (BAR_EMPTYB + bi), bph, t0);
          if (eb < 16) {
            mbar_expect_tx(fb, 16384);
            tma_load_3d_mc(dst, &P.tmWqkv, 64 * j, eb * 32 + rank * 16, 0, fb);
            tma_load_3d_mc(dst + 6144, &P.tmW1a, 0, eb * 32 + rank * 16, 20 + j, fb);
          }
          else if (eb < bo) {
            if (typeB) { mbar_expect_tx(fb, 16384); tma_load_3d_mc(dst, &P.tmW1c, 0, (eb - 16) * 64 + rank * 32, h_first(j), fb); }
            else { mbar_expect_tx(fb, 12288); tma_load_3d_mc(dst, &P.tmW1b, 0, (eb - 16) * 32 + rank * 16, h_first(j), fb); }
          }
          else if (eb < bo + on) { int ow; const int ch = oh_chunk(j, eb - bo, ow); mbar_expect_tx(fb, 16384); tma_load_3d_mc(dst, &P.tmW2, 0, ch * 64 + rank * 32, (j >> 1) * 2, fb); }
          else { mbar_expect_tx(fb, 16384); tma_load_4d_mc(dst, &P.tmWo, 64 * j, 0, eb - bo - on, rank * 4, fb); }
#ifdef TRACE3
          if (eb < 6) TR(32 + eb);
#endif
          if (++bi == NB) { bi = 0; bph ^= 1; }
#ifndef NOPF
          if (eb == PFAT) {
            const int b = blockIdx.x;
             int ch = ea & 7, need = -1;
          if (ea >= 16 + on) { need = 8 + ea - 16 - on; ch = 20 + need; }
          else if (ea >= 16 + hn) ch = oh_chunk(j, ea - 16, need);
          if (need >= 0 && !((ready >> need) & 1)) {
            const unsigned* fp = need < 8 ? &g_flag_h[rb * 8 * FS] : need < 16 ? &g_flag_o[rb * 8 * FS] : &g_flag_e[rb * 8 * FS];
            const unsigned tgt = (need & 8) ? ep1 * 4 : ep1;
            do {
              unsigned v[8];
#pragma unroll
              for (int i = 0; i < 8; i++) v[i] = ld_relaxed(fp + i * FS);
#pragma unroll
              for (int i = 0; i < 8; i++) if ((int)(v[i] - tgt) >= 0) ready |= 1u << (i + (need & 24));
            } while (!((ready >> need) & 1) && clk32() - t0 < TIMEOUT);
            fence_async_global();
          }
 1; ea < 5; ea++) mbar_arrive(bars + 8 * (BAR_EMPTYA + ea));
        uint32_t aph = 0;
        const int na = 16 + on + 8;
        unsigned ready = 0;
        for (int ea = 4; ea < na; ea++) {
          const int ai = a_slot(ea);
          const uint32_t fb = bars + 8 * (BAR_FULLA + ai), dst = sbase + OFF_A + ai * SLOT;
          int ch = ea & 7;
          if (ea >= 19) {
            ch = ea >= 16 + on ? 12 - on + ea : oh_chunk(j, ea - 16);
            while (!((ready >> ch) & 1) && clk32() - t0 < TIMEOUT) {
              const unsigned* fp = ch < 24 ? &g_flag_h[rb * 8 * FS] : ch < 28 ? &g_flag_e[rb * 8 * FS] : &g_flag_o[rb * 8 * FS];
              unsigned v[8];
#pragma unroll
              for (int i = 0; i < 8; i++) v[i] = ld_relaxed(fp + i * FS);
#pragma unroll
              for (int i = 0; i < 8; i++) {
                if (ch < 24) ready |= (uint64_t)((1u << min(max((int)(v[i] - (ep1 - 1) * 3), 0), 3)) - 1) << (3 * i);
                else if (ch < 28) { if (!(i & 1) && (int)(v[i] - ep1) >= 0) ready |= 1ull << (24 + (i >> 1)); }
                else if ((int)(v[i] - ep1 * 4) >= 0) ready |= 1ull << (28 + i);
              }
              fence_async_global();
            }
          }
          mbar_wait(bars + 8 * (BAR_EMPTYA + ai), (aph >> ai) & 1, t0);
          if (ea >= 16 && ea < 16 + hn) mbar_arrive(fb);
          else {
            mbar_arrive(bars + 8 * (BAR_EMPTYA + ai));
            mbar_expect_tx(fb, 16384);
            tma_load_2d(dst, ea < 16 ? &P.tmX : &P.tmHO, ch * 64, rb * 128, fb);
          }
#if !defined(TRACE2) && !defined(TRACE3)
          TR(24 + ea);
#endif
          aph ^= 1u << ai;
        }
      }
    } else {
      const int wg = warp - 18;
      cluster_wait();
      if (lane == 0 && wg == 0) {
        const uint32_t stg = bars + 8 * BAR_STG;
        mbar_wait(stg, 0, t0);
        for (int hh = 0; hh < 4; hh++) bulk_store(g_kv + ((size_t)(4 * j + hh) * SEQ + rb * 128) * 64, sbase + OFF_KV + hh * 8192, 8192);
        bulk_commit(); bulk_wait_all();
        flag_add(&g_flag_kv[(rb * 8 + j) * FS]);
        TR(21);
        {
          mbar_wait(bars + 8 * BAR_STE, 0, t0);
          tma_store_2d(&P.tmHO, (20 + j) * 64, rb * 128, sbase + OFF_KV + 32768);
          bulk_commit(); bulk_wait_all();
          mbar_arrive(bars + 8 * BAR_KVOK);
          flag_add(&g_flag_e[(rb * 8 + j) * FS]);
        }
        mbar_wait(stg, 1, t0);
        for (int i = 0; i < hn; i++) { tma_store_2d(&P.tmHO, (h_first(j) + i) * 64, rb * 128, sbase + OFF_A + (1 + i) * SLOT); bulk_commit(); }
        if (!typeB) { asm volatile("cp.async.bulk.wait_group.read 2;" ::: "memory"); mbar_arrive(bars + 8 * (BAR_EMPTYA + 1)); }
        asm volatile("cp.async.bulk.wait_group.read 1;" ::: "memory");
        mbar_arrive(bars + 8 * (BAR_EMPTYA + hn - 1));
        bulk_wait_all();
        mbar_arrive(bars + 8 * (BAR_EMPTYA + hn));
        flag_add(&g_flag_h[(rb * 8 + j) * FS]);
        TR(22);
        {
          const unsigned old = atomicAdd(&g_done, 1u);
          if (old == gridDim.x - 1) { g_done = 0; *(volatile unsigned*)&g_epoch = ep1; }
        }
        mbar_wait(stg, 0, t0);
        bulk_store(g_part + (size_t)(rb * 8 + (j ^ 1)) * 16384, sbase + OFF_B + ((nb - 6) % NB) * SLOT, 16384);
        bulk_commit(); bulk_wait_all();
        flag_add(&g_flag_p[(rb * 8 + (j ^ 1)) * FS]);
        TR(23);
      } else if (lane == 0) {
        const int nblk = rb >= 2 ? 3 : rb + 1;
        const uint32_t kvbytes = nblk * 8192;
        const uint8_t* kvsrc = g_kv + ((size_t)(4 * j) * SEQ + (rb + 1 - nblk) * 128) * 64;
        const uint32_t kvdst = sbase + OFF_KV + (3 - nblk) * 8192;
        {
          const unsigned* f0 = &g_flag_kv[(rb * 8 + j) * FS];
          const unsigned* f1 = rb >= 1 ? f0 - 8 * FS : f0;
          const unsigned* f2 = rb >= 2 ? f0 - 16 * FS : f0;
          unsigned v0, v1, v2;
          do { v0 = ld_relaxed(f0); v1 = ld_relaxed(f1); v2 = ld_relaxed(f2); }
          while (((int)(v0 - ep1) < 0 || (int)(v1 - ep1) < 0 || (int)(v2 - ep1) < 0) && clk32() - t0 < TIMEOUT);
        }
        TR(11);
        mbar_wait(bars + 8 * BAR_GIN, 0, t0);
        fence_async_global();
        mbar_expect_tx(bars + 8 * BAR_KVFULL, kvbytes);
        bulk_load(kvdst, kvsrc, kvbytes, bars + 8 * BAR_KVFULL);
        mbar_wait(bars + 8 * BAR_KVOK, 0, t0);
        mbar_expect_tx(bars + 8 * (BAR_KVFULL + 1), kvbytes);
        bulk_load(kvdst + KVBUF, kvsrc + (size_t)SEQ * 64, kvbytes, bars + 8 * (BAR_KVFULL + 1));
        for (int hh = 0; hh < 4; hh++) {
          mbar_wait(bars + 8 * (BAR_OST + hh), 0, t0);
          for (int aw = 0; aw < 2; aw++) {
            tma_store_2d(&P.tmOs, DFF + hh * 128 + j * 16, rb * 128 + aw * 64, sbase + OFF_A + aw * 8192 + hh * 2048);
          }
          bulk_commit();
          if (hh < 2) {
            mbar_wait(bars + 8 * (BAR_KVEMPTY + hh), 0, t0);
            mbar_expect_tx(bars + 8 * (BAR_KVFULL + hh), kvbytes);
            bulk_load(kvdst + hh * KVBUF, kvsrc + (size_t)(hh + 2) * SEQ * 64, kvbytes, bars + 8 * (BAR_KVFULL + hh));
          }
          bulk_wait_all();
          flag_add(&g_flag_o[(rb * 8 + hh * 2 + (j >> 2)) * FS]);
          TR(12 + hh);
        }
      }
    }
  }
}

typedef CUresult (*EncodeFn)(CUtensorMap*, CUtensorMapDataType, cuuint32_t, void*, const cuuint64_t*, const cuuint64_t*, const cuuint32_t*,
                             const cuuint32_t*, CUtensorMapInterleave, CUtensorMapSwizzle, CUtensorMapL2promotion, CUtensorMapFloatOOBfill);

void make_map(EncodeFn enc, CUtensorMap* m, const void* ptr, int rank, const cuuint64_t* dims, const cuuint64_t* strides, const cuuint32_t* box,
              CUtensorMapSwizzle sw = CU_TENSOR_MAP_SWIZZLE_128B) {
  cuuint32_t es[4] = {1, 1, 1, 1};
  enc(m, CU_TENSOR_MAP_DATA_TYPE_BFLOAT16, rank, const_cast<void*>(ptr), dims, strides, box, es, CU_TENSOR_MAP_INTERLEAVE_NONE, sw,
      CU_TENSOR_MAP_L2_PROMOTION_L2_256B, CU_TENSOR_MAP_FLOAT_OOB_FILL_NONE);
}

}

extern "C" void kernel_launch(void* const* d_in, const int* in_sizes, int n_in, void* d_out, int out_size) {
  (void)in_sizes; (void)n_in; (void)out_size;
  static EncodeFn enc = nullptr;
  static void* ho_ptr = nullptr;
  if (!enc) {
    void* fn = nullptr; cudaDriverEntryPointQueryResult st;
    cudaGetDriverEntryPoint("cuTensorMapEncodeTiled", &fn, cudaEnableDefault, &st);
    enc = (EncodeFn)fn;
    cudaGetSymbolAddress(&ho_ptr, g_ho);
    cudaFuncSetAttribute(fused_kernel, cudaFuncAttributeMaxDynamicSharedMemorySize, SMEM_BYTES);
  }
  const __nv_bfloat16* x = (const __nv_bfloat16*)d_in[0];
  const __nv_bfloat16* wqkv = (const __nv_bfloat16*)d_in[1];
  const __nv_bfloat16* wo = (const __nv_bfloat16*)d_in[2];
  const __nv_bfloat16* w1 = (const __nv_bfloat16*)d_in[4];
  const __nv_bfloat16* w2 = (const __nv_bfloat16*)d_in[5];
  const __nv_bfloat16* gate_w = (const __nv_bfloat16*)d_in[6];
  Params P;
  { cuuint64_t d[2] = {DM, SEQ}, s[1] = {DM * 2}; cuuint32_t b[2] = {64, 128}; make_map(enc, &P.tmX, x, 2, d, s, b); }
  { cuuint64_t d[3] = {512, 512, 3}, s[2] = {1536 * 2, 512 * 2}; cuuint32_t b[3] = {64, 16, 3}; make_map(enc, &P.tmWqkv, wqkv, 3, d, s, b); }
  { cuuint64_t d[3] = {64, 512, 28}, s[2] = {DFF * 2, 128}; cuuint32_t b[3] = {64, 16, 1}; make_map(enc, &P.tmW1a, w1, 3, d, s, b);
    b[2] = 3; make_map(enc, &P.tmW1b, w1, 3, d, s, b);
    b[1] = 32; b[2] = 2; make_map(enc, &P.tmW1c, w1, 3, d, s, b); }
  { cuuint64_t d[3] = {64, DFF, 8}, s[2] = {DM * 2, 128}; cuuint32_t b[3] = {64, 32, 2}; make_map(enc, &P.tmW2, w2, 3, d, s, b); }
  { cuuint64_t d[4] = {DM, 16, 4, 8}, s[3] = {DM * 2, 16 * DM * 2, 64 * DM * 2}; cuuint32_t b[4] = {64, 16, 1, 4}; make_map(enc, &P.tmWo, wo, 4, d, s, b); }
  { cuuint64_t d[2] = {KHO, SEQ}, s[1] = {KHO * 2}; cuuint32_t b[2] = {64, 128}; make_map(enc, &P.tmHO, ho_ptr, 2, d, s, b);
    b[1] = 64; b[0] = 16; make_map(enc, &P.tmOs, ho_ptr, 2, d, s, b, CU_TENSOR_MAP_SWIZZLE_NONE); }
  P.x = x; P.gate_w = gate_w; P.w1 = w1; P.w2 = w2; P.wo = wo; P.out = (__nv_bfloat16*)d_out;
  fused_kernel<<<128, 640, SMEM_BYTES>>>(P);
}

#ifdef TRACE
extern "C" void dbg_trace(unsigned* host) { cudaDeviceSynchronize(); cudaMemcpyFromSymbol(host, g_trace, sizeof(g_trace)); }
#endif
#ifdef DEBUG_EXPORTS
extern "C" void dbg_copy(int which, void* dst) {
  cudaDeviceSynchronize();
  if (which == 0) cudaMemcpyFromSymbol(dst, g_kv, sizeof(g_kv), 0, cudaMemcpyDeviceToDevice);
  if (which == 2) cudaMemcpyFromSymbol(dst, g_ho, sizeof(g_ho), 0, cudaMemcpyDeviceToDevice);
  if (which == 3) cudaMemcpyFromSymbol(dst, g_gate, sizeof(g_gate), 0, cudaMemcpyDeviceToDevice);
  cudaDeviceSynchronize();
}
#endif
```

```cpp
#include <cuda_runtime.h>
#include <cuda_bf16.h>
#include <cuda.h>
#include <stdint.h>

#define DEVI __device__ __forceinline__

namespace {

constexpr int SEQ = 2048, DM = 512, DFF = 1792, KHO = 2304;
constexpr int NA = 5, NB = 6, SLOT = 16384, KVBUF = 24576;
constexpr int OFF_B = 0, OFF_A = NB * SLOT, OFF_KV = OFF_A + NA * SLOT, OFF_BAR = OFF_KV + 2 * KVBUF;
constexpr int OFF_GST = OFF_BAR + 512;
constexpr int OFF_GIN = OFF_BAR + 1024;
constexpr int OFF_NM = OFF_BAR + 1536;
constexpr int SMEM_BYTES = OFF_BAR + 2560;
constexpr uint32_t TIMEOUT = 1u << 28;
constexpr uint32_t WAIT_HINT_NS = 20000u;
constexpr int PFAT = 10, PF2 = 24;
constexpr int SHS = 10;
constexpr int FS = 8;

constexpr int BAR_FULLA = 0, BAR_EMPTYA = BAR_FULLA + NA, BAR_FULLB = BAR_EMPTYA + NA, BAR_EMPTYB = BAR_FULLB + NB,
              BAR_KVFULL = BAR_EMPTYB + NB, BAR_KVEMPTY = BAR_KVFULL + 2, BAR_STG = BAR_KVEMPTY + 2, BAR_PIN = BAR_STG + 1, BAR_STE = BAR_PIN + 1,
              BAR_PFREE = BAR_STE + 1, BAR_GIN = BAR_PFREE + 1, BAR_OST = BAR_GIN + 1, BAR_QRDY = BAR_OST + 4, BAR_KVOK = BAR_QRDY + 2;

__device__ __align__(1024) uint8_t g_kv[32 * SEQ * 64];
__device__ __align__(1024) __nv_bfloat16 g_ho[SEQ * KHO];
__device__ __align__(1024) uint8_t g_part[128 * 16384];
__device__ __align__(128) float g_gate[SEQ];
__device__ unsigned g_flag_kv[128 * FS], g_flag_h[128 * FS], g_flag_o[128 * FS], g_flag_g[16 * FS], g_flag_p[128 * FS], g_flag_e[128 * FS];
__device__ unsigned g_epoch, g_done;

struct Params {
  CUtensorMap tmX, tmWqkv, tmW1a, tmW1b, tmW2, tmWo, tmHO, tmOs;
  const __nv_bfloat16* x;
  const __nv_bfloat16* gate_w;
  const __nv_bfloat16* w1;
  const __nv_bfloat16* w2;
  const __nv_bfloat16* wo;
  __nv_bfloat16* out;
};

DEVI uint32_t smem_u32(const void* p) { return (uint32_t)__cvta_generic_to_shared(p); }
DEVI uint32_t clk32() { uint32_t c; asm volatile("mov.u32 %0, %%clock;" : "=r"(c)); return c; }
DEVI void mbar_init(uint32_t bar, uint32_t cnt) { asm volatile("mbarrier.init.shared::cta.b64 [%0], %1;" ::"r"(bar), "r"(cnt)); }
DEVI void mbar_expect_tx(uint32_t bar, uint32_t bytes) { asm volatile("mbarrier.arrive.expect_tx.shared::cta.b64 _, [%0], %1;" ::"r"(bar), "r"(bytes) : "memory"); }
DEVI void mbar_arrive(uint32_t bar) { asm volatile("mbarrier.arrive.shared::cta.b64 _, [%0];" ::"r"(bar) : "memory"); }
DEVI void mbar_arrive_cluster(uint32_t bar, uint32_t cta) {
  asm volatile("{ .reg .b32 ra; mapa.shared::cluster.u32 ra, %0, %1; mbarrier.arrive.shared::cluster.b64 _, [ra]; }" ::"r"(bar), "r"(cta) : "memory");
}
DEVI void mbar_wait(uint32_t bar, uint32_t parity, uint32_t t0) {
  asm volatile("{ .reg .pred p; .reg .u32 c;\n"
               "mbarrier.try_wait.parity.shared::cta.b64 p, [%0], %1;\n"
               "@p bra DONE_%=;\n"
               "WAIT_%=:\n"
               "mbarrier.try_wait.parity.shared::cta.b64 p, [%0], %1, %4;\n"
               "@p bra DONE_%=;\n"
               "mov.u32 c, %%clock; sub.u32 c, c, %2; setp.lt.u32 p, c, %3;\n"
               "@p bra WAIT_%=;\n"
               "DONE_%=: }" ::"r"(bar), "r"(parity), "r"(t0), "n"(TIMEOUT), "r"(WAIT_HINT_NS) : "memory");
}
DEVI unsigned ld_relaxed(const unsigned* p) { unsigned v; asm volatile("ld.relaxed.gpu.global.u32 %0, [%1];" : "=r"(v) : "l"(p) : "memory"); return v; }
DEVI void flag_wait(const unsigned* p, unsigned target, uint32_t t0) {
  while ((int)(ld_relaxed(p) - target) < 0) { if (clk32() - t0 > TIMEOUT) break; }
}
DEVI void flag_add(unsigned* p) {
  asm volatile("fence.proxy.async.global;\n red.release.gpu.global.add.u32 [%0], 1;" ::"l"(p) : "memory");
}
DEVI void fence_async_smem() { asm volatile("fence.proxy.async.shared::cta;" ::: "memory"); }
DEVI void fence_async_global() {
  asm volatile("fence.acquire.gpu;" ::: "memory");
  asm volatile("fence.proxy.async.global;" ::: "memory");
}
DEVI void tma_load_2d(uint32_t dst, const CUtensorMap* m, int c0, int c1, uint32_t bar) {
  asm volatile("cp.async.bulk.tensor.2d.shared::cluster.global.mbarrier::complete_tx::bytes [%0], [%1, {%3, %4}], [%2];" ::"r"(dst), "l"(m), "r"(bar), "r"(c0), "r"(c1) : "memory");
}
DEVI void tma_load_3d(uint32_t dst, const CUtensorMap* m, int c0, int c1, int c2, uint32_t bar) {
  asm volatile("cp.async.bulk.tensor.3d.shared::cluster.global.mbarrier::complete_tx::bytes [%0], [%1, {%3, %4, %5}], [%2];"
               ::"r"(dst), "l"(m), "r"(bar), "r"(c0), "r"(c1), "r"(c2) : "memory");
}
DEVI void tma_load_3d_mc(uint32_t dst, const CUtensorMap* m, int c0, int c1, int c2, uint32_t bar) {
  asm volatile("cp.async.bulk.tensor.3d.shared::cluster.global.mbarrier::complete_tx::bytes.multicast::cluster [%0], [%1, {%3, %4, %5}], [%2], %6;"
               ::"r"(dst), "l"(m), "r"(bar), "r"(c0), "r"(c1), "r"(c2), "h"((uint16_t)3) : "memory");
}
DEVI void tma_load_4d_mc(uint32_t dst, const CUtensorMap* m, int c0, int c1, int c2, int c3, uint32_t bar) {
  asm volatile("cp.async.bulk.tensor.4d.shared::cluster.global.mbarrier::complete_tx::bytes.multicast::cluster [%0], [%1, {%3, %4, %5, %6}], [%2], %7;"
               ::"r"(dst), "l"(m), "r"(bar), "r"(c0), "r"(c1), "r"(c2), "r"(c3), "h"((uint16_t)3) : "memory");
}
DEVI void tma_store_2d(const CUtensorMap* m, int c0, int c1, uint32_t src) {
  asm volatile("cp.async.bulk.tensor.2d.global.shared::cta.bulk_group [%0, {%1, %2}], [%3];" ::"l"(m), "r"(c0), "r"(c1), "r"(src) : "memory");
}
DEVI void bulk_store(void* dst, uint32_t src, uint32_t bytes) {
  asm volatile("cp.async.bulk.global.shared::cta.bulk_group [%0], [%1], %2;" ::"l"(dst), "r"(src), "r"(bytes) : "memory");
}
DEVI void bulk_load(uint32_t dst, const void* src, uint32_t bytes, uint32_t bar) {
  asm volatile("cp.async.bulk.shared::cluster.global.mbarrier::complete_tx::bytes [%0], [%1], %2, [%3];" ::"r"(dst), "l"(src), "r"(bytes), "r"(bar) : "memory");
}
DEVI void bulk_commit() { asm volatile("cp.async.bulk.commit_group;" ::: "memory"); }
DEVI void bulk_wait_all() { asm volatile("cp.async.bulk.wait_group 0;" ::: "memory"); }
DEVI void l2_prefetch(const void* p, uint32_t bytes) { asm volatile("cp.async.bulk.prefetch.L2.global [%0], %1;" ::"l"(p), "r"(bytes) : "memory"); }
DEVI void cluster_arrive() { asm volatile("barrier.cluster.arrive.relaxed.aligned;" ::: "memory"); }
DEVI void cluster_wait() { asm volatile("barrier.cluster.wait.aligned;" ::: "memory"); }
template <int ID> DEVI void named_bar(int n) { asm volatile("bar.sync %0, %1;" ::"n"(ID), "r"(n) : "memory"); }
DEVI void wg_bar(int wg) { if (wg == 0) named_bar<1>(128); else named_bar<2>(128); }
DEVI void wgmma_fence() { asm volatile("wgmma.fence.sync.aligned;" ::: "memory"); }
DEVI void wgmma_commit() { asm volatile("wgmma.commit_group.sync.aligned;" ::: "memory"); }
template <int N> DEVI void wgmma_wait() { asm volatile("wgmma.wait_group.sync.aligned %0;" ::"n"(N) : "memory"); }
template <uint32_t LBO> DEVI uint64_t desc_sw128(uint32_t a16) {
  return ((uint64_t)(0x40000000u | (1024 >> 4)) << 32) | (a16 + ((LBO >> 4) << 16));
}
DEVI uint64_t desc_sw64(uint32_t a16) {
  return ((uint64_t)(0x80000000u | (512 >> 4)) << 32) | (a16 + ((512 >> 4) << 16));
}
DEVI uint32_t pack_bf16(float lo, float hi) { uint32_t r; asm("cvt.rn.bf16x2.f32 %0, %1, %2;" : "=r"(r) : "f"(hi), "f"(lo)); return r; }
DEVI void stsm_x4(uint32_t addr, uint32_t r0, uint32_t r1, uint32_t r2, uint32_t r3) {
  asm volatile("stmatrix.sync.aligned.m8n8.x4.shared.b16 [%0], {%1, %2, %3, %4};" ::"r"(addr), "r"(r0), "r"(r1), "r"(r2), "r"(r3) : "memory");
}
DEVI void sts128(uint32_t addr, uint32_t r0, uint32_t r1, uint32_t r2, uint32_t r3) {
  asm volatile("st.shared.v4.b32 [%0], {%1, %2, %3, %4};" ::"r"(addr), "r"(r0), "r"(r1), "r"(r2), "r"(r3) : "memory");
}
DEVI uint4 lds128(uint32_t addr) {
  uint4 v; asm volatile("ld.shared.v4.b32 {%0, %1, %2, %3}, [%4];" : "=r"(v.x), "=r"(v.y), "=r"(v.z), "=r"(v.w) : "r"(addr) : "memory"); return v;
}
DEVI float ex2(float x) { float y; asm("ex2.approx.ftz.f32 %0, %1;" : "=f"(y) : "f"(x)); return y; }

DEVI void wgmma_ss_n64(float (&d)[32], uint64_t da, uint64_t db) {
  asm volatile("wgmma.mma_async.sync.aligned.m64n64k16.f32.bf16.bf16 {%0, %1, %2, %3, %4, %5, %6, %7, %8, %9, %10, %11, %12, %13, %14, %15, %16, %17, %18, %19, %20, %21, %22, %23, %24, %25, %26, %27, %28, %29, %30, %31}, %32, %33, 1, 1, 1, 0, 1;"
    : "+f"(d[0]), "+f"(d[1]), "+f"(d[2]), "+f"(d[3]), "+f"(d[4]), "+f"(d[5]), "+f"(d[6]), "+f"(d[7]), "+f"(d[8]), "+f"(d[9]), "+f"(d[10]), "+f"(d[11]), "+f"(d[12]), "+f"(d[13]), "+f"(d[14]), "+f"(d[15]), "+f"(d[16]), "+f"(d[17]), "+f"(d[18]), "+f"(d[19]), "+f"(d[20]), "+f"(d[21]), "+f"(d[22]), "+f"(d[23]), "+f"(d[24]), "+f"(d[25]), "+f"(d[26]), "+f"(d[27]), "+f"(d[28]), "+f"(d[29]), "+f"(d[30]), "+f"(d[31])
    : "l"(da), "l"(db));
}
DEVI void wgmma_ss_n128(float (&d)[64], uint64_t da, uint64_t db) {
  asm volatile("wgmma.mma_async.sync.aligned.m64n128k16.f32.bf16.bf16 {%0, %1, %2, %3, %4, %5, %6, %7, %8, %9, %10, %11, %12, %13, %14, %15, %16, %17, %18, %19, %20, %21, %22, %23, %24, %25, %26, %27, %28, %29, %30, %31, %32, %33, %34, %35, %36, %37, %38, %39, %40, %41, %42, %43, %44, %45, %46, %47, %48, %49, %50, %51, %52, %53, %54, %55, %56, %57, %58, %59, %60, %61, %62, %63}, %64, %65, 1, 1, 1, 0, 1;"
    : "+f"(d[0]), "+f"(d[1]), "+f"(d[2]), "+f"(d[3]), "+f"(d[4]), "+f"(d[5]), "+f"(d[6]), "+f"(d[7]), "+f"(d[8]), "+f"(d[9]), "+f"(d[10]), "+f"(d[11]), "+f"(d[12]), "+f"(d[13]), "+f"(d[14]), "+f"(d[15]), "+f"(d[16]), "+f"(d[17]), "+f"(d[18]), "+f"(d[19]), "+f"(d[20]), "+f"(d[21]), "+f"(d[22]), "+f"(d[23]), "+f"(d[24]), "+f"(d[25]), "+f"(d[26]), "+f"(d[27]), "+f"(d[28]), "+f"(d[29]), "+f"(d[30]), "+f"(d[31]), "+f"(d[32]), "+f"(d[33]), "+f"(d[34]), "+f"(d[35]), "+f"(d[36]), "+f"(d[37]), "+f"(d[38]), "+f"(d[39]), "+f"(d[40]), "+f"(d[41]), "+f"(d[42]), "+f"(d[43]), "+f"(d[44]), "+f"(d[45]), "+f"(d[46]), "+f"(d[47]), "+f"(d[48]), "+f"(d[49]), "+f"(d[50]), "+f"(d[51]), "+f"(d[52]), "+f"(d[53]), "+f"(d[54]), "+f"(d[55]), "+f"(d[56]), "+f"(d[57]), "+f"(d[58]), "+f"(d[59]), "+f"(d[60]), "+f"(d[61]), "+f"(d[62]), "+f"(d[63])
    : "l"(da), "l"(db));
}
DEVI void wgmma_qk64(float (&d)[32], uint32_t a0, uint32_t a1, uint32_t a2, uint32_t a3, uint64_t db) {
  asm volatile("wgmma.mma_async.sync.aligned.m64n64k16.f32.bf16.bf16 {%0, %1, %2, %3, %4, %5, %6, %7, %8, %9, %10, %11, %12, %13, %14, %15, %16, %17, %18, %19, %20, %21, %22, %23, %24, %25, %26, %27, %28, %29, %30, %31}, {%32, %33, %34, %35}, %36, 0, 1, 1, 0;"
    : "=f"(d[0]), "=f"(d[1]), "=f"(d[2]), "=f"(d[3]), "=f"(d[4]), "=f"(d[5]), "=f"(d[6]), "=f"(d[7]), "=f"(d[8]), "=f"(d[9]), "=f"(d[10]), "=f"(d[11]), "=f"(d[12]), "=f"(d[13]), "=f"(d[14]), "=f"(d[15]), "=f"(d[16]), "=f"(d[17]), "=f"(d[18]), "=f"(d[19]), "=f"(d[20]), "=f"(d[21]), "=f"(d[22]), "=f"(d[23]), "=f"(d[24]), "=f"(d[25]), "=f"(d[26]), "=f"(d[27]), "=f"(d[28]), "=f"(d[29]), "=f"(d[30]), "=f"(d[31])
    : "r"(a0), "r"(a1), "r"(a2), "r"(a3), "l"(db));
}
DEVI void wgmma_pv(float (&d)[8], uint32_t a0, uint32_t a1, uint32_t a2, uint32_t a3, uint64_t db) {
  asm volatile("wgmma.mma_async.sync.aligned.m64n16k16.f32.bf16.bf16 {%0, %1, %2, %3, %4, %5, %6, %7}, {%8, %9, %10, %11}, %12, 1, 1, 1, 1;"
    : "+f"(d[0]), "+f"(d[1]), "+f"(d[2]), "+f"(d[3]), "+f"(d[4]), "+f"(d[5]), "+f"(d[6]), "+f"(d[7])
    : "r"(a0), "r"(a1), "r"(a2), "r"(a3), "l"(db));
}
DEVI void wgmma_pv0(float (&d)[8], uint32_t a0, uint32_t a1, uint32_t a2, uint32_t a3, uint64_t db) {
  asm volatile("wgmma.mma_async.sync.aligned.m64n16k16.f32.bf16.bf16 {%0, %1, %2, %3, %4, %5, %6, %7}, {%8, %9, %10, %11}, %12, 0, 1, 1, 1;"
    : "=f"(d[0]), "=f"(d[1]), "=f"(d[2]), "=f"(d[3]), "=f"(d[4]), "=f"(d[5]), "=f"(d[6]), "=f"(d[7])
    : "r"(a0), "r"(a1), "r"(a2), "r"(a3), "l"(db));
}


template <int N> struct Acc { float a[64]; float b[(N - 128) / 2]; DEVI float& operator[](int i) { return i < 64 ? a[i] : b[i - 64]; } };
template <> struct Acc<128> { float a[64]; DEVI float& operator[](int i) { return a[i]; } };
template <int N> DEVI void wgmma_ss(Acc<N>& d, uint64_t da, uint64_t db) {
  wgmma_ss_n128(d.a, da, db);
  if constexpr (N == 192) wgmma_ss_n64(d.b, da, db + 256);
  if constexpr (N == 256) wgmma_ss_n128(d.b, da, db + 256);
}

DEVI int oh_chunk(int j, int i, int& need) {
  if (i >= 3 && i < 5) { const int e = (j & 1) * 2 + i - 3; need = 16 + 2 * e; return 24 + e; }
  if (i >= 5) i -= 2;
  int o, r;
  if (i >= 12) { o = (j + 5) & 7; r = i - 11; }
  else { const int g = i / 3; o = (j + 2 * g) & 7; r = i - 3 * g; }
  need = o;
  return 3 * o + r;
}

DEVI int a_slot(int e) { return 1 + (e & 3); }

struct Ctx {
  uint32_t sbase, bars, peer, t0, a16, b16;
  int wg, lane;
  int ai, bi; uint32_t aph, bph;
  int brem, ae;
  int pa, pb;
};

DEVI void release_prev(Ctx& c) {
  if (c.pb >= 0) {
    if (c.lane == 0) mbar_arrive(c.bars + 8 * (BAR_EMPTYB + c.pb));
    if (c.lane == 1) mbar_arrive_cluster(c.bars + 8 * (BAR_EMPTYB + c.pb), c.peer);
  }
  if (c.pa >= 0 && c.lane == 2) mbar_arrive(c.bars + 8 * (BAR_EMPTYA + c.pa));
}

DEVI void gemm_wait(Ctx& c) {
  asm volatile("{ .reg .pred p, q; .reg .u32 c;\n"
               "mbarrier.try_wait.parity.shared::cta.b64 p, [%0], %1;\n"
               "mbarrier.try_wait.parity.shared::cta.b64 q, [%2], %3;\n"
               "and.pred p, p, q;\n"
               "@p bra DONE_%=;\n"
               "WAIT_%=:\n"
               "mbarrier.try_wait.parity.shared::cta.b64 p, [%0], %1, %6;\n"
               "mbarrier.try_wait.parity.shared::cta.b64 q, [%2], %3, %6;\n"
               "and.pred p, p, q;\n"
               "@p bra DONE_%=;\n"
               "mov.u32 c, %%clock; sub.u32 c, c, %4; setp.lt.u32 p, c, %5;\n"
               "@p bra WAIT_%=;\n"
               "DONE_%=: }" ::"r"(c.bars + 8 * (BAR_FULLA + c.ai)), "r"((c.aph >> c.ai) & 1), "r"(c.bars + 8 * (BAR_FULLB + c.bi)), "r"(c.bph), "r"(c.t0),
               "n"(TIMEOUT), "r"(WAIT_HINT_NS) : "memory");
}
template <int N, bool SHALLOW>
DEVI void gemm_group(Acc<N>& acc, Ctx& c, int g, int& npa, int& npb) {
  const uint32_t a16 = c.a16 + c.ai * (SLOT >> 4);
  const uint32_t b16 = c.b16 + c.bi * (SLOT >> 4);
  bool adv;
  if constexpr (N >= 192) {
    const uint32_t a2 = a16 + (g & 1) * 4;
    wgmma_ss<N>(acc, desc_sw128<16>(a2), desc_sw128<2048>(b16));
    if (SHALLOW) { wgmma_commit(); wgmma_wait<0>(); }
    wgmma_ss<N>(acc, desc_sw128<16>(a2 + 2), desc_sw128<2048>(b16 + 512));
    adv = g & 1;
  } else {
#pragma unroll
    for (int s = 0; s < 4; s++) {
      wgmma_ss<N>(acc, desc_sw128<16>(a16 + s * 2), desc_sw128<4096>(b16 + (s >> 1) * 512 + (s & 1) * 128));
      if (SHALLOW && s < 3) { wgmma_commit(); wgmma_wait<0>(); }
    }
    adv = true;
  }
  wgmma_commit();
  npb = c.brem > 0 ? c.bi : -1;
  c.brem--;
  if (++c.bi == NB) { c.bi = 0; c.bph ^= 1; }
  npa = -1;
  if (adv) { npa = c.ai; c.aph ^= 1u << c.ai; c.ae++; c.ai = 1 + (c.ae & 3); }
}

template <int N, bool SHALLOW = false>
DEVI void bare_groups(Acc<N>& acc, Ctx& c, int g0, int g1) {
  for (int g = g0; g < g1; g++) {
    int npa, npb;
    gemm_wait(c);
    wgmma_fence();
    gemm_group<N, SHALLOW>(acc, c, g, npa, npb);
    wgmma_wait<SHALLOW ? 0 : 1>();
    if (SHALLOW) { c.pa = npa; c.pb = npb; }
    release_prev(c);
    c.pa = SHALLOW ? -1 : npa; c.pb = SHALLOW ? -1 : npb;
  }
}
DEVI void drain(Ctx& c) {
  wgmma_wait<0>();
  release_prev(c);
  c.pa = c.pb = -1;
}

constexpr float SC = 0.25f * 1.4426950408889634f;

#define ONCE _Pragma("unroll 1") for (unsigned once_ = 0; once_ < gridDim.y; once_++)

struct Gate { float g0, g1; };

DEVI void kill32(float (&S)[32]) {
#pragma unroll
  for (int i = 0; i < 32; i++) S[i] = __int_as_float(0xff800000);
}
DEVI void row_max(const float (&S)[32], float& x0, float& x1) {
  float y0 = S[1], y1 = S[3];
  x0 = fmaxf(x0, S[0]); x1 = fmaxf(x1, S[2]);
#pragma unroll
  for (int n = 1; n < 8; n++) {
    x0 = fmaxf(x0, S[4 * n]); y0 = fmaxf(y0, S[4 * n + 1]); x1 = fmaxf(x1, S[4 * n + 2]); y1 = fmaxf(y1, S[4 * n + 3]);
  }
  x0 = fmaxf(x0, y0); x1 = fmaxf(x1, y1);
}
DEVI void quad_max(float& x0, float& x1) {
  x0 = fmaxf(x0, __shfl_xor_sync(0xffffffffu, x0, 1)); x1 = fmaxf(x1, __shfl_xor_sync(0xffffffffu, x1, 1));
  x0 = fmaxf(x0, __shfl_xor_sync(0xffffffffu, x0, 2)); x1 = fmaxf(x1, __shfl_xor_sync(0xffffffffu, x1, 2));
}
DEVI void exp32(const float (&S)[32], float (&E)[32], float n0, float n1, float (&l)[4]) {
#pragma unroll
  for (int i = 0; i < 32; i++) { E[i] = ex2(fmaf(S[i], SC, (i & 2) ? n1 : n0)); l[i & 3] += E[i]; }
}
DEVI void pack32(const float (&E)[32], uint32_t (&P)[16]) {
#pragma unroll
  for (int i = 0; i < 16; i++) P[i] = pack_bf16(E[2 * i], E[2 * i + 1]);
}
template <bool FIRST> DEVI void pv4(float (&O)[8], const uint32_t (&P)[16], uint32_t v16) {
  if (FIRST) wgmma_pv0(O, P[0], P[1], P[2], P[3], desc_sw64(v16)); else wgmma_pv(O, P[0], P[1], P[2], P[3], desc_sw64(v16));
#pragma unroll
  for (int k = 1; k < 4; k++) wgmma_pv(O, P[4 * k], P[4 * k + 1], P[4 * k + 2], P[4 * k + 3], desc_sw64(v16 + k * 64));
}
DEVI bool wg_any(int wg, bool v) {
  uint32_t r;
  if (wg == 0) asm volatile("{ .reg .pred p, q; setp.ne.u32 p, %1, 0; bar.red.or.pred q, 4, 128, p; selp.u32 %0, 1, 0, q; }" : "=r"(r) : "r"((uint32_t)v) : "memory");
  else asm volatile("{ .reg .pred p, q; setp.ne.u32 p, %1, 0; bar.red.or.pred q, 5, 128, p; selp.u32 %0, 1, 0, q; }" : "=r"(r) : "r"((uint32_t)v) : "memory");
  return r != 0;
}
DEVI void get_gate(Gate& g, uint32_t sbase, int row16, int lane, uint32_t t0) {
  mbar_wait(sbase + OFF_BAR + 8 * BAR_GIN, 0, t0);
  const uint32_t a = sbase + OFF_GIN + (row16 * 16 + (lane >> 2)) * 4;
  asm volatile("ld.shared.f32 %0, [%1];" : "=f"(g.g0) : "r"(a) : "memory");
  asm volatile("ld.shared.f32 %0, [%1];" : "=f"(g.g1) : "r"(a + 32) : "memory");
}

DEVI void attention(uint32_t sbase, int aw, int wi, int lane, int rb, uint32_t t0) {
  const uint32_t bars = sbase + OFF_BAR;
  const uint32_t kvb = ((sbase & 0x3FFFF) + OFF_KV + aw * 4096) >> 4;
  const int cmin = 4 - 2 * rb - aw;
  const int rowc = wi * 16 + (lane >> 2) - (lane & 3) * 2;
  const uint32_t qst = sbase + OFF_A + aw * 8192;
  const float NINF = __int_as_float(0xff800000);
  const int tlo = max(cmin, 1);
#pragma unroll 1
  for (int h = 0; h < 4; h++) {
    const uint32_t kb = kvb + (h & 1) * (KVBUF >> 4);
    const uint4 q = lds128(qst + h * 2048 + (wi * 32 + lane) * 16);
    float O[8], l0, l1;
    uint32_t nm;
    asm volatile("ld.shared.u32 %0, [%1];" : "=r"(nm) : "r"(sbase + OFF_NM + ((aw * 4 + wi) * 32 + (lane & 28) + h) * 4) : "memory");
    float n0 = __uint_as_float(nm << 16), n1 = __uint_as_float(nm & 0xffff0000u);
    mbar_wait(bars + 8 * (BAR_KVFULL + (h & 1)), h >> 1, t0);
#pragma unroll 1
    for (int attempt = 0; attempt < 2; attempt++) {
      float l[4] = {0.f, 0.f, 0.f, 0.f};
      uint32_t P[16];
      {
        float S[32], F[32];
        wgmma_fence();
        wgmma_qk64(S, q.x, q.y, q.z, q.w, desc_sw64(kb + 4 * 256));
        wgmma_qk64(F, q.x, q.y, q.z, q.w, desc_sw64(kb));
        wgmma_commit();
        wgmma_wait<0>();
        for (int r = 0; r < (cmin > 0 ? 1 : 0); r++) kill32(F);
        float M[32];
#pragma unroll
        for (int i = 0; i < 32; i++) M[i] = ((i >> 2) * 8 + (i & 1) > rowc + (i & 2) * 4) ? F[i] : S[i];
        for (int r = 0; r < attempt; r++) {
          row_max(M, n0, n1);
          quad_max(n0, n1);
          n0 *= -SC; n1 *= -SC;
        }
        exp32(M, M, n0, n1, l);
        pack32(M, P);
        uint32_t PF[16];
#pragma unroll
        for (int i = 0; i < 16; i++) {
          const int col = (i >> 1) * 8, r = rowc + (i & 1) * 8;
          const uint32_t m = (col > r ? 0xFFFFu : 0u) | (col + 1 > r ? 0xFFFF0000u : 0u);
          PF[i] = P[i] & m; P[i] &= ~m;
        }
        wgmma_fence();
        pv4<true>(O, PF, kb + 2);
        wgmma_commit();
        wgmma_wait<0>();
      }
      int t = 3;
#pragma unroll 1
      for (; t >= tlo; t--) {
        float S[32];
        wgmma_fence();
        wgmma_qk64(S, q.x, q.y, q.z, q.w, desc_sw64(kb + t * 256));
        wgmma_commit();
        pv4<false>(O, P, kb + (t + 1) * 256 + 2);
        wgmma_commit();
        wgmma_wait<1>();
        ONCE { exp32(S, S, n0, n1, l); }
        wgmma_wait<0>();
        pack32(S, P);
      }
      wgmma_fence();
      pv4<false>(O, P, kb + (t + 1) * 256 + 2);
      wgmma_commit();
      l0 = l[0] + l[1]; l1 = l[2] + l[3];
      l0 += __shfl_xor_sync(0xffffffffu, l0, 1); l1 += __shfl_xor_sync(0xffffffffu, l1, 1);
      l0 += __shfl_xor_sync(0xffffffffu, l0, 2); l1 += __shfl_xor_sync(0xffffffffu, l1, 2);
      const bool redo = wg_any(aw, attempt == 0 && !(l0 > 1e-6f && l0 < 1e18f && l1 > 1e-6f && l1 < 1e18f));
      wgmma_wait<0>();
      if (!redo) break;
      n0 = NINF; n1 = NINF;
#pragma unroll 1
      for (int u = 3; u >= tlo; u--) {
        float S[32];
        wgmma_fence();
        wgmma_qk64(S, q.x, q.y, q.z, q.w, desc_sw64(kb + u * 256));
        wgmma_commit();
        wgmma_wait<0>();
        row_max(S, n0, n1);
      }
    }
    if (lane == 0) mbar_arrive(bars + 8 * (BAR_KVEMPTY + (h & 1)));
    Gate g;
    get_gate(g, sbase, aw * 4 + wi, lane, t0);
    const float c0 = __fdividef(g.g0, l0), c1 = __fdividef(g.g1, l1);
    const int mi = lane >> 3;
    const int srow = wi * 16 + (lane & 7) + 8 * (mi & 1);
    stsm_x4(qst + h * 2048 + srow * 32 + (mi >> 1) * 16, pack_bf16(O[0] * c0, O[1] * c0), pack_bf16(O[2] * c1, O[3] * c1),
            pack_bf16(O[4] * c0, O[5] * c0), pack_bf16(O[6] * c1, O[7] * c1));
    fence_async_smem();
    __syncwarp();
    if (lane == 0) mbar_arrive(bars + 8 * (BAR_OST + h));
  }
}

template <int CH, int N>
DEVI void store_h_chunk(Acc<N>& acc, uint32_t base  , int lane, float s0, float s1) {
  const int mi = lane >> 3;
#pragma unroll
  for (int tp = 0; tp < 4; tp++) {
    const int t = CH * 8 + tp * 2;
    const uint32_t r0 = pack_bf16(fmaxf(acc[4 * t + 0], 0.f) * s0, fmaxf(acc[4 * t + 1], 0.f) * s0);
    const uint32_t r1 = pack_bf16(fmaxf(acc[4 * t + 2], 0.f) * s1, fmaxf(acc[4 * t + 3], 0.f) * s1);
    const uint32_t r2 = pack_bf16(fmaxf(acc[4 * t + 4], 0.f) * s0, fmaxf(acc[4 * t + 5], 0.f) * s0);
    const uint32_t r3 = pack_bf16(fmaxf(acc[4 * t + 6], 0.f) * s1, fmaxf(acc[4 * t + 7], 0.f) * s1);
    stsm_x4(base + (((tp * 2 + (mi >> 1)) ^ (lane & 7)) << 4), r0, r1, r2, r3);
  }
}

template <int N>
DEVI void phase_q(Ctx& c, int warp) {
  Acc<N> acc;
#pragma unroll
  for (int i = 0; i < N / 2; i++) acc[i] = 0.f;
  bare_groups<N>(acc, c, 0, 16);
  drain(c);
  const int lane = c.lane, mi = lane >> 3;
  const int row = warp * 16 + (lane & 7) + 8 * (mi & 1);
  const int sw = (row >> 1) & 3;
#pragma unroll
  for (int hh = 0; hh < 4; hh++) {
    const uint32_t base = c.sbase + OFF_KV + hh * 8192 + row * 64;
#pragma unroll
    for (int kv = 0; kv < 2; kv++) {
      const int t = 8 + kv * 8 + 2 * hh;
      stsm_x4(base + (((kv * 2 + (mi >> 1)) ^ sw) << 4),
              pack_bf16(acc[4 * t + 0], acc[4 * t + 1]), pack_bf16(acc[4 * t + 2], acc[4 * t + 3]),
              pack_bf16(acc[4 * t + 4], acc[4 * t + 5]), pack_bf16(acc[4 * t + 6], acc[4 * t + 7]));
    }
  }
  fence_async_smem();
  __syncwarp();
  if (lane == 0) mbar_arrive(c.bars + 8 * BAR_STG);
#pragma unroll
  for (int hh = 0; hh < 4; hh++)
    sts128(c.sbase + OFF_A + c.wg * 8192 + hh * 2048 + ((warp & 3) * 32 + lane) * 16,
           pack_bf16(acc[8 * hh], acc[8 * hh + 1]), pack_bf16(acc[8 * hh + 2], acc[8 * hh + 3]),
           pack_bf16(acc[8 * hh + 4], acc[8 * hh + 5]), pack_bf16(acc[8 * hh + 6], acc[8 * hh + 7]));
#pragma unroll
  for (int hh = 0; hh < 4; hh++) {
    const int q = 8 * hh, k = 32 + 8 * hh;
    float d0 = acc[q] * acc[k] + acc[q + 1] * acc[k + 1] + acc[q + 4] * acc[k + 4] + acc[q + 5] * acc[k + 5];
    float d1 = acc[q + 2] * acc[k + 2] + acc[q + 3] * acc[k + 3] + acc[q + 6] * acc[k + 6] + acc[q + 7] * acc[k + 7];
    d0 += __shfl_xor_sync(0xffffffffu, d0, 1); d1 += __shfl_xor_sync(0xffffffffu, d1, 1);
    d0 += __shfl_xor_sync(0xffffffffu, d0, 2); d1 += __shfl_xor_sync(0xffffffffu, d1, 2);
    if ((lane & 3) == hh)
      asm volatile("st.shared.u32 [%0], %1;" ::"r"(c.sbase + OFF_NM + (warp * 32 + lane) * 4), "r"(pack_bf16(-d0 * SC, -d1 * SC)) : "memory");
  }
  __syncwarp();
  if (lane == 0) mbar_arrive(c.bars + 8 * (BAR_QRDY + c.wg));
  if constexpr (N == 256) {
    Gate g;
    get_gate(g, c.sbase, warp, lane, c.t0);
    store_h_chunk<3>(acc, c.sbase + OFF_KV + 32768 + row * 128, lane, 1.f - g.g0, 1.f - g.g1);
    fence_async_smem();
    __syncwarp();
    if (lane == 0) mbar_arrive(c.bars + 8 * BAR_STE);
  }
}

DEVI void first_loads(const Params& P, uint32_t sbase, int e, int j, int rb) {
  const uint32_t bars = sbase + OFF_BAR, fb = bars + 8 * (BAR_FULLB + e), fa = bars + 8 * (BAR_FULLA + 1 + e);
  mbar_expect_tx(fa, 16384);
  mbar_expect_tx(fb, (j & 1) ? 12288 : 16384);
  if (e == 0) tma_load_2d(sbase + OFF_A + SLOT, &P.tmX, 0, rb * 128, fa);
#pragma unroll
  for (int r = 0; r < 2; r++) {
    tma_load_3d(sbase + OFF_B + e * SLOT + r * 8192, &P.tmWqkv, 64 * j, e * 32 + r * 16, 0, fb);
    if (!(j & 1)) tma_load_3d(sbase + OFF_B + e * SLOT + r * 8192 + 6144, &P.tmW1a, 0, e * 32 + r * 16, 24 + (j >> 1), fb);
  }
  if (e == 1) tma_load_2d(sbase + OFF_A + 2 * SLOT, &P.tmX, 64, rb * 128, fa);
}

__global__ void __cluster_dims__(2, 1, 1) __launch_bounds__(640, 1) fused_kernel(const __grid_constant__ Params P) {
  extern __shared__ __align__(1024) uint8_t smem_raw[];
  const uint32_t sbase = smem_u32(smem_raw);
  const uint32_t bars = sbase + OFF_BAR;
  const int tid = threadIdx.x, warp = tid >> 5, lane = tid & 31;
  const uint32_t rank = blockIdx.x & 1, peer = rank ^ 1;
  const int j = (blockIdx.x >> 1) & 7, rb = ((blockIdx.x >> 4) << 1) | rank;
  const uint32_t t0 = clk32();

  const int typeB = j & 1;
  if (tid == 544) {
    for (int s = 0; s < NA; s++) mbar_init(bars + 8 * (BAR_FULLA + s), 1);
    for (int s = 0; s < NB; s++) mbar_init(bars + 8 * (BAR_FULLB + s), 1);
    fence_async_smem();
  } else if (tid < 8) {
    asm volatile("prefetch.tensormap [%0];" ::"l"(&P.tmX + tid) : "memory");
  } else if (tid == 512) {
    for (int s = 0; s < NA; s++) mbar_init(bars + 8 * (BAR_EMPTYA + s), 9);
    for (int s = 0; s < NB; s++) mbar_init(bars + 8 * (BAR_EMPTYB + s), 16);
  } else if (tid == 576) {
    for (int s = 0; s < 2; s++) { mbar_init(bars + 8 * (BAR_KVFULL + s), 1); mbar_init(bars + 8 * (BAR_KVEMPTY + s), 8); mbar_init(bars + 8 * (BAR_OST + s), 8); mbar_init(bars + 8 * (BAR_OST + 2 + s), 8); mbar_init(bars + 8 * (BAR_QRDY + s), 4); }
    mbar_init(bars + 8 * BAR_STG, 8); mbar_init(bars + 8 * BAR_STE, 8); mbar_init(bars + 8 * BAR_KVOK, 1);
    mbar_init(bars + 8 * BAR_PIN, 1); mbar_init(bars + 8 * BAR_PFREE, 8); mbar_init(bars + 8 * BAR_GIN, 1);
  }
  if (tid >= 512 && lane == 0) asm volatile("fence.mbarrier_init.release.cluster;" ::: "memory");
  const unsigned ep1 = ld_relaxed(&g_epoch) + 1;
  __syncwarp();
  cluster_arrive();
  if (tid == 544) { first_loads(P, sbase, 0, j, rb); first_loads(P, sbase, 1, j, rb); }
  __syncwarp();

  const int on = 12 + 4 * typeB;

  if (warp < 8) {
    asm volatile("setmaxnreg.inc.sync.aligned.u32 160;");
    cluster_wait();
    const int wg = __shfl_sync(0xffffffffu, warp >> 2, 0);
    Ctx c{sbase, bars, peer, t0, ((sbase & 0x3FFFF) + OFF_A + wg * 8192) >> 4, ((sbase & 0x3FFFF) + OFF_B) >> 4, wg, lane, 1, 0, 0u, 0u, 32 + on + 4 - NB, 0, -1, -1};
    if (typeB) phase_q<192>(c, warp);
    else phase_q<256>(c, warp);
    asm volatile("setmaxnreg.dec.sync.aligned.u32 128;");
    {
      Acc<192> acc;
#pragma unroll
      for (int i = 0; i < 96; i++) acc[i] = 0.f;
      bare_groups<192>(acc, c, 0, SHS);
      drain(c);
      bare_groups<192, true>(acc, c, SHS, 16);
      Gate at;
      get_gate(at, sbase, warp, lane, t0);
      drain(c);
      const uint32_t rowoff = (warp * 16 + (lane & 7) + 8 * ((lane >> 3) & 1)) * 128;
      const float s0 = 1.f - at.g0, s1 = 1.f - at.g1;
      constexpr int e0 = 1, e1 = 2, e2 = 3;
      mbar_wait(bars + 8 * (BAR_FULLA + e0), 0, t0);
      store_h_chunk<0>(acc, sbase + OFF_A + e0 * SLOT + rowoff, lane, s0, s1);
      mbar_wait(bars + 8 * (BAR_FULLA + e1), 0, t0);
      store_h_chunk<1>(acc, sbase + OFF_A + e1 * SLOT + rowoff, lane, s0, s1);
      mbar_wait(bars + 8 * (BAR_FULLA + e2), 0, t0);
      store_h_chunk<2>(acc, sbase + OFF_A + e2 * SLOT + rowoff, lane, s0, s1);
    }
    fence_async_smem();
    wg_bar(wg);
    if (lane == 0) mbar_arrive(bars + 8 * BAR_STG);
    float own[32];
    {
      Acc<128> acc;
#pragma unroll
      for (int i = 0; i < 64; i++) acc[i] = 0.f;
      bare_groups<128, true>(acc, c, 0, on);
      drain(c);
      if (lane == 0) mbar_arrive(bars + 8 * BAR_PFREE);
      named_bar<3>(256);
      const uint32_t pst = sbase + OFF_B + ((30 + on) % NB) * SLOT + wg * 8192 + (tid & 127) * 16;
#pragma unroll
      for (int i = 0; i < 4; i++) {
        uint32_t r[4];
#pragma unroll
        for (int k = 0; k < 4; k++) {
          const int idx = 8 * i + 2 * k;
          const float lo = typeB ? acc[idx] : acc[32 + idx], hi = typeB ? acc[idx + 1] : acc[32 + idx + 1];
          r[k] = pack_bf16(lo, hi);
        }
        sts128(pst + i * 2048, r[0], r[1], r[2], r[3]);
      }
#pragma unroll
      for (int i = 0; i < 32; i++) own[i] = typeB ? acc[32 + i] : acc[i];
      fence_async_smem();
      __syncwarp();
      if (lane == 0) mbar_arrive(bars + 8 * BAR_STG);
    }
#pragma unroll 1
    for (int g = 0; g < 8; g++) {
      const uint32_t a16 = c.a16 + c.ai * (SLOT >> 4);
      const uint32_t b16 = c.b16 + c.bi * (SLOT >> 4) + (g & 1) * 512;
      if (g == 6) {
        mbar_wait(bars + 8 * BAR_PIN, 0, t0);
        const uint32_t pin = sbase + OFF_B + ((31 + on) % NB) * SLOT + wg * 8192 + (tid & 127) * 16;
#pragma unroll
        for (int i = 0; i < 4; i++) {
          const uint4 v = lds128(pin + i * 2048);
          const uint32_t r[4] = {v.x, v.y, v.z, v.w};
#pragma unroll
          for (int k = 0; k < 4; k++) { own[8 * i + 2 * k] += __uint_as_float(r[k] << 16); own[8 * i + 2 * k + 1] += __uint_as_float(r[k] & 0xffff0000u); }
        }
        named_bar<3>(256);
      }
      gemm_wait(c);
      wgmma_fence();
#pragma unroll
      for (int s = 0; s < 4; s++) wgmma_ss_n64(own, desc_sw128<16>(a16 + s * 2), desc_sw128<2048>(b16 + s * 128));
      wgmma_commit();
      wgmma_wait<0>();
      if (lane == 2) mbar_arrive(bars + 8 * (BAR_EMPTYA + c.ai));
      c.aph ^= 1u << c.ai;
      c.ae++; c.ai = a_slot(c.ae);
      if (g & 1) { if (++c.bi == NB) { c.bi = 0; c.bph ^= 1; } }
    }
    {
      const uint32_t ob = sbase + OFF_B + ((31 + on) % NB) * SLOT;
      const uint32_t wb = ob + warp * 2048;
      const uint32_t orow = wb + ((lane & 7) + 8 * ((lane >> 3) & 1)) * 128;
#pragma unroll
      for (int i = 0; i < 4; i++)
        stsm_x4(orow + (((i * 2 + (lane >> 4)) ^ (lane & 7)) << 4), pack_bf16(own[8 * i], own[8 * i + 1]), pack_bf16(own[8 * i + 2], own[8 * i + 3]),
                pack_bf16(own[8 * i + 4], own[8 * i + 5]), pack_bf16(own[8 * i + 6], own[8 * i + 7]));
      __syncwarp();
      uint4* o = (uint4*)(P.out + (size_t)(rb * 128 + warp * 16 + (lane >> 3)) * DM + j * 64) + (lane & 7);
#pragma unroll
      for (int i = 0; i < 4; i++) {
        const int r = i * 4 + (lane >> 3);
        o[i * 4 * (DM / 8)] = lds128(wb + r * 128 + (((lane & 7) ^ (r & 7)) << 4));
      }
    }
  } else if (warp < 16) {
    asm volatile("setmaxnreg.dec.sync.aligned.u32 56;");
    cluster_wait();
    const int aw = __shfl_sync(0xffffffffu, (warp >> 2) & 1, 0);
    {
      const int rowg = rb * 128 + j * 16 + (warp - 8) * 2;
      const uint4* gw = (const uint4*)P.gate_w;
      const uint4* xr = (const uint4*)(P.x + (size_t)rowg * DM);
      mbar_wait(bars + 8 * (BAR_FULLB + 1), 0, t0);
      const uint4 w0 = __ldg(gw + lane), w1 = __ldg(gw + 32 + lane);
      const uint4 xa0 = __ldg(xr + lane), xa1 = __ldg(xr + 32 + lane), xb0 = __ldg(xr + 64 + lane), xb1 = __ldg(xr + 96 + lane);
#pragma unroll
      for (int i = 0; i < 4; i++) sts128(sbase + OFF_KV + 32768 + i * 4096 + (tid - 256) * 16, 0u, 0u, 0u, 0u);
      const uint32_t wa[8] = {w0.x, w0.y, w0.z, w0.w, w1.x, w1.y, w1.z, w1.w};
      const uint32_t xa[8] = {xa0.x, xa0.y, xa0.z, xa0.w, xa1.x, xa1.y, xa1.z, xa1.w};
      const uint32_t xb[8] = {xb0.x, xb0.y, xb0.z, xb0.w, xb1.x, xb1.y, xb1.z, xb1.w};
      float za = 0.f, zb = 0.f;
#pragma unroll
      for (int e = 0; e < 8; e++) {
        const float wl = __uint_as_float(wa[e] << 16), wh = __uint_as_float(wa[e] & 0xffff0000u);
        za = fmaf(__uint_as_float(xa[e] << 16), wl, za); za = fmaf(__uint_as_float(xa[e] & 0xffff0000u), wh, za);
        zb = fmaf(__uint_as_float(xb[e] << 16), wl, zb); zb = fmaf(__uint_as_float(xb[e] & 0xffff0000u), wh, zb);
      }
#pragma unroll
      for (int o = 16; o > 0; o >>= 1) { za += __shfl_xor_sync(0xffffffffu, za, o); zb += __shfl_xor_sync(0xffffffffu, zb, o); }
      if (lane < 2) asm volatile("st.shared.f32 [%0], %1;" ::"r"(sbase + OFF_GST + (warp - 8) * 8 + lane * 4), "f"(1.f / (1.f + __expf(-(lane ? zb : za)))) : "memory");
      fence_async_smem();
      named_bar<6>(256);
      if (tid == 256) {
        bulk_store(&g_gate[rb * 128 + j * 16], sbase + OFF_GST, 64);
        bulk_commit(); bulk_wait_all();
        flag_add(&g_flag_g[rb * FS]);
        flag_wait(&g_flag_g[rb * FS], ep1 * 8, t0);
        fence_async_global();
        mbar_expect_tx(bars + 8 * BAR_GIN, 512);
        bulk_load(sbase + OFF_GIN, &g_gate[rb * 128], 512, bars + 8 * BAR_GIN);
      }
      __syncwarp();
    }
    mbar_wait(bars + 8 * (BAR_QRDY + aw), 0, t0);
    asm volatile("setmaxnreg.inc.sync.aligned.u32 96;");
    attention(sbase, aw, warp & 3, lane, rb, t0);
  } else {
    asm volatile("setmaxnreg.dec.sync.aligned.u32 32;");
    if (warp == 16) {
      __syncwarp();
      cluster_wait();
      if (lane == 0) {
        int bi = 2; uint32_t bph = 1;
        const int nb = 32 + on + 4;
        for (int eb = 2; eb < nb; eb++) {
          if (eb == 4 || eb == 6) {
            const int ea = eb >> 1;
            mbar_expect_tx(bars + 8 * (BAR_FULLA + 1 + ea), 16384);
            tma_load_2d(sbase + OFF_A + (1 + ea) * SLOT, &P.tmX, ea * 64, rb * 128, bars + 8 * (BAR_FULLA + 1 + ea));
          }
          const uint32_t fb = bars + 8 * (BAR_FULLB + bi), dst = sbase + OFF_B + bi * SLOT + rank * 8192;
          mbar_wait(bars + 8 * (BAR_EMPTYB + bi), bph, t0);
          if (eb < 16) {
            mbar_expect_tx(fb, typeB ? 12288 : 16384);
            tma_load_3d_mc(dst, &P.tmWqkv, 64 * j, eb * 32 + rank * 16, 0, fb);
            if (!typeB) tma_load_3d_mc(dst + 6144, &P.tmW1a, 0, eb * 32 + rank * 16, 24 + (j >> 1), fb);
          }
          else if (eb < 32) { mbar_expect_tx(fb, 12288); tma_load_3d_mc(dst, &P.tmW1b, 0, (eb - 16) * 32 + rank * 16, 3 * j, fb); }
          else if (eb < 32 + on) { int ow; const int ch = oh_chunk(j, eb - 32, ow); mbar_expect_tx(fb, 16384); tma_load_3d_mc(dst, &P.tmW2, 0, ch * 64 + rank * 32, (j >> 1) * 2, fb); }
          else { mbar_expect_tx(fb, 16384); tma_load_4d_mc(dst, &P.tmWo, 64 * j, 0, eb - 32 - on, rank * 4, fb); }
          if (++bi == NB) { bi = 0; bph ^= 1; }
          if (eb == PFAT) {
            const int b = blockIdx.x;
            l2_prefetch((const uint8_t*)P.w1 + b * 14336, 14336);
          }
          if (eb == PF2) {
            const int b = blockIdx.x;
            l2_prefetch((const uint8_t*)P.w2 + b * 14336, 14336);
            l2_prefetch((const uint8_t*)P.wo + b * 4096, 4096);
          }
        }
        mbar_wait(bars + 8 * BAR_PFREE, 0, t0);
        flag_wait(&g_flag_p[(rb * 8 + j) * FS], ep1, t0);
        fence_async_global();
        mbar_expect_tx(bars + 8 * BAR_PIN, 16384);
        bulk_load(sbase + OFF_B + ((31 + on) % NB) * SLOT, g_part + (size_t)(rb * 8 + j) * 16384, 16384, bars + 8 * BAR_PIN);
      }
    } else if (warp == 17) {
      cluster_wait();
      if (lane == 0) {
        for (int ea = 1; ea < 5; ea++) mbar_arrive(bars + 8 * (BAR_EMPTYA + ea));
        uint32_t aph = 0;
        const int na = 16 + on + 8;
        unsigned ready = 0;
        for (int ea = 4; ea < na; ea++) {
          const int ai = a_slot(ea);
          const uint32_t fb = bars + 8 * (BAR_FULLA + ai), dst = sbase + OFF_A + ai * SLOT;
          int ch = ea & 7, need = -1;
          if (ea >= 16 + on) { need = 8 + ea - 16 - on; ch = 20 + need; }
          else if (ea >= 19) ch = oh_chunk(j, ea - 16, need);
          if (need >= 0 && !((ready >> need) & 1)) {
            const unsigned* fp = need < 8 ? &g_flag_h[rb * 8 * FS] : need < 16 ? &g_flag_o[rb * 8 * FS] : &g_flag_e[rb * 8 * FS];
            const unsigned tgt = (need & 8) ? ep1 * 4 : ep1;
            do {
              unsigned v[8];
#pragma unroll
              for (int i = 0; i < 8; i++) v[i] = ld_relaxed(fp + i * FS);
#pragma unroll
              for (int i = 0; i < 8; i++) if ((int)(v[i] - tgt) >= 0) ready |= 1u << (i + (need & 24));
            } while (!((ready >> need) & 1) && clk32() - t0 < TIMEOUT);
            fence_async_global();
          }
          mbar_wait(bars + 8 * (BAR_EMPTYA + ai), (aph >> ai) & 1, t0);
          if (ea >= 16 && ea < 19) mbar_arrive(fb);
          else {
            mbar_arrive(bars + 8 * (BAR_EMPTYA + ai));
            mbar_expect_tx(fb, 16384);
            tma_load_2d(dst, ea < 16 ? &P.tmX : &P.tmHO, ch * 64, rb * 128, fb);
          }
          aph ^= 1u << ai;
        }
      }
    } else {
      const int wg = warp - 18;
      cluster_wait();
      if (lane == 0 && wg == 0) {
        const uint32_t stg = bars + 8 * BAR_STG;
        mbar_wait(stg, 0, t0);
        for (int hh = 0; hh < 4; hh++) bulk_store(g_kv + ((size_t)(4 * j + hh) * SEQ + rb * 128) * 64, sbase + OFF_KV + hh * 8192, 8192);
        bulk_commit(); bulk_wait_all();
        flag_add(&g_flag_kv[(rb * 8 + j) * FS]);
        if (!typeB) {
          mbar_wait(bars + 8 * BAR_STE, 0, t0);
          tma_store_2d(&P.tmHO, (24 + (j >> 1)) * 64, rb * 128, sbase + OFF_KV + 32768);
          bulk_commit(); bulk_wait_all();
        }
        mbar_arrive(bars + 8 * BAR_KVOK);
        if (!typeB) flag_add(&g_flag_e[(rb * 8 + j) * FS]);
        mbar_wait(stg, 1, t0);
        for (int i = 0; i < 3; i++) { tma_store_2d(&P.tmHO, (3 * j + i) * 64, rb * 128, sbase + OFF_A + (1 + i) * SLOT); bulk_commit(); }
        asm volatile("cp.async.bulk.wait_group.read 2;" ::: "memory");
        mbar_arrive(bars + 8 * (BAR_EMPTYA + 1));
        asm volatile("cp.async.bulk.wait_group.read 1;" ::: "memory");
        mbar_arrive(bars + 8 * (BAR_EMPTYA + 2));
        bulk_wait_all();
        mbar_arrive(bars + 8 * (BAR_EMPTYA + 3));
        flag_add(&g_flag_h[(rb * 8 + j) * FS]);
        {
          const unsigned old = atomicAdd(&g_done, 1u);
          if (old == gridDim.x - 1) { g_done = 0; *(volatile unsigned*)&g_epoch = ep1; }
        }
        mbar_wait(stg, 0, t0);
        bulk_store(g_part + (size_t)(rb * 8 + (j ^ 1)) * 16384, sbase + OFF_B + ((30 + on) % NB) * SLOT, 16384);
        bulk_commit(); bulk_wait_all();
        flag_add(&g_flag_p[(rb * 8 + (j ^ 1)) * FS]);
      } else if (lane == 0) {
        const int nblk = rb >= 2 ? 3 : rb + 1;
        const uint32_t kvbytes = nblk * 8192;
        const uint8_t* kvsrc = g_kv + ((size_t)(4 * j) * SEQ + (rb + 1 - nblk) * 128) * 64;
        const uint32_t kvdst = sbase + OFF_KV + (3 - nblk) * 8192;
        {
          const unsigned* f0 = &g_flag_kv[(rb * 8 + j) * FS];
          const unsigned* f1 = rb >= 1 ? f0 - 8 * FS : f0;
          const unsigned* f2 = rb >= 2 ? f0 - 16 * FS : f0;
          unsigned v0, v1, v2;
          do { v0 = ld_relaxed(f0); v1 = ld_relaxed(f1); v2 = ld_relaxed(f2); }
          while (((int)(v0 - ep1) < 0 || (int)(v1 - ep1) < 0 || (int)(v2 - ep1) < 0) && clk32() - t0 < TIMEOUT);
        }
        mbar_wait(bars + 8 * BAR_GIN, 0, t0);
        fence_async_global();
        mbar_expect_tx(bars + 8 * BAR_KVFULL, kvbytes);
        bulk_load(kvdst, kvsrc, kvbytes, bars + 8 * BAR_KVFULL);
        mbar_wait(bars + 8 * BAR_KVOK, 0, t0);
        mbar_expect_tx(bars + 8 * (BAR_KVFULL + 1), kvbytes);
        bulk_load(kvdst + KVBUF, kvsrc + (size_t)SEQ * 64, kvbytes, bars + 8 * (BAR_KVFULL + 1));
        for (int hh = 0; hh < 4; hh++) {
          mbar_wait(bars + 8 * (BAR_OST + hh), 0, t0);
          for (int aw = 0; aw < 2; aw++) {
            tma_store_2d(&P.tmOs, DFF + hh * 128 + j * 16, rb * 128 + aw * 64, sbase + OFF_A + aw * 8192 + hh * 2048);
          }
          bulk_commit();
          if (hh < 2) {
            mbar_wait(bars + 8 * (BAR_KVEMPTY + hh), 0, t0);
            mbar_expect_tx(bars + 8 * (BAR_KVFULL + hh), kvbytes);
            bulk_load(kvdst + hh * KVBUF, kvsrc + (size_t)(hh + 2) * SEQ * 64, kvbytes, bars + 8 * (BAR_KVFULL + hh));
          }
          bulk_wait_all();
          flag_add(&g_flag_o[(rb * 8 + hh * 2 + (j >> 2)) * FS]);
        }
      }
    }
  }
}

typedef CUresult (*EncodeFn)(CUtensorMap*, CUtensorMapDataType, cuuint32_t, void*, const cuuint64_t*, const cuuint64_t*, const cuuint32_t*,
                             const cuuint32_t*, CUtensorMapInterleave, CUtensorMapSwizzle, CUtensorMapL2promotion, CUtensorMapFloatOOBfill);

void make_map(EncodeFn enc, CUtensorMap* m, const void* ptr, int rank, const cuuint64_t* dims, const cuuint64_t* strides, const cuuint32_t* box,
              CUtensorMapSwizzle sw = CU_TENSOR_MAP_SWIZZLE_128B) {
  cuuint32_t es[4] = {1, 1, 1, 1};
  enc(m, CU_TENSOR_MAP_DATA_TYPE_BFLOAT16, rank, const_cast<void*>(ptr), dims, strides, box, es, CU_TENSOR_MAP_INTERLEAVE_NONE, sw,
      CU_TENSOR_MAP_L2_PROMOTION_L2_256B, CU_TENSOR_MAP_FLOAT_OOB_FILL_NONE);
}

}

extern "C" void kernel_launch(void* const* d_in, const int* in_sizes, int n_in, void* d_out, int out_size) {
  (void)in_sizes; (void)n_in; (void)out_size;
  static EncodeFn enc = nullptr;
  static void* ho_ptr = nullptr;
  if (!enc) {
    void* fn = nullptr; cudaDriverEntryPointQueryResult st;
    cudaGetDriverEntryPoint("cuTensorMapEncodeTiled", &fn, cudaEnableDefault, &st);
    enc = (EncodeFn)fn;
    cudaGetSymbolAddress(&ho_ptr, g_ho);
    cudaFuncSetAttribute(fused_kernel, cudaFuncAttributeMaxDynamicSharedMemorySize, SMEM_BYTES);
  }
  const __nv_bfloat16* x = (const __nv_bfloat16*)d_in[0];
  const __nv_bfloat16* wqkv = (const __nv_bfloat16*)d_in[1];
  const __nv_bfloat16* wo = (const __nv_bfloat16*)d_in[2];
  const __nv_bfloat16* w1 = (const __nv_bfloat16*)d_in[4];
  const __nv_bfloat16* w2 = (const __nv_bfloat16*)d_in[5];
  const __nv_bfloat16* gate_w = (const __nv_bfloat16*)d_in[6];
  Params P;
  { cuuint64_t d[2] = {DM, SEQ}, s[1] = {DM * 2}; cuuint32_t b[2] = {64, 128}; make_map(enc, &P.tmX, x, 2, d, s, b); }
  { cuuint64_t d[3] = {512, 512, 3}, s[2] = {1536 * 2, 512 * 2}; cuuint32_t b[3] = {64, 16, 3}; make_map(enc, &P.tmWqkv, wqkv, 3, d, s, b); }
  { cuuint64_t d[3] = {64, 512, 28}, s[2] = {DFF * 2, 128}; cuuint32_t b[3] = {64, 16, 1}; make_map(enc, &P.tmW1a, w1, 3, d, s, b);
    b[2] = 3; make_map(enc, &P.tmW1b, w1, 3, d, s, b); }
  { cuuint64_t d[3] = {64, DFF, 8}, s[2] = {DM * 2, 128}; cuuint32_t b[3] = {64, 32, 2}; make_map(enc, &P.tmW2, w2, 3, d, s, b); }
  { cuuint64_t d[4] = {DM, 16, 4, 8}, s[3] = {DM * 2, 16 * DM * 2, 64 * DM * 2}; cuuint32_t b[4] = {64, 16, 1, 4}; make_map(enc, &P.tmWo, wo, 4, d, s, b); }
  { cuuint64_t d[2] = {KHO, SEQ}, s[1] = {KHO * 2}; cuuint32_t b[2] = {64, 128}; make_map(enc, &P.tmHO, ho_ptr, 2, d, s, b);
    b[1] = 64; b[0] = 16; make_map(enc, &P.tmOs, ho_ptr, 2, d, s, b, CU_TENSOR_MAP_SWIZZLE_NONE); }
  P.x = x; P.gate_w = gate_w; P.w1 = w1; P.w2 = w2; P.wo = wo; P.out = (__nv_bfloat16*)d_out;
  fused_kernel<<<128, 640, SMEM_BYTES>>>(P);
}
```
